```python
import torch

def _softmax(x, axis=-1):
    return torch.softmax(x, dim=axis)
def _gelu(x):
    return torch.nn.functional.gelu(x, approximate="tanh")
def _silu(x):
    return torch.nn.functional.silu(x)
def _sigmoid(x):
    return torch.sigmoid(x)
def _layernorm(x, axis=-1, eps=1e-5):
    m = x.mean(dim=axis, keepdim=True)
    v = x.var(dim=axis, keepdim=True, unbiased=False)
    return (x - m) / torch.sqrt(v + eps)
def _scatter_add(tgt, idx, src, axis=0):
    return tgt.clone().index_add_(axis, idx, src)
def _segment_sum(src, seg, n):
    out = torch.zeros((n,) + src.shape[1:], dtype=src.dtype)
    return out.index_add_(0, seg, src)
def _pad(x, pw):
    flat = tuple(v for pair in reversed(pw) for v in pair)
    return torch.nn.functional.pad(x, flat)

kernel_name = 'interleave_layers__sliding_block_cached__glu_gated_swiglu__decode'

def setup_inputs():

    _w = (lambda a: (lambda t: t.to(torch.bfloat16) if t.is_floating_point() else t)(torch.as_tensor(a)))
    def _A_setup():
        B, Sq, D = 1, 1, 640
        Hq, Hkv, Sk, Dh = 32, 32, 32768, 192
        assert Hq % Hkv == 0, (Hq, Hkv)
        return {
            "x": _w((lambda *s: torch.randn(*s, dtype=torch.bfloat16) * 0.05)(B, Sq, D)),
            "k_cache": _w((lambda *s: torch.randn(*s, dtype=torch.bfloat16) * 0.8)(B, Hkv, Sk, Dh)),
            "v_cache": _w((lambda *s: torch.randn(*s, dtype=torch.bfloat16) * 1.6)(B, Hkv, Sk, Dh)),
            "wq": _w((lambda *s: torch.randn(*s, dtype=torch.bfloat16) * 0.8)(D, Hq * Dh) * (D ** -0.5)),
            "wo": _w((lambda *s: torch.randn(*s, dtype=torch.bfloat16) * 1.6)(Hq * Dh, D) * ((Hq * Dh) ** -0.5)),
        }
    _A_in = _A_setup()

    def _B_setup():
        B, S, D, F = 1, 1, 640, 1536
        return {
            "x": _w((lambda *s: torch.randn(*s, dtype=torch.bfloat16) * 0.05)(B, S, D)),
            "w1": _w((lambda *s: torch.randn(*s, dtype=torch.bfloat16) * 0.4)(D, F) * (2.0 / D) ** 0.5),
            "w3": _w((lambda *s: torch.randn(*s, dtype=torch.bfloat16) * 0.4)(D, F) * (2.0 / D) ** 0.5),
            "w2": _w((lambda *s: torch.randn(*s, dtype=torch.bfloat16) * 0.4)(F, D) * (2.0 / F) ** 0.5),
        }
    _B_in = _B_setup()

    return {
        "A_x": _A_in["x"],
        "A_k_cache": _A_in["k_cache"],
        "A_v_cache": _A_in["v_cache"],
        "A_wq": _A_in["wq"],
        "A_wo": _A_in["wo"],
        "B_x": _B_in["x"],
        "B_w1": _B_in["w1"],
        "B_w3": _B_in["w3"],
        "B_w2": _B_in["w2"],
    }

def reference(A_x, A_k_cache, A_v_cache, A_wq, A_wo, B_x, B_w1, B_w3, B_w2):
    def _A_ref(x, k_cache, v_cache, wq, wo):
        B, Sq, D = x.shape
        Hq, Dh = 32, 192
        Hkv, Sk = k_cache.shape[1], k_cache.shape[2]
        W = min(4096, max(256, Sk // 4))
        rep = Hq // Hkv
        q = (lambda x, *d: x.permute(*d))((x @ wq).reshape(B, Sq, Hq, Dh), 0, 2, 1, 3)
        k = (lambda x, n, axis: torch.repeat_interleave(x, n, dim=axis))(k_cache[:, :, Sk - W:, :], rep, axis=1)
        v = (lambda x, n, axis: torch.repeat_interleave(x, n, dim=axis))(v_cache[:, :, Sk - W:, :], rep, axis=1)
        scores = torch.einsum("bhqd,bhkd->bhqk", q, k) * (Dh ** -0.5)
        p = _softmax(scores, axis=-1)
        o = torch.einsum("bhqk,bhkd->bhqd", p, v)
        return (lambda x, *d: x.permute(*d))(o, 0, 2, 1, 3).reshape(B, Sq, Hq * Dh) @ wo

    def _B_ref(x, w1, w3, w2):
        gate = torch.einsum("bsd,df->bsf", x, w1)
        up = torch.einsum("bsd,df->bsf", x, w3)
        h = _silu(gate) * up
        out = torch.einsum("bsf,fd->bsd", h, w2)
        return out

    x = A_x
    x = x + _A_ref(_layernorm(x, axis=-1), A_k_cache, A_v_cache, A_wq, A_wo)
    x = x + _B_ref(_layernorm(x, axis=-1), B_w1, B_w3, B_w2)
    x = x + _A_ref(_layernorm(x, axis=-1), A_k_cache, A_v_cache, A_wq, A_wo)
    x = x + _B_ref(_layernorm(x, axis=-1), B_w1, B_w3, B_w2)
    return x
```

```cpp
#include <cuda_runtime.h>
#include <cuda_bf16.h>
#include <cuda.h>
#include <stdint.h>
#include <math.h>
#include <stdlib.h>

namespace {

constexpr int DM = 640;
constexpr int NH = 32;
constexpr int DH = 192;
constexpr int SK = 32768;
constexpr int WIN = 4096;
constexpr int FF = 1536;
constexpr int NCTA = 128;
constexpr int NT = 256;
constexpr int TILE = 6144;
constexpr int NG = 64;
constexpr int DN0 = 64;
constexpr int NDN = 40;

constexpr int SM_RING = 0;
constexpr int SM_B = 8 * 2 * TILE;
constexpr int SM_Q = SM_B + 61440;
constexpr int SM_XS = SM_Q + 61440;
constexpr int SM_R = SM_XS + 1280;
constexpr int SM_ST = SM_R + 4096;
constexpr int SM_QS = SM_R + 6272;
constexpr int SM_OS = SM_QS + 384;
constexpr int SM_BAR = SM_OS + 384;
constexpr int SM_XBAR = SM_BAR + 24 * 8;
constexpr int SM_MISC = SM_XBAR + 8 * 8;
constexpr int SM_ONE = SM_MISC + 16;
constexpr int SM_ZERO = SM_ONE + 160;
constexpr int SM_TOTAL = SM_ZERO + 160;
static_assert(SM_TOTAL <= 232448, "shared memory");

constexpr unsigned long long POL_EF = 0x12F0000000000000ull;
constexpr unsigned long long POL_EN = 0x1000000000000000ull;

#define RT_MASK 0x2DE0u
#define RT_MASK2 0x36E0u
#define RESET_AT 14
#define WO_AT 15
#define WO_AT1 7
#define FFN_PROMO CU_TENSOR_MAP_L2_PROMOTION_NONE
#define FFN_POL POL_EF
#define HAS_FFN (__float_as_uint(misc[1]) < DN0 + NDN)
#define ACC_STR 2
#define NPRE 6

#define SCHED 1
#define WPRE 0
#define NWPRE 0
#define L1R 3
#define PRE1 5
#define HOLD 3
#define DNTH 23
#define KEEP4 1
#define XCH(w) ((0x83765210u >> (4 * (w))) & 15u)
#define LAYOUT 1
#define ROW0(w) ((h * SK + (SK - WIN) + c * 1024 + (w) * 128) * 3)
constexpr int TS = 48;
constexpr int SPIN_CAP = 1 << 19;
constexpr uint32_t ONES = 0x3F803F80u;

struct Scratch {
    uint4 qx[NCTA * 48];
    uint4 cx[NCTA * 56];
    uint4 pad0[32 * 5 * 32 + 160];
    uint4 acc[2][216 * 8];
    uint4 ay[160];
    uint4 ah[NG * 8];
    uint2 mx[NH * 32];
    uint32_t ticket[32];
    uint32_t pad1[32];
};
__device__ Scratch g_scr;
#define PROF_T(i)
#define PROF_D(i)
#define PROF_X(i)
#define PC(i)

__device__ __forceinline__ uint32_t smem_u32(const void* p) { return (uint32_t)__cvta_generic_to_shared(p); }
__device__ __forceinline__ void mbar_init(uint32_t bar, uint32_t cnt) {
    asm volatile("mbarrier.init.shared::cta.b64 [%0], %1;" ::"r"(bar), "r"(cnt) : "memory");
}
__device__ __forceinline__ void mbar_expect_tx(uint32_t bar, uint32_t bytes) {
    asm volatile("mbarrier.arrive.expect_tx.shared::cta.b64 _, [%0], %1;" ::"r"(bar), "r"(bytes) : "memory");
}
__device__ __forceinline__ bool mbar_test(uint32_t bar, uint32_t parity) {
    uint32_t done;
    asm volatile("{\n.reg .pred p;\nmbarrier.try_wait.parity.shared::cta.b64 p, [%1], %2;\nselp.u32 %0, 1, 0, p;\n}"
                 : "=r"(done) : "r"(bar), "r"(parity) : "memory");
    return done;
}
__device__ __forceinline__ void mbar_wait(uint32_t bar, uint32_t parity) {
    int it = 0;
    while (!mbar_test(bar, parity) && ++it < SPIN_CAP) {}
}
__device__ __forceinline__ void tma2d(uint32_t dst, const CUtensorMap* map, int c0, int c1, uint32_t bar, unsigned long long pol) {
    asm volatile("cp.async.bulk.tensor.2d.shared::cluster.global.mbarrier::complete_tx::bytes.L2::cache_hint [%0], [%1, {%3, %4}], [%2], %5;"
                 ::"r"(dst), "l"(map), "r"(bar), "r"(c0), "r"(c1), "l"(pol) : "memory");
}
__device__ __forceinline__ void tma3d(uint32_t dst, const CUtensorMap* map, int c0, int c1, int c2, uint32_t bar, unsigned long long pol) {
    asm volatile("cp.async.bulk.tensor.3d.shared::cluster.global.mbarrier::complete_tx::bytes.L2::cache_hint [%0], [%1, {%3, %4, %5}], [%2], %6;"
                 ::"r"(dst), "l"(map), "r"(bar), "r"(c0), "r"(c1), "r"(c2), "l"(pol) : "memory");
}
__device__ __forceinline__ void tma4d(uint32_t dst, const CUtensorMap* map, int c2, int c3, uint32_t bar, unsigned long long pol) {
    asm volatile("cp.async.bulk.tensor.4d.shared::cluster.global.mbarrier::complete_tx::bytes.L2::cache_hint [%0], [%1, {0, 0, %3, %4}], [%2], %5;"
                 ::"r"(dst), "l"(map), "r"(bar), "r"(c2), "r"(c3), "l"(pol) : "memory");
}
__device__ __forceinline__ void tma2d_pf(const CUtensorMap* map, int c0, int c1, unsigned long long pol) {
    asm volatile("cp.async.bulk.prefetch.tensor.2d.L2.global.L2::cache_hint [%0, {%1, %2}], %3;" ::"l"(map), "r"(c0), "r"(c1), "l"(pol) : "memory");
}
__device__ __forceinline__ void tile_load(uint32_t dst, const CUtensorMap* map, int row, uint32_t bar) {
    asm volatile("{\n.reg .pred p;\nelect.sync _|p, 0xffffffff;\n"
                 "@p mbarrier.arrive.expect_tx.shared::cta.b64 _, [%2], 6144;\n"
                 "@p cp.async.bulk.tensor.2d.shared::cluster.global.mbarrier::complete_tx::bytes.L2::cache_hint [%0], [%1, {0, %3}], [%2], %4;\n}"
                 ::"r"(dst), "l"(map), "r"(bar), "r"(row), "l"(POL_EF) : "memory");
}
__device__ __forceinline__ void tile_keep(const CUtensorMap* map, int row) {
    asm volatile("{\n.reg .pred p;\nelect.sync _|p, 0xffffffff;\n"
                 "@p cp.async.bulk.prefetch.tensor.2d.L2.global.L2::cache_hint [%0, {0, %1}], %2;\n}"
                 ::"l"(map), "r"(row), "l"(POL_EN) : "memory");
}
__device__ __forceinline__ void tile_load_l1(uint32_t dst, const void* base, int row, uint32_t bar, int lane) {
    const char* g = static_cast<const char*>(base) + (size_t)row * 128 + lane * 16;
    const uint32_t s0 = dst + (lane >> 3) * 128 + (((lane & 7) ^ (lane >> 3)) << 4), s1 = s0 ^ 64;
#pragma unroll
    for (int k = 0; k < 12; k++)
        asm volatile("cp.async.ca.shared.global.L2::cache_hint [%0], [%1], 16, %2;" ::"r"(((k & 1) ? s1 : s0) + k * 512), "l"(g + k * 512), "l"(POL_EF) : "memory");
    asm volatile("cp.async.mbarrier.arrive.shared::cta.b64 [%0];" ::"r"(bar) : "memory");
    __syncwarp();
    if (lane == 0) asm volatile("mbarrier.arrive.shared::cta.b64 _, [%0];" ::"r"(bar) : "memory");
}
__device__ __forceinline__ bool elect_one() {
    uint32_t p;
    asm volatile("{\n.reg .pred p;\nelect.sync _|p, 0xffffffff;\nselp.u32 %0, 1, 0, p;\n}" : "=r"(p));
    return p;
}
__device__ __forceinline__ void lds128(uint32_t addr, uint32_t& a, uint32_t& b, uint32_t& c, uint32_t& d) {
    asm volatile("ld.shared.v4.u32 {%0,%1,%2,%3}, [%4];" : "=r"(a), "=r"(b), "=r"(c), "=r"(d) : "r"(addr) : "memory");
}
__device__ __forceinline__ void lds64(uint32_t addr, uint32_t& a, uint32_t& b) {
    asm volatile("ld.shared.v2.u32 {%0,%1}, [%2];" : "=r"(a), "=r"(b) : "r"(addr) : "memory");
}
__device__ __forceinline__ void ldsm4t(uint32_t addr, uint32_t (&a)[4]) {
    asm volatile("ldmatrix.sync.aligned.m8n8.x4.trans.shared.b16 {%0,%1,%2,%3}, [%4];" : "=r"(a[0]), "=r"(a[1]), "=r"(a[2]), "=r"(a[3]) : "r"(addr) : "memory");
}
__device__ __forceinline__ void mma16816(float (&c)[4], uint32_t a0, uint32_t a1, uint32_t a2, uint32_t a3, uint32_t b0, uint32_t b1) {
    asm("mma.sync.aligned.m16n8k16.row.col.f32.bf16.bf16.f32 {%0,%1,%2,%3}, {%4,%5,%6,%7}, {%8,%9}, {%0,%1,%2,%3};"
        : "+f"(c[0]), "+f"(c[1]), "+f"(c[2]), "+f"(c[3]) : "r"(a0), "r"(a1), "r"(a2), "r"(a3), "r"(b0), "r"(b1));
}
__device__ __forceinline__ void mma16816v(float (&c)[4], uint32_t a0, uint32_t a1, uint32_t a2, uint32_t a3, uint32_t b0, uint32_t b1) {
    asm volatile("mma.sync.aligned.m16n8k16.row.col.f32.bf16.bf16.f32 {%0,%1,%2,%3}, {%4,%5,%6,%7}, {%8,%9}, {%0,%1,%2,%3};"
        : "+f"(c[0]), "+f"(c[1]), "+f"(c[2]), "+f"(c[3]) : "r"(a0), "r"(a1), "r"(a2), "r"(a3), "r"(b0), "r"(b1));
}
__device__ __forceinline__ int xpos(int w) {
    const int seg = w / 40, r = w - 40 * seg;
    return 40 * seg + (r < 32 ? (r & 16) + 4 * (r & 3) + ((r >> 2) & 3) : 32 + 2 * (r & 3) + ((r >> 2) & 1));
}
#define NA_LD ""
#define NA_ST ""
__device__ __forceinline__ void st_pkt(uint4* p, uint32_t a, uint32_t b, uint32_t c, uint32_t d) {
    asm volatile("{\n.reg .b128 t;\n.reg .b64 lo, hi;\nmov.b64 lo, {%1,%2};\nmov.b64 hi, {%3,%4};\nmov.b128 t, {lo,hi};\nst.relaxed.gpu.global" NA_ST ".b128 [%0], t;\n}"
                 ::"l"(p), "r"(a), "r"(b), "r"(c), "r"(d) : "memory");
}
__device__ __forceinline__ void st_pktf(uint4* p, float a, float b, float c, float d, uint32_t bit) {
    st_pkt(p, __float_as_uint(a), __float_as_uint(b), __float_as_uint(c), (__float_as_uint(d) & ~1u) | bit);
}
__device__ __forceinline__ void red_pkt(uint4* p, float a, float b, float c) {
    asm volatile("red.relaxed.gpu.global.add.v4.f32 [%0], {%1,%2,%3,%4};" ::"l"(p), "f"(a), "f"(b), "f"(c), "f"(1.0f) : "memory");
}
__device__ __forceinline__ uint4 ld_pkt(const uint4* p) {
    uint4 v;
    asm volatile("{\n.reg .b128 t;\n.reg .b64 lo, hi;\nld.relaxed.gpu.global" NA_LD ".b128 t, [%4];\nmov.b128 {lo,hi}, t;\nmov.b64 {%0,%1}, lo;\nmov.b64 {%2,%3}, hi;\n}"
                 : "=r"(v.x), "=r"(v.y), "=r"(v.z), "=r"(v.w) : "l"(p) : "memory");
    return v;
}
__device__ __forceinline__ uint2 ld_pkt2(const uint2* p) {
    unsigned long long v;
    asm volatile("ld.relaxed.gpu.global" NA_LD ".b64 %0, [%1];" : "=l"(v) : "l"(p) : "memory");
    return make_uint2((uint32_t)v, (uint32_t)(v >> 32));
}
__device__ __forceinline__ void st_pkt2(uint2* p, uint32_t a, uint32_t b) {
    asm volatile("st.relaxed.gpu.global" NA_ST ".b64 [%0], %1;" ::"l"(p), "l"((unsigned long long)a | ((unsigned long long)b << 32)) : "memory");
}
__device__ __forceinline__ float ex2(float x) { float y; asm("ex2.approx.ftz.f32 %0, %1;" : "=f"(y) : "f"(x)); return y; }
__device__ __forceinline__ float rcp(float x) { float y; asm("rcp.approx.ftz.f32 %0, %1;" : "=f"(y) : "f"(x)); return y; }
__device__ __forceinline__ uint32_t pack2(float lo, float hi) {
    uint32_t r; asm("cvt.rn.bf16x2.f32 %0, %1, %2;" : "=r"(r) : "f"(hi), "f"(lo)); return r;
}
__device__ __forceinline__ float bf_lo(uint32_t w) { return __uint_as_float(w << 16); }
__device__ __forceinline__ float bf_hi(uint32_t w) { return __uint_as_float(w & 0xffff0000u); }
__device__ __forceinline__ float bfr(float x) { return bf_lo(pack2(x, 0.f)); }
__device__ __forceinline__ float f_(uint32_t u) { return __uint_as_float(u); }

__device__ __forceinline__ void ln_stats(const unsigned char* smem, float& mean, float& inv) {
    const float4* st = reinterpret_cast<const float4*>(smem + SM_ST);
    const float4 a = st[0], b = st[1], c = st[2], d = st[3];
    const float s2 = ((a.x + a.z) + (b.x + b.z)) + ((c.x + c.z) + (d.x + d.z));
    const float md = (((a.y + a.w) + (b.y + b.w)) + ((c.y + c.w) + (d.y + d.w))) * (1.0f / DM);
    const float var = fmaxf(s2 * (1.0f / DM) - md * md, 0.f);
    mean = bfr(md);
    asm("rsqrt.approx.ftz.f32 %0, %1;" : "=f"(inv) : "f"(var + 1e-5f));
}
template <int SK, bool PRE3, typename AddrF>
__device__ __forceinline__ void gemv15(float (&cc)[3][4], uint32_t (&pre)[6][4], uint32_t (&a)[3][4], AddrF ad, uint32_t px, uint32_t px2, float& sv, float so) {
    uint32_t x0[4], x1[4];
    lds128(px, x0[0], x0[1], x0[2], x0[3]);
    lds128(px + 64, x1[0], x1[1], x1[2], x1[3]);
    if (!PRE3) {
#pragma unroll
        for (int i = 0; i < 3; i++) ldsm4t(ad(i) + 2 * SK, a[i]);
    }
    __syncwarp();
    sv += __shfl_xor_sync(0xffffffffu, so, 16);
#pragma unroll
    for (int i = 0; i < 3; i++) {
        cc[i][0] = cc[i][1] = cc[i][2] = cc[i][3] = 0.f;
        mma16816v(cc[i], pre[i][0], pre[i][1], pre[i][2], pre[i][3], x0[0], x0[1]);
    }
    sv += __shfl_xor_sync(0xffffffffu, sv, 8);
#pragma unroll
    for (int i = 0; i < 3; i++) {
        mma16816v(cc[i], pre[3 + i][0], pre[3 + i][1], pre[3 + i][2], pre[3 + i][3], x0[2], x0[3]);
        ldsm4t(ad(i) + 3 * SK, pre[i]);
    }
    lds64(px2, x0[0], x0[1]);
    __syncwarp();
    sv += __shfl_xor_sync(0xffffffffu, sv, 4);
#pragma unroll
    for (int i = 0; i < 3; i++) {
        mma16816v(cc[i], a[i][0], a[i][1], a[i][2], a[i][3], x1[0], x1[1]);
        ldsm4t(ad(i) + 4 * SK, pre[3 + i]);
    }
    __syncwarp();
    sv += __shfl_xor_sync(0xffffffffu, sv, 2);
#pragma unroll
    for (int i = 0; i < 3; i++) mma16816v(cc[i], pre[i][0], pre[i][1], pre[i][2], pre[i][3], x1[2], x1[3]);
    sv += __shfl_xor_sync(0xffffffffu, sv, 1);
#pragma unroll
    for (int i = 0; i < 3; i++) mma16816v(cc[i], pre[3 + i][0], pre[3 + i][1], pre[3 + i][2], pre[3 + i][3], x0[0], x0[1]);
}
__device__ __forceinline__ void gemv15r(float (&cc)[3][4], const uint32_t (&pre)[6][4], const uint32_t (&ext)[12][4], uint32_t px, uint32_t px2, float& sv, float so) {
    uint32_t x0[4], x1[4], x2[2];
    float cd[3][4];
    lds128(px, x0[0], x0[1], x0[2], x0[3]);
    lds128(px + 64, x1[0], x1[1], x1[2], x1[3]);
    lds64(px2, x2[0], x2[1]);
    sv += __shfl_xor_sync(0xffffffffu, so, 16);
#pragma unroll
    for (int i = 0; i < 3; i++) {
        cc[i][0] = cc[i][1] = cc[i][2] = cc[i][3] = cd[i][0] = cd[i][1] = cd[i][2] = cd[i][3] = 0.f;
        mma16816v(cc[i], pre[i][0], pre[i][1], pre[i][2], pre[i][3], x0[0], x0[1]);
        mma16816v(cd[i], pre[3 + i][0], pre[3 + i][1], pre[3 + i][2], pre[3 + i][3], x0[2], x0[3]);
    }
    sv += __shfl_xor_sync(0xffffffffu, sv, 8);
#pragma unroll
    for (int i = 0; i < 3; i++) {
        mma16816v(cc[i], ext[i][0], ext[i][1], ext[i][2], ext[i][3], x1[0], x1[1]);
        mma16816v(cd[i], ext[3 + i][0], ext[3 + i][1], ext[3 + i][2], ext[3 + i][3], x1[2], x1[3]);
    }
    sv += __shfl_xor_sync(0xffffffffu, sv, 4);
#pragma unroll
    for (int i = 0; i < 3; i++) mma16816v(cc[i], ext[6 + i][0], ext[6 + i][1], ext[6 + i][2], ext[6 + i][3], x2[0], x2[1]);
    sv += __shfl_xor_sync(0xffffffffu, sv, 2);
    sv += __shfl_xor_sync(0xffffffffu, sv, 1);
#pragma unroll
    for (int i = 0; i < 3; i++) { cc[i][0] += cd[i][0]; cc[i][1] += cd[i][1]; cc[i][2] += cd[i][2]; cc[i][3] += cd[i][3]; }
}

__device__ __forceinline__ int opq(int x) { asm volatile("" : "+r"(x)); return x; }
__device__ __forceinline__ uint32_t opq(uint32_t x) { asm volatile("" : "+r"(x)); return x; }
__device__ __forceinline__ void sts32(uint32_t a, float v) { asm volatile("st.shared.f32 [%0], %1;" ::"r"(a), "f"(v) : "memory"); }
__device__ __forceinline__ void sts64(uint32_t a, float v, float w) { asm volatile("st.shared.v2.f32 [%0], {%1,%2};" ::"r"(a), "f"(v), "f"(w) : "memory"); }

struct Maps { CUtensorMap k, v, wq, wo, w1, w3, w2, ks, vs; const void* vp; };
#define RT_SEL ((wu & 1) ? RT_MASK2 : RT_MASK)
#define K4D_G 0
#define K4D_R 1500
#define PWA -1
#define PWS 0
#define PWP 0
#define K4LATE 0

__device__ __forceinline__ void load_ffn(const Maps& maps, int b, uint32_t dst, uint32_t bar) {
    const bool gu = b < NG;
    mbar_expect_tx(bar, gu ? 61440 : 49152);
    tma3d(dst, gu ? (b < NG / 2 ? &maps.w1 : &maps.w3) : &maps.w2, gu ? 48 * (b & (NG / 2 - 1)) : 16 * (b - DN0), 0, 0, bar, FFN_POL);
}

__device__ __forceinline__ void load_wo(const Maps& maps, uint32_t dst, int h, int c, uint32_t bar, int nbox) {
#pragma unroll 1
    for (int i = 0; i < nbox; i++) {
        mbar_expect_tx(bar + 8 * i, 12288);
        tma3d(dst + i * 12288, &maps.wo, 0, h * DH, 5 * c + i, bar + 8 * i, POL_EF);
    }
}

__global__ void __launch_bounds__(NT, 1)
decode_kernel(const __grid_constant__ Maps maps, const __nv_bfloat16* __restrict__ x_in, __nv_bfloat16* __restrict__ out) {
    extern __shared__ __align__(1024) unsigned char smem[];
    const int tid = threadIdx.x, warp = tid >> 5, lane = tid & 31;
    const int wu = __shfl_sync(0xffffffffu, tid >> 5, 0);
    const int b = blockIdx.x, h = b >> 2, c = b & 3;
    const uint32_t sb = smem_u32(smem);
    const uint32_t rbar = sb + SM_BAR + warp * 16;
    const uint32_t xbar = sb + SM_XBAR + warp * 8;
    const uint32_t qbar = sb + SM_BAR + 16 * 8, fbar = qbar + 8, wbar = qbar + 16;
    uint32_t* xs32 = reinterpret_cast<uint32_t*>(smem + SM_XS);
    float* rr = reinterpret_cast<float*>(smem + SM_R);
    uint32_t* qs32 = reinterpret_cast<uint32_t*>(smem + SM_QS);
    uint32_t* os32 = reinterpret_cast<uint32_t*>(smem + SM_OS);
    float* misc = reinterpret_cast<float*>(smem + SM_MISC);

    PROF_T(0);
    if (lane == 0) {
        mbar_init(rbar, 1); mbar_init(rbar + 8, 1); mbar_init(xbar, 1);
        if (warp == 0) {
            mbar_init(qbar, 1); mbar_init(fbar, 1);
#pragma unroll
            for (int i = 0; i < 5; i++) mbar_init(wbar + 8 * i, 1);
            asm volatile("fence.mbarrier_init.release.cluster;" ::: "memory");
            mbar_expect_tx(qbar, 61440);
            tma4d(sb + SM_Q, &maps.wq, 3 * h, 10 * c, qbar, POL_EF);
        }
        asm volatile("fence.mbarrier_init.release.cluster;" ::: "memory");
        if (warp >= 1 && warp < 7) {
            const CUtensorMap* mp = warp == 1 ? &maps.k : warp == 2 ? &maps.v : warp == 3 ? &maps.wo : warp == 4 ? &maps.w1 : warp == 5 ? &maps.w3 : &maps.w2;
            asm volatile("prefetch.tensormap [%0];" ::"l"(mp) : "memory");
        }
    }
    if (tid == 96) misc[2] = 0.f;
    if (tid >= 128 && tid < 148) {
        const uint32_t v = tid < 138 ? ONES : 0u;
        reinterpret_cast<uint4*>(smem + SM_ONE)[tid - 128] = make_uint4(v, v, v, v);
    }
    if (b == 0 && tid == 255) asm volatile("st.relaxed.gpu.global.u32 [%0], %1;" ::"l"(g_scr.ticket), "r"(0) : "memory");
    if (tid < 52) st_pkt(tid < 48 ? &g_scr.qx[b * 48 + tid] : reinterpret_cast<uint4*>(&g_scr.mx[h * 32 + c * 8]) + (tid - 48), 0, 0, 0, 0);
    if (tid >= 64 && tid < 66 && b < 108) st_pkt(&g_scr.acc[1][(2 * b + tid - 64) * ACC_STR], 0, 0, 0, 0);
    __syncthreads();
    PROF_D(14);
    if (lane == 0) {
        const int row = ROW0(warp);
        mbar_expect_tx(rbar, TILE);
        tma2d(sb + SM_RING + warp * 2 * TILE, &maps.k, 0, row, rbar, POL_EF);
        mbar_expect_tx(rbar + 8, TILE);
        tma2d(sb + SM_RING + (warp * 2 + 1) * TILE, &maps.k, 0, row + TS, rbar + 8, POL_EF);
    }

    uint32_t kr[4][12][4];
    const float SC = 0.07216878364870322f * 1.4426950408889634f;

#pragma unroll 1
    for (int layer = 0; layer < 2; layer++) {
        const uint32_t tag = layer + 1, tbit = layer ^ 1;
        PROF_D(1 + layer * 16);
        {
            const int tl = opq(tid), warp = tl >> 5, lane = tl & 31, g = lane >> 2, t = lane & 3, mat = lane >> 3, r8 = lane & 7;
            const int kh = warp >> 2, mg = warp & 3;
            const uint32_t aq = sb + SM_Q + kh * 5 * TILE + ((mat >> 1) * 8 + r8) * 128 + (((2 * mg + (mat & 1)) ^ r8) << 4);
#define PF_K4 if (layer == 1 && lane == 0 && warp >= 6) tma2d_pf(&maps.k, 0, ROW0(warp) + 4 * TS, POL_EN);
            uint2 xv = make_uint2(0u, 0u);
            if (layer == 0 && tl < 160) xv = reinterpret_cast<const uint2*>(x_in)[tl];
            mbar_wait(qbar, 0);
            uint32_t pre[6][4], pr2[3][4];
#pragma unroll
            for (int n = 0; n < 6; n++) ldsm4t(aq + (n % 3) * 2048 + (n / 3) * TILE, pre[n]);
#pragma unroll
            for (int n = 0; n < 3; n++) ldsm4t(aq + n * 2048 + 2 * TILE, pr2[n]);
            const bool late = K4LATE && __float_as_uint(misc[1]) - DN0 < NDN;
            if (layer == 1 && !late) {
                __syncthreads();
                const int row = ROW0(wu) + 4 * TS;
                if (K4D_G | K4D_R) {
                    const uint32_t role = __float_as_uint(misc[1]), d = role < NG ? K4D_G : role >= DN0 + NDN ? K4D_R : 0;
                    uint32_t t0, t1; asm volatile("mov.u32 %0, %%clock;" : "=r"(t0));
                    do asm volatile("mov.u32 %0, %%clock;" : "=r"(t1)); while (t1 - t0 < d);
                }
                if (wu < 6) tile_load(sb + SM_Q + XCH(wu) * TILE, &maps.k, row, sb + SM_XBAR + wu * 8);
            }
            const uint32_t pm = opq(g == 1 ? sb + SM_ONE : sb + SM_XS + 160 * (2 * c + kh) + 16 * t), pm2 = opq(pm + 128 - (g == 1 ? 0 : 8 * t));
            const uint32_t dq = opq(sb + SM_R + 8 * (kh * 192 + 16 * mg + g)), ds = opq(sb + SM_ST + 8 * warp + (lane < 16 ? 4 : 0));
            const bool wr = t == 0, ws = (lane & 15) == 0, lo = lane < 16;
            if (tl < 160) {
                const int p0 = xpos(2 * tl), p1 = xpos(2 * tl + 1);
                if (layer == 1) {
                    uint4 v;
                    int it = 0;
                    do { v = ld_pkt(&g_scr.ay[tl]); } while (!__all_sync(0xffffffffu, v.w == 1) && ++it < SPIN_CAP);
                    xv = make_uint2(v.x, v.y);
                }
                xs32[p0] = xv.x; xs32[p1] = xv.y;
            }
            if (layer) PC(24);
            __syncthreads();
            if (layer == 1 && late && wu < 6) tile_load(sb + SM_Q + XCH(wu) * TILE, &maps.k, ROW0(wu) + 4 * TS, sb + SM_XBAR + wu * 8);
            PF_K4
            if (layer) PC(25);
            if (layer == 1 && tl >= 192 && tl < 194 && b < 108) st_pkt(&g_scr.acc[0][(2 * b + tl - 192) * ACC_STR], 0, 0, 0, 0);
            PROF_T(13 + layer * 16);
            const float e0 = bf_lo(xv.x), e1 = bf_hi(xv.x), e2 = bf_lo(xv.y), e3 = bf_hi(xv.y);
            const float s1 = (e0 + e1) + (e2 + e3), s2 = (e0 * e0 + e1 * e1) + (e2 * e2 + e3 * e3);
            float sv = lo ? s1 : s2, cc[3][4];
            gemv15<TILE, true>(cc, pre, pr2, [&](int i) { return aq + i * 2048; }, pm, pm2, sv, lo ? s2 : s1);
            if (wr) {
#pragma unroll
                for (int i = 0; i < 3; i++) { sts64(dq + 512 * i, cc[i][0], cc[i][1]); sts64(dq + 512 * i + 64, cc[i][2], cc[i][3]); }
            }
            if (ws) sts32(ds, sv);
        }
        if (layer) PC(26);
        __syncthreads();
        if (layer) PC(27);
        PROF_D(33 + layer * 16);
        if (layer == 1 && wu >= 6) tile_load(sb + SM_Q + XCH(wu) * TILE, &maps.k, ROW0(wu) + 4 * TS, sb + SM_XBAR + wu * 8);
        if (tid < 48) {
            const int tid = opq(threadIdx.x);
            float mean, inv;
            ln_stats(smem, mean, inv);
            const float4* p = reinterpret_cast<const float4*>(rr) + 2 * tid;
            const float4 a0 = p[0], a1 = p[1], b0 = p[96], b1 = p[97];
            float q0 = inv * ((a0.x + b0.x) - mean * (a0.y + b0.y)), q1 = inv * ((a0.z + b0.z) - mean * (a0.w + b0.w));
            float q2 = inv * ((a1.x + b1.x) - mean * (a1.y + b1.y)), q3 = inv * ((a1.z + b1.z) - mean * (a1.w + b1.w));
            st_pktf(&g_scr.qx[b * 48 + tid], q0, q1, q2, q3, tbit);
        }
        if (layer) PC(28);

        float sc0 = -INFINITY, sc1 = -INFINITY, sc2 = 0.f, sc3 = 0.f, mw;
        uint32_t pk0, pk1;
        float acc[3][4];
        {
            const uint32_t ring = sb + SM_RING + wu * 2 * TILE, rb = sb + SM_BAR + wu * 16;
            const uint32_t xtile = sb + SM_Q + XCH(wu) * TILE, xb = sb + SM_XBAR + wu * 8;
            const int row0 = ROW0(wu);
            auto issue1 = [&](int n, bool vph = false) {
                const CUtensorMap* mp = n < 8 ? &maps.k : &maps.v;
                const int row = row0 + ((n + (n >= 8 ? 2 : 0)) & 7) * TS;
                if (vph && wu < L1R && n == 12 - (wu & 1)) {
                    tile_load_l1(ring + (n & 1) * TILE, maps.vp, row, rb + (n & 1) * 8, opq(tid) & 31);
                    return;
                }
                tile_load(ring + (n & 1) * TILE, mp, row, rb + (n & 1) * 8);
                if ((RT_SEL >> n) & 1) tile_keep(n < 8 ? &maps.ks : &maps.vs, row);
            };
            auto refill1 = [&](int s, bool vph = false) { issue1(s + 2, vph); };
#define K_OFF(i) ((uint32_t)((3 * ((g >> 1) + 4 * (g & 1)) + ((i) >> 1)) * 128 + ((t ^ ((3 * ((g >> 1) + 4 * (g & 1)) + ((i) >> 1)) & 7) ^ (((i) & 1) << 2)) << 4)))
#define V_OFF(i) ((uint32_t)((6 * t + (i)) * 128 + ((g ^ ((6 * t + (i)) & 7)) << 4)))
#define LANE_IDS const int tl = opq(tid), lane = tl & 31, g = lane >> 2, t = lane & 3; (void)tl; (void)lane; (void)g; (void)t;
            if (layer == 0) {
                LANE_IDS
#pragma unroll
                for (int s = 0; s < 4; s++) {
                    mbar_wait(rb + (s & 1) * 8, (s >> 1) & 1);
                    if (s == 0) PROF_D(52);
                    if (s == 3) PROF_D(53);
#pragma unroll
                    for (int i = 0; i < 6; i++) {
                        const uint32_t a = ring + (s & 1) * TILE + K_OFF(i);
                        lds128(a, kr[s][i][0], kr[s][i][1], kr[s][i][2], kr[s][i][3]);
                        lds128(a + 3072, kr[s][6 + i][0], kr[s][6 + i][1], kr[s][6 + i][2], kr[s][6 + i][3]);
                    }
                    __syncwarp();
                    refill1(s);
                }
            }
            {
                const int tl = opq(tid);
                if (tl < 48) {
                    uint4 v[4];
                    int it = 0;
                    bool ok;
                    do {
#pragma unroll
                        for (int k = 0; k < 4; k++) v[k] = ld_pkt(&g_scr.qx[(h * 4 + k) * 48 + tl]);
                        ok = ((v[0].w ^ tbit) | (v[1].w ^ tbit) | (v[2].w ^ tbit) | (v[3].w ^ tbit)) & 1;
                    } while (ok && ++it < SPIN_CAP);
                    const int w = 2 * tl, pos = ((w >> 2) & 3) * 24 + 2 * (w >> 4) + ((w >> 1) & 1);
                    qs32[pos] = pack2((f_(v[0].x) + f_(v[1].x)) + (f_(v[2].x) + f_(v[3].x)), (f_(v[0].y) + f_(v[1].y)) + (f_(v[2].y) + f_(v[3].y)));
                    qs32[pos + 12] = pack2((f_(v[0].z) + f_(v[1].z)) + (f_(v[2].z) + f_(v[3].z)), (f_(v[0].w) + f_(v[1].w)) + (f_(v[2].w) + f_(v[3].w)));
                }
            }
            if (layer) PC(29);
            __syncthreads();
            if (layer) PC(30);
            PROF_T(2 + layer * 16);
            {
                uint32_t qf[12];
                int t;
                {
                    const int lane = opq(tid) & 31;
                    t = lane & 3;
                    const uint32_t qa = sb + SM_QS + (2 * t + ((lane >> 2) & 1)) * 48;
#pragma unroll
                    for (int i = 0; i < 3; i++) lds128(qa + 16 * i, qf[4 * i], qf[4 * i + 1], qf[4 * i + 2], qf[4 * i + 3]);
                }
#define KR_SCORES(T0) { \
                _Pragma("unroll") for (int tau = T0; tau < T0 + 2; tau++) { \
                    float cA[4] = {0.f, 0.f, 0.f, 0.f}, cB[4] = {0.f, 0.f, 0.f, 0.f}; \
                    _Pragma("unroll") for (int i = 0; i < 6; i++) { \
                        mma16816(cA, kr[tau][i][0], kr[tau][i][1], kr[tau][i][2], kr[tau][i][3], qf[2 * i], qf[2 * i + 1]); \
                        mma16816(cB, kr[tau][6 + i][0], kr[tau][6 + i][1], kr[tau][6 + i][2], kr[tau][6 + i][3], qf[2 * i], qf[2 * i + 1]); \
                    } \
                    if (t == tau) { sc0 = cA[0] + cA[3]; sc1 = cB[0] + cB[3]; } \
                } }
                if (layer == 1) {
                    LANE_IDS
                    mbar_wait(xb, 0);
                    PROF_D(34);
                    float cA[4] = {0.f, 0.f, 0.f, 0.f}, cB[4] = {0.f, 0.f, 0.f, 0.f};
#pragma unroll
                    for (int i = 0; i < 6; i++) {
                        uint32_t a0, a1, a2, a3;
                        lds128(xtile + K_OFF(i), a0, a1, a2, a3);
                        mma16816(cA, a0, a1, a2, a3, qf[2 * i], qf[2 * i + 1]);
                        lds128(xtile + K_OFF(i) + 3072, a0, a1, a2, a3);
                        mma16816(cB, a0, a1, a2, a3, qf[2 * i], qf[2 * i + 1]);
                    }
                    __syncwarp();
                    tile_load(xtile, &maps.k, row0 + 5 * TS, xb);
                    sc2 = cA[0] + cA[3]; sc3 = cB[0] + cB[3];
                }
                KR_SCORES(0)
                if (layer == 1) {
                    const int lane = opq(tid) & 31, g = lane >> 2, t = lane & 3;
#pragma unroll
                    for (int s = 0; s < 2; s++) {
#pragma unroll
                        for (int i = 0; i < 6; i++) {
                            const uint32_t a = ring + s * TILE + V_OFF(i);
                            lds128(a, kr[s][i][0], kr[s][i][1], kr[s][i][2], kr[s][i][3]);
                            lds128(a + 3072, kr[s][6 + i][0], kr[s][6 + i][1], kr[s][6 + i][2], kr[s][6 + i][3]);
                        }
                        __syncwarp();
                        tile_load(ring + s * TILE, &maps.k, row0 + (6 + s) * TS, rb + s * 8);
                    }
                }
                KR_SCORES(2)
#undef KR_SCORES
                if (layer == 0) {
                    LANE_IDS
#pragma unroll 1
                    for (int s = 4; s < 8; s++) {
                        mbar_wait(rb + (s & 1) * 8, (s >> 1) & 1);
                        const uint32_t tile = ring + (s & 1) * TILE;
                        float cA[4] = {0.f, 0.f, 0.f, 0.f}, cB[4] = {0.f, 0.f, 0.f, 0.f};
#pragma unroll
                        for (int i = 0; i < 6; i++) {
                            uint32_t a0, a1, a2, a3;
                            lds128(tile + K_OFF(i), a0, a1, a2, a3);
                            mma16816(cA, a0, a1, a2, a3, qf[2 * i], qf[2 * i + 1]);
                            lds128(tile + K_OFF(i) + 3072, a0, a1, a2, a3);
                            mma16816(cB, a0, a1, a2, a3, qf[2 * i], qf[2 * i + 1]);
                        }
                        if (t == (s & 3)) { sc2 = cA[0] + cA[3]; sc3 = cB[0] + cB[3]; }
                        __syncwarp();
                        refill1(s);
                    }
                } else {
                    LANE_IDS
#pragma unroll 1
                    for (int i = 1; i < 4; i++) {
                        const int sl = i - 1;
                        const uint32_t tile = sl ? ring + (sl - 1) * TILE : xtile, tb = sl ? rb + (sl - 1) * 8 : xb;
                        mbar_wait(tb, i == 1);
                        PROF_D(34 + i);
#pragma unroll
                        for (int k = 0; k < 6; k++) {
                            const uint32_t a = tile + K_OFF(k);
                            lds128(a, kr[2][k][0], kr[2][k][1], kr[2][k][2], kr[2][k][3]);
                            lds128(a + 3072, kr[2][6 + k][0], kr[2][6 + k][1], kr[2][6 + k][2], kr[2][6 + k][3]);
                        }
                        float cA[4] = {0.f, 0.f, 0.f, 0.f}, cB[4] = {0.f, 0.f, 0.f, 0.f}, cC[4] = {0.f, 0.f, 0.f, 0.f}, cD[4] = {0.f, 0.f, 0.f, 0.f};
#pragma unroll
                        for (int k = 0; k < 3; k++) {
                            mma16816(cA, kr[2][k][0], kr[2][k][1], kr[2][k][2], kr[2][k][3], qf[2 * k], qf[2 * k + 1]);
                            mma16816(cB, kr[2][6 + k][0], kr[2][6 + k][1], kr[2][6 + k][2], kr[2][6 + k][3], qf[2 * k], qf[2 * k + 1]);
                            mma16816(cC, kr[2][3 + k][0], kr[2][3 + k][1], kr[2][3 + k][2], kr[2][3 + k][3], qf[6 + 2 * k], qf[7 + 2 * k]);
                            mma16816(cD, kr[2][9 + k][0], kr[2][9 + k][1], kr[2][9 + k][2], kr[2][9 + k][3], qf[6 + 2 * k], qf[7 + 2 * k]);
                        }
                        __syncwarp();
                        tile_load(tile, &maps.v, row0 + (i + 1) * TS, tb);
                        if (t == i) { sc2 = (cA[0] + cC[0]) + (cA[3] + cC[3]); sc3 = (cB[0] + cD[0]) + (cB[3] + cD[3]); }
                    }
                }
            }
            mw = fmaxf(fmaxf(sc0, sc1), fmaxf(sc2, sc3));
#pragma unroll
            for (int o = 16; o > 0; o >>= 1) mw = fmaxf(mw, __shfl_xor_sync(0xffffffffu, mw, o));
            if ((opq(tid) & 31) == 0) st_pkt2(&g_scr.mx[h * 32 + c * 8 + wu], __float_as_uint(mw), tag);
            pk0 = pack2(ex2((sc0 - mw) * SC), ex2((sc1 - mw) * SC));
            pk1 = pack2(ex2((sc2 - mw) * SC), ex2((sc3 - mw) * SC));
            sc2 = (bf_lo(pk0) + bf_hi(pk0)) + (bf_lo(pk1) + bf_hi(pk1));
#pragma unroll
            for (int o = 16; o > 0; o >>= 1) sc2 += __shfl_xor_sync(0xffffffffu, sc2, o);
#pragma unroll
            for (int s = 0; s < 3; s++) { acc[s][0] = acc[s][1] = acc[s][2] = acc[s][3] = 0.f; }
#define P_CONSTS \
                const uint32_t sel0 = g == 0 ? 0x4410u : (g == 1 ? 0x1044u : 0x4444u); \
                const uint32_t sel1 = g == 2 ? 0x4410u : (g == 3 ? 0x1044u : 0x4444u); \
                const int src00 = 4 * (t < 2 ? 4 * t : 4 * (t - 2) + 1);
#define P_FRAGS(tau) \
                const uint32_t pk = ((tau) & 4) ? pk1 : pk0; \
                const uint32_t w0 = __shfl_sync(0xffffffffu, pk, src00 + ((tau) & 3)); \
                const uint32_t w1 = __shfl_sync(0xffffffffu, pk, src00 + ((tau) & 3) + 8); \
                uint32_t pb[4][2]; \
                _Pragma("unroll") for (int j = 0; j < 4; j++) { \
                    const uint32_t src = ((j & 1) ? w1 : w0) >> ((j >> 1) * 16); \
                    pb[j][0] = __byte_perm(src, 0, sel0); pb[j][1] = __byte_perm(src, 0, sel1); \
                }
            if (layer == 0) {
#pragma unroll 1
                for (int s = 8; s < 16; s++) {
                    LANE_IDS
                    P_CONSTS
                    if (RESET_AT == s) {
                        uint4* p = nullptr;
                        if (tl < 48) p = &g_scr.qx[b * 48 + tl];
                        else if (tl < 98) p = &g_scr.cx[b * 56 + tl - 48];
                        else if (tl < 145) {}
                        else if (b < NG) { if (tl < 153) p = &g_scr.ah[b * 8 + tl - 145]; }
                        else if (b < DN0 + NDN && tl < 149) p = &g_scr.ay[(b - DN0) * 4 + tl - 145];
                        if (p) st_pkt(p, 0, 0, 0, tl < 48);
                    }
                    if (s == 13) { const uint2 mv = ld_pkt2(&g_scr.mx[h * 32 + lane]); sc0 = f_(mv.x); sc1 = f_(mv.y); }
                    P_FRAGS((s + 2) & 7)
                    mbar_wait(rb + (s & 1) * 8, (s >> 1) & 1);
                    const uint32_t tile = ring + (s & 1) * TILE;
#pragma unroll
                    for (int j = 0; j < 4; j++) {
#pragma unroll
                        for (int u = 0; u < 3; u++) {
                            uint32_t a0, a1, a2, a3;
                            lds128(tile + (j >> 1) * 3072 + V_OFF(3 * (j & 1) + u), a0, a1, a2, a3);
                            mma16816(acc[u], a0, a1, a2, a3, pb[j][0], pb[j][1]);
                        }
                    }
                    __syncwarp();
                    if (s < 14) refill1(s, true);
                    if (s == 13) {
                        int it = 0;
                        while (!__all_sync(0xffffffffu, __float_as_uint(sc1) == tag) && ++it < SPIN_CAP) {
                            const uint2 mv = ld_pkt2(&g_scr.mx[h * 32 + lane]); sc0 = f_(mv.x); sc1 = f_(mv.y);
                        }
                    }
                    if (wu == 7 && s == WO_AT && elect_one()) {
                        PROF_X(47);
                        load_wo(maps, sb + SM_B, h, c, wbar, 5);
                    }
                }
            } else {
                LANE_IDS
                P_CONSTS
#pragma unroll
                for (int s = 0; s < 2; s++) {
                    P_FRAGS(s)
#pragma unroll
                    for (int j = 0; j < 4; j++) {
#pragma unroll
                        for (int u = 0; u < 3; u++) {
                            const int k = 6 * (j >> 1) + 3 * (j & 1) + u;
                            mma16816(acc[u], kr[s][k][0], kr[s][k][1], kr[s][k][2], kr[s][k][3], pb[j][0], pb[j][1]);
                        }
                    }
                }
#pragma unroll 1
                for (int i = 4; i < 10; i++) {
                    const int sl = SCHED ? (i == 4 ? 0 : 2 - (i & 1)) : i >= 7 ? i - 7 : i - 4;
                    const uint32_t tile = sl ? ring + (sl - 1) * TILE : xtile, tb = sl ? rb + (sl - 1) * 8 : xb;
                    if (i == 8) { const uint2 mv = ld_pkt2(&g_scr.mx[h * 32 + lane]); sc0 = f_(mv.x); sc1 = f_(mv.y); }
                    P_FRAGS(i - 2)
                    mbar_wait(tb, SCHED ? (0x260 >> i) & 1 : (i >= 7) == (sl == 0));
                    PROF_D(34 + i);
#pragma unroll
                    for (int k = 0; k < 6; k++) {
                        const uint32_t a = tile + V_OFF(k);
                        lds128(a, kr[2][k][0], kr[2][k][1], kr[2][k][2], kr[2][k][3]);
                        lds128(a + 3072, kr[2][6 + k][0], kr[2][6 + k][1], kr[2][6 + k][2], kr[2][6 + k][3]);
                    }
#pragma unroll
                    for (int j = 0; j < 4; j++) {
#pragma unroll
                        for (int u = 0; u < 3; u++) {
                            const int k = 6 * (j >> 1) + 3 * (j & 1) + u;
                            mma16816(acc[u], kr[2][k][0], kr[2][k][1], kr[2][k][2], kr[2][k][3], pb[j][0], pb[j][1]);
                        }
                    }
                    __syncwarp();
                    if (wu < L1R && i == 5 + SCHED - (wu & 1)) tile_load_l1(tile, maps.vp, row0 + (i + 1 - SCHED) * TS, tb, lane);
                    else if (i < 7 + SCHED && i >= 4 + SCHED) tile_load(tile, &maps.v, row0 + (i + 1 - SCHED) * TS, tb);
                    if (PWA >= 0 && wu < 5 && i == PWA + ((wu * PWS) >> 2) && HAS_FFN && !(wu == 4 && KEEP4 && __float_as_uint(misc[1]) >= DN0) && elect_one())
                        asm volatile("cp.async.bulk.prefetch.tensor.3d.L2.global.L2::cache_hint [%0, {0, %1, %2}], %3;" ::"l"(&maps.wo), "r"(h * DH), "r"(5 * c + wu), "l"(PWP ? POL_EF : POL_EN) : "memory");
                    if (i == WO_AT1 && HAS_FFN && elect_one()) {
                        if (atomicAdd(reinterpret_cast<unsigned*>(misc + 2), 1u) == 7u) {
                            PROF_X(63);
                            load_wo(maps, sb + SM_Q, h, c, wbar, KEEP4 && __float_as_uint(misc[1]) >= DN0 ? 4 : 5);
                        }
                    }
                }
            }
#undef P_FRAGS
#undef P_CONSTS
#undef LANE_IDS
#undef K_OFF
#undef V_OFF
            {
                int it = 0;
                while (!__all_sync(0xffffffffu, __float_as_uint(sc1) == tag) && ++it < SPIN_CAP) {
                    const uint2 mv = ld_pkt2(&g_scr.mx[h * 32 + (opq(tid) & 31)]); sc0 = f_(mv.x); sc1 = f_(mv.y);
                }
#pragma unroll
                for (int o = 16; o > 0; o >>= 1) sc0 = fmaxf(sc0, __shfl_xor_sync(0xffffffffu, sc0, o));
                sc3 = ex2((mw - sc0) * SC);
            }
        }
        PROF_D(3 + layer * 16);
        PC(layer * 32 + 1);

        {
            const int tl = opq(tid), warp = tl >> 5, lane = tl & 31, g = lane >> 2, t = lane & 3;
            if (t < 2) {
#pragma unroll
                for (int u = 0; u < 3; u++)
                    *reinterpret_cast<float4*>(rr + warp * 196 + 64 * u + 8 * g + 4 * t) = make_float4(acc[u][0] * sc3, acc[u][1] * sc3, acc[u][2] * sc3, acc[u][3] * sc3);
            }
            if (lane == 0) *reinterpret_cast<float4*>(rr + warp * 196 + 192) = make_float4(sc2 * sc3, 0.f, 0.f, 0.f);
        }
        __syncthreads();
        PROF_T(4 + layer * 16);
        PC(layer * 32 + 2);
        uint32_t ticket = 0;
        {
            const int tid = opq(threadIdx.x), warp = tid >> 5, lane = tid & 31, g = lane >> 2, t = lane & 3, mat = lane >> 3, r8 = lane & 7;
            const int kg = warp >> 1, mg = warp & 1;
            const bool wo2 = layer && HAS_FFN;
            const bool wo4 = wo2 && !(KEEP4 && __float_as_uint(misc[1]) >= DN0);
            const uint32_t aw4 = wo2 && !wo4 ? SM_B - SM_Q : 0;
            const uint32_t aw = sb + (wo2 ? SM_Q : SM_B) + (48 * kg + (mat >> 1) * 8 + r8) * 64 + (((2 * mg + (mat & 1)) ^ ((r8 >> 1) & 3)) << 4);
            float4 o = make_float4(0.f, 0.f, 0.f, 0.f);
            if (tid < 49) {
                const float4* p = reinterpret_cast<const float4*>(rr) + tid;
                float4 v[8];
#pragma unroll
                for (int w = 0; w < 8; w++) v[w] = p[w * 49];
                o.x = ((v[0].x + v[1].x) + (v[2].x + v[3].x)) + ((v[4].x + v[5].x) + (v[6].x + v[7].x));
                o.y = ((v[0].y + v[1].y) + (v[2].y + v[3].y)) + ((v[4].y + v[5].y) + (v[6].y + v[7].y));
                o.z = ((v[0].z + v[1].z) + (v[2].z + v[3].z)) + ((v[4].z + v[5].z) + (v[6].z + v[7].z));
                o.w = ((v[0].w + v[1].w) + (v[2].w + v[3].w)) + ((v[4].w + v[5].w) + (v[6].w + v[7].w));
                st_pktf(&g_scr.cx[b * 56 + tid], o.x, o.y, o.z, o.w, tbit);
            }
            uint32_t a[2][3][4];
            auto preload = [&]() {
                if (layer) {
#pragma unroll
                    for (int i = 0; i < 5; i++) {
                        mbar_wait(wbar + 8 * i, i == 4 ? wo4 : wo2);
#pragma unroll
                        for (int ks = 0; ks < 3; ks++) ldsm4t(aw + (i == 4 ? aw4 : 0) + i * 12288 + ks * 1024, kr[i >> 2][3 * (i & 3) + ks]);
                    }
                } else {
#pragma unroll
                    for (int i = 0; i < NWPRE; i++) {
                        mbar_wait(wbar + 8 * i, 0);
#pragma unroll
                        for (int ks = 0; ks < 3; ks++) ldsm4t(aw + i * 12288 + ks * 1024, a[i][ks]);
                    }
                }
            };
            if (WPRE && (layer || NWPRE)) {
                if (warp < 2) asm volatile("bar.arrive 1, 256;" ::: "memory");
                else asm volatile("bar.sync 1, 256;" ::: "memory");
            }
            {
                bool got = warp >= 2, pre = !WPRE || (!layer && !NWPRE);
                const int tc = min(tid, 48);
                int it = 0;
                do {
                    if (!got) {
                        uint4 v3[3];
#pragma unroll
                        for (int k = 0; k < 3; k++) v3[k] = ld_pkt(&g_scr.cx[(h * 4 + ((c + 1 + k) & 3)) * 56 + tc]);
                        if (__all_sync(0xffffffffu, !(((v3[0].w ^ tbit) | (v3[1].w ^ tbit) | (v3[2].w ^ tbit)) & 1))) {
                            got = true;
#pragma unroll
                            for (int k = 0; k < 3; k++) { o.x += f_(v3[k].x); o.y += f_(v3[k].y); o.z += f_(v3[k].z); o.w += f_(v3[k].w); }
                            if (tid < 48) {
                                const int w = 2 * tid, k3 = w / 24, r = w - 24 * k3, st = r < 16 ? 4 : 2;
                                uint32_t* d = os32 + 24 * k3 + (r < 16 ? 4 * (r & 3) + (r >> 2) : 16 + 2 * (r & 3) + ((r >> 2) & 1));
                                d[0] = pack2(o.x, o.y); d[st] = pack2(o.z, o.w);
                            } else if (tid == 48) misc[0] = rcp(o.x);
                        }
                    }
                    if (!pre && (got || mbar_test(wbar + (layer ? 24 : 8), wo2))) { preload(); pre = true; }
                } while (!(got && pre) && ++it < SPIN_CAP);
            }
            PC(layer * 32 + 3);
            __syncthreads();
            PROF_T(5 + layer * 16);
            PC(layer * 32 + 5);
            if (tid == 224 && layer == 0)
                asm volatile("atom.relaxed.gpu.global.inc.u32 %0, [%1], 0x7fffffff;" : "=r"(ticket) : "l"(g_scr.ticket) : "memory");
            uint32_t ob[6];
            lds128(sb + SM_OS + 96 * kg + 16 * t, ob[0], ob[1], ob[2], ob[3]);
            lds64(sb + SM_OS + 96 * kg + 64 + 8 * t, ob[4], ob[5]);
            float cc[5][4];
            if (WPRE && layer) {
#pragma unroll
                for (int i = 0; i < 5; i++) cc[i][0] = cc[i][1] = cc[i][2] = cc[i][3] = 0.f;
#pragma unroll
                for (int ks = 0; ks < 3; ks++) {
#pragma unroll
                    for (int i = 0; i < 5; i++) {
                        const uint32_t (&f)[4] = kr[i >> 2][3 * (i & 3) + ks];
                        mma16816(cc[i], f[0], f[1], f[2], f[3], ob[2 * ks], ob[2 * ks + 1]);
                    }
                }
            } else {
#pragma unroll
                for (int i = 0; i < 6; i++) {
                    if (i < 5 && i >= NWPRE) {
                        mbar_wait(wbar + 8 * i, WPRE ? 0 : i == 4 ? wo4 : wo2);
                        if (i == 4) { PC(layer * 32 + 4); PROF_D(48); }
#pragma unroll
                        for (int ks = 0; ks < 3; ks++) ldsm4t(aw + (i == 4 && !WPRE ? aw4 : 0) + i * 12288 + ks * 1024, a[i & 1][ks]);
                    }
                    if (i > 0) {
                        cc[i - 1][0] = cc[i - 1][1] = cc[i - 1][2] = cc[i - 1][3] = 0.f;
#pragma unroll
                        for (int ks = 0; ks < 3; ks++) {
                            const uint32_t (&f)[4] = a[(i - 1) & 1][ks];
                            mma16816(cc[i - 1], f[0], f[1], f[2], f[3], ob[2 * ks], ob[2 * ks + 1]);
                        }
                    }
                }
            }
            if (t == 0) {
                float* d = rr + 4 * (16 * mg + g) + kg;
#pragma unroll
                for (int i = 0; i < 5; i++) { d[128 * i] = cc[i][0]; d[128 * i + 32] = cc[i][2]; }
            }
        }
        PC(layer * 32 + 6);
        __syncthreads();
        PROF_D(6 + layer * 16);
        PC(layer * 32 + 7);
        if (tid < 54) {
            const int tid = opq(threadIdx.x);
            const float4* p = reinterpret_cast<const float4*>(rr) + 3 * tid;
            const float4 v0 = p[0], v1 = p[1], v2 = p[2];
            const float il = misc[0];
            const float y0 = il * ((v0.x + v0.y) + (v0.z + v0.w)), y1 = il * ((v1.x + v1.y) + (v1.z + v1.w)), y2 = il * ((v2.x + v2.y) + (v2.z + v2.w));
            red_pkt(&g_scr.acc[layer][(54 * c + tid) * ACC_STR], y0, tid == 53 ? 0.f : y1, tid == 53 ? 0.f : y2);
        }
        if (tid == 224 && layer == 0) {
            misc[1] = __uint_as_float(ticket);
            if (ticket < DN0 + NDN && (ticket < NG || !DNTH)) load_ffn(maps, ticket, sb + SM_B, fbar);
        }
        PROF_T(7 + layer * 16);
        PC(layer * 32 + 8);
        __syncthreads();
        const int role = (int)__float_as_uint(misc[1]);
        PC(layer * 32 + 9);
        const uint32_t fbase = sb + SM_B;
        const uint32_t DONE32 = 0x42000000u;
        if (role < NG) {
            const int tid = opq(threadIdx.x), warp = tid >> 5, lane = tid & 31, g = lane >> 2, t = lane & 3, mat = lane >> 3, r8 = lane & 7;
            const uint32_t ag = fbase + (80 * warp + (mat >> 1) * 8 + r8) * 96 + (((mat & 1) ^ (r8 >> 2)) << 4);
            constexpr int GI = 32, GK = 16 * 96;
            const bool on = (g & 1) == (t >> 1), isx = on && g < 2;
            const uint32_t pm = opq(isx ? sb + SM_XS + 160 * warp + 16 * t : sb + (on ? SM_ONE : SM_ZERO)), pm2 = opq(pm + 128 - (isx ? 8 * t : 0));
            const uint32_t dg = opq(sb + SM_R + 4 * (2 * (warp * 48 + g) + t)), ds = opq(sb + SM_ST + 8 * warp + (lane < 16 ? 4 : 0));
            const bool wr = t < 2, ws = (lane & 15) == 0, lo = lane < 16;
            uint32_t pre[6][4];
            float s1 = 0.f, s2 = 0.f;
            {
                bool hx = tid >= 224;
                int it = 0;
                const uint4* px = &g_scr.acc[layer][min(tid, 215) * ACC_STR];
                const int cq = tid / 54, r = tid - 54 * cq, k0 = min(160 * cq + 3 * r, DM - 1);
                const uint32_t w0 = sb + SM_XS + 4 * xpos(k0 >> 1), w1 = sb + SM_XS + 4 * xpos(min((k0 >> 1) + 1, DM / 2 - 1));
                const uint32_t e0 = w0 + 2 * (k0 & 1), e1 = (k0 & 1) ? w1 : w0 + 2, e2 = w1 + 2 * (k0 & 1);
                auto lds16 = [](uint32_t a) { unsigned short v; asm volatile("ld.shared.u16 %0, [%1];" : "=h"(v) : "r"(a) : "memory"); return __uint_as_float((uint32_t)v << 16); };
                auto sts16 = [](uint32_t a, float x) { asm volatile("st.shared.u16 [%0], %1;" ::"r"(a), "h"((unsigned short)(__float_as_uint(x) >> 16)) : "memory"); };
                const float x0 = lds16(e0), x1 = lds16(e1), x2 = lds16(e2);
                auto take_x = [&](const uint4 v) {
                    if (__all_sync(0xffffffffu, v.w == DONE32)) {
                        hx = true;
                        if (tid < 216) {
                            const float y0 = bfr(x0 + bfr(f_(v.x)));
                            sts16(e0, y0);
                            s1 = y0; s2 = y0 * y0;
                            if (r != 53) {
                                const float y1 = bfr(x1 + bfr(f_(v.y))), y2 = bfr(x2 + bfr(f_(v.z)));
                                sts16(e1, y1); sts16(e2, y2);
                                s1 += y1 + y2; s2 += y1 * y1 + y2 * y2;
                            }
                        }
                    }
                };
                auto try_x = [&]() { take_x(ld_pkt(px)); };
                while (!mbar_test(fbar, 0) && ++it < SPIN_CAP) { if (!hx) try_x(); }
                uint4 v0 = make_uint4(0u, 0u, 0u, 0u);
                if ((PRE1 & 4) && !hx) v0 = ld_pkt(px);
#pragma unroll
                for (int n = 0; n < 6; n++) ldsm4t(ag + (n % 3) * GI + (n / 3) * GK, pre[n]);
                if ((PRE1 & 1) && layer) {
#pragma unroll
                    for (int n = 6; n < 15; n++) ldsm4t(ag + (n % 3) * GI + (n / 3) * GK, kr[0][n - 6]);
                }
                if ((PRE1 & 4) && !hx) take_x(v0);
                PC(layer * 32 + 10);
                while (!hx && ++it < SPIN_CAP) try_x();
                PC(layer * 32 + 11);
            __syncthreads();
            PC(layer * 32 + 12);
            PROF_T(9 + layer * 16);
            float sv = lo ? s1 : s2, cc[3][4];
            if ((PRE1 & 1) && layer) gemv15r(cc, pre, kr[0], pm, pm2, sv, lo ? s2 : s1);
            else { uint32_t pr2[3][4]; gemv15<GK, false>(cc, pre, pr2, [&](int i) { return ag + i * GI; }, pm, pm2, sv, lo ? s2 : s1); }
            if (wr) {
#pragma unroll
                for (int i = 0; i < 3; i++) { sts32(dg + 128 * i, cc[i][0] + cc[i][3]); sts32(dg + 128 * i + 64, cc[i][1] + cc[i][2]); }
            }
            if (ws) sts32(ds, sv);
            PC(layer * 32 + 13);
            __syncthreads();
            PC(layer * 32 + 14);
            PROF_D(43 + layer * 16);
            if (warp < 2) {
                float mean, inv;
                ln_stats(smem, mean, inv);
                const float2* p = reinterpret_cast<const float2*>(rr) + 24 * warp + (lane < 24 ? lane : 0);
                float2 v[8];
#pragma unroll
                for (int w = 0; w < 8; w++) v[w] = p[w * 48];
                const float gx = ((v[0].x + v[1].x) + (v[2].x + v[3].x)) + ((v[4].x + v[5].x) + (v[6].x + v[7].x));
                const float gs = ((v[0].y + v[1].y) + (v[2].y + v[3].y)) + ((v[4].y + v[5].y) + (v[6].y + v[7].y));
                const float ga = inv * (gx - mean * gs);
                const uint32_t wd = pack2(ga, __shfl_down_sync(0xffffffffu, ga, 1));
                const uint32_t wa = __shfl_down_sync(0xffffffffu, wd, 2), wb = __shfl_down_sync(0xffffffffu, wd, 4);
                if (lane < 24 && lane % 6 == 0) st_pkt(&g_scr.ah[role * 8 + 4 * warp + lane / 6], wd, wa, wb, tag);
            }
            if (HOLD & 2) __syncthreads();
            }
            PROF_T(10 + layer * 16);
            PC(layer * 32 + 15);
        } else if (role < DN0 + NDN) {
            const int j = role - DN0;
            const int tid = opq(threadIdx.x), warp = tid >> 5, lane = tid & 31, g = lane >> 2, t = lane & 3, mat = lane >> 3, r8 = lane & 7;
            float xres = 0.f;
            if (warp == 0) {
                const int col = 16 * j + (lane & 15), cc = col / 160, r = col - 160 * cc, e = r % 3;
                const uint4* px = &g_scr.acc[layer][(54 * cc + r / 3) * ACC_STR];
                const float x0 = __bfloat162float(reinterpret_cast<const __nv_bfloat16*>(xs32)[2 * xpos(col >> 1) + (col & 1)]);
                uint4 v;
                int it = 0;
                bool ld = DNTH && layer == 0;
                do {
                    v = ld_pkt(px);
                    if (ld && f_(__shfl_sync(0xffffffffu, v.w, 0)) >= (float)DNTH) { ld = false; if (lane == 0) load_ffn(maps, role, sb + SM_B, fbar); }
                } while (!__all_sync(0xffffffffu, v.w == DONE32) && ++it < SPIN_CAP);
                if (ld && lane == 0) load_ffn(maps, role, sb + SM_B, fbar);
                xres = bfr(x0 + bfr(f_(e == 0 ? v.x : (e == 1 ? v.y : v.z))));
            }
            PC(layer * 32 + 17);
            PROF_T(9 + layer * 16);
            const uint32_t ad = fbase + (192 * warp + (mat >> 1) * 8 + r8) * 32 + (((mat & 1) ^ (r8 >> 2)) << 4);
            uint32_t* hs = reinterpret_cast<uint32_t*>(rr) + warp * 96;
            uint32_t pre[NPRE][4];
            {
                int pos[3];
#pragma unroll
                for (int i = 0; i < 3; i++) { const int w = 3 * lane + i; pos[i] = (w & ~15) + 4 * (w & 3) + ((w >> 2) & 1) + ((w >> 2) & 2); }
                mbar_wait(fbar, 0);
#pragma unroll
                for (int n = 0; n < NPRE; n++) ldsm4t(ad + n * 512, pre[n]);
                if ((PRE1 & 2) && layer) {
#pragma unroll
                    for (int n = NPRE; n < 12; n++) ldsm4t(ad + n * 512, kr[1][n]);
                }
                PC(layer * 32 + 18);
                uint4 v = make_uint4(0u, 0u, 0u, 0u), u = v;
                int it = 0;
                do { v = ld_pkt(&g_scr.ah[tid]); u = ld_pkt(&g_scr.ah[256 + tid]); }
                while (!__all_sync(0xffffffffu, v.w == tag && u.w == tag) && ++it < SPIN_CAP);
                PC(layer * 32 + 19);
                auto glu = [](uint32_t gw, uint32_t uw) {
                    const float g0 = bf_lo(gw), g1 = bf_hi(gw);
                    const float s0 = bfr(g0 * rcp(1.0f + ex2(-1.4426950408889634f * g0))), s1 = bfr(g1 * rcp(1.0f + ex2(-1.4426950408889634f * g1)));
                    return pack2(s0 * bf_lo(uw), s1 * bf_hi(uw));
                };
                hs[pos[0]] = glu(v.x, u.x); hs[pos[1]] = glu(v.y, u.y); hs[pos[2]] = glu(v.z, u.z);
            __syncwarp();
            PROF_T(11 + layer * 16);
            PC(layer * 32 + 20);
            float ca[4] = {0.f, 0.f, 0.f, 0.f}, cb[4] = {0.f, 0.f, 0.f, 0.f};
            if ((PRE1 & 2) && layer) {
                float cc[4] = {0.f, 0.f, 0.f, 0.f}, cd[4] = {0.f, 0.f, 0.f, 0.f};
#pragma unroll
                for (int jj = 0; jj < 6; jj++) {
                    const uint4 hv = *reinterpret_cast<const uint4*>(hs + 16 * jj + 4 * t);
                    const uint32_t (&f0)[4] = 2 * jj < NPRE ? pre[2 * jj < NPRE ? 2 * jj : 0] : kr[1][2 * jj];
                    const uint32_t (&f1)[4] = 2 * jj + 1 < NPRE ? pre[2 * jj + 1 < NPRE ? 2 * jj + 1 : 0] : kr[1][2 * jj + 1];
                    if (jj & 1) { mma16816(cc, f0[0], f0[1], f0[2], f0[3], hv.x, hv.y); mma16816(cd, f1[0], f1[1], f1[2], f1[3], hv.z, hv.w); }
                    else { mma16816(ca, f0[0], f0[1], f0[2], f0[3], hv.x, hv.y); mma16816(cb, f1[0], f1[1], f1[2], f1[3], hv.z, hv.w); }
                }
#pragma unroll
                for (int e = 0; e < 4; e++) { ca[e] += cc[e]; cb[e] += cd[e]; }
            } else {
#pragma unroll
                for (int jj = 0; jj < 6; jj++) {
                    const uint4 hv = *reinterpret_cast<const uint4*>(hs + 16 * jj + 4 * t);
                    uint32_t a[4];
                    if (2 * jj < NPRE) { a[0] = pre[2 * jj][0]; a[1] = pre[2 * jj][1]; a[2] = pre[2 * jj][2]; a[3] = pre[2 * jj][3]; }
                    else ldsm4t(ad + 2 * jj * 512, a);
                    mma16816(ca, a[0], a[1], a[2], a[3], hv.x, hv.y);
                    if (2 * jj + 1 < NPRE) { a[0] = pre[2 * jj + 1][0]; a[1] = pre[2 * jj + 1][1]; a[2] = pre[2 * jj + 1][2]; a[3] = pre[2 * jj + 1][3]; }
                    else ldsm4t(ad + (2 * jj + 1) * 512, a);
                    mma16816(cb, a[0], a[1], a[2], a[3], hv.z, hv.w);
                }
            }
            if (t == 0) { rr[768 + warp * 16 + g] = ca[0] + cb[0]; rr[768 + warp * 16 + 8 + g] = ca[2] + cb[2]; }
            PC(layer * 32 + 21);
            __syncthreads();
            PC(layer * 32 + 22);
            if (warp == 0) {
                const float* p = rr + 768 + (lane & 15);
                const float y = ((p[0] + p[16]) + (p[32] + p[48])) + ((p[64] + p[80]) + (p[96] + p[112]));
                const float s = xres + bfr(y);
                const int p4 = 4 * (lane & 3);
                const uint32_t wd = pack2(__shfl_sync(0xffffffffu, s, p4), __shfl_sync(0xffffffffu, s, p4 + 1));
                const uint32_t wn = pack2(__shfl_sync(0xffffffffu, s, p4 + 2), __shfl_sync(0xffffffffu, s, p4 + 3));
                if (lane < 4) st_pkt(&g_scr.ay[j * 4 + lane], wd, wn, 0, tag);
                if (layer && lane < 4) *reinterpret_cast<uint2*>(out + 16 * j + p4) = make_uint2(wd, wn);
            }
            if (HOLD & 1) __syncthreads();
            }
            PROF_T(12 + layer * 16);
            PC(layer * 32 + 23);
        }
    }
}

typedef CUresult (*EncodeFn)(CUtensorMap*, CUtensorMapDataType, cuuint32_t, void*, const cuuint64_t*, const cuuint64_t*, const cuuint32_t*,
                             const cuuint32_t*, CUtensorMapInterleave, CUtensorMapSwizzle, CUtensorMapL2promotion, CUtensorMapFloatOOBfill);

void make_map(EncodeFn enc, CUtensorMap* m, const void* base, int rank, uint64_t d0, uint64_t d1, uint64_t d2, uint64_t s1, uint64_t s2,
              uint32_t b0, uint32_t b1, uint32_t b2, CUtensorMapSwizzle sw, CUtensorMapL2promotion pr = CU_TENSOR_MAP_L2_PROMOTION_NONE) {
    cuuint64_t dims[3] = {d0, d1, d2};
    cuuint64_t strides[2] = {s1, s2};
    cuuint32_t box[3] = {b0, b1, b2};
    cuuint32_t es[3] = {1, 1, 1};
    enc(m, CU_TENSOR_MAP_DATA_TYPE_BFLOAT16, rank, const_cast<void*>(base), dims, strides, box, es, CU_TENSOR_MAP_INTERLEAVE_NONE, sw,
        pr, CU_TENSOR_MAP_FLOAT_OOB_FILL_NONE);
}

}

extern "C" void kernel_launch(void* const* d_in, const int* in_sizes, int n_in, void* d_out, int out_size) {
    (void)in_sizes; (void)n_in; (void)out_size;
    static EncodeFn enc = nullptr;
    if (!enc) {
        void* fn = nullptr;
        cudaDriverEntryPointQueryResult qr;
        cudaGetDriverEntryPoint("cuTensorMapEncodeTiled", &fn, cudaEnableDefault, &qr);
        enc = reinterpret_cast<EncodeFn>(fn);
        cudaFuncSetAttribute(decode_kernel, cudaFuncAttributeMaxDynamicSharedMemorySize, SM_TOTAL);
    }
    Maps maps;
    make_map(enc, &maps.k, d_in[1], 2, 64, (uint64_t)NH * SK * 3, 1, 128, 0, 64, 48, 1, CU_TENSOR_MAP_SWIZZLE_128B);
    make_map(enc, &maps.v, d_in[2], 2, 64, (uint64_t)NH * SK * 3, 1, 128, 0, 64, 48, 1, CU_TENSOR_MAP_SWIZZLE_128B);
    {
        cuuint64_t dims[4] = {64, 16, NH * DH / 64, DM / 16};
        cuuint64_t strides[3] = {NH * DH * 2, 128, 16 * NH * DH * 2};
        cuuint32_t box[4] = {64, 16, 3, 10};
        cuuint32_t es[4] = {1, 1, 1, 1};
        enc(&maps.wq, CU_TENSOR_MAP_DATA_TYPE_BFLOAT16, 4, d_in[3], dims, strides, box, es, CU_TENSOR_MAP_INTERLEAVE_NONE, CU_TENSOR_MAP_SWIZZLE_128B,
            CU_TENSOR_MAP_L2_PROMOTION_NONE, CU_TENSOR_MAP_FLOAT_OOB_FILL_NONE);
    }
    make_map(enc, &maps.wo, d_in[4], 3, 32, NH * DH, DM / 32, DM * 2, 64, 32, 192, 1, CU_TENSOR_MAP_SWIZZLE_64B);
    constexpr int GW = 48;
    make_map(enc, &maps.w1, d_in[6], 3, FF, 160, 4, FF * 2, 160 * FF * 2, GW, 160, 4, CU_TENSOR_MAP_SWIZZLE_NONE, FFN_PROMO);
    make_map(enc, &maps.w3, d_in[7], 3, FF, 160, 4, FF * 2, 160 * FF * 2, GW, 160, 4, CU_TENSOR_MAP_SWIZZLE_NONE, FFN_PROMO);
    make_map(enc, &maps.w2, d_in[8], 3, DM, 256, 6, DM * 2, 256 * DM * 2, 16, 256, 6, CU_TENSOR_MAP_SWIZZLE_32B, FFN_PROMO);
    maps.vp = d_in[2];
    const int KW = 16;
    make_map(enc, &maps.ks, d_in[1], 2, 64, (uint64_t)NH * SK * 3, 1, 128, 0, KW, 48, 1, CU_TENSOR_MAP_SWIZZLE_NONE);
    make_map(enc, &maps.vs, d_in[2], 2, 64, (uint64_t)NH * SK * 3, 1, 128, 0, KW, 48, 1, CU_TENSOR_MAP_SWIZZLE_NONE);
    decode_kernel<<<NCTA, NT, SM_TOTAL, cudaStreamPerThread>>>(maps, (const __nv_bfloat16*)d_in[0], (__nv_bfloat16*)d_out);
}
```

```cpp
#include <cuda_runtime.h>
#include <cuda_bf16.h>
#include <cuda.h>
#include <stdint.h>
#include <math.h>
#include <stdlib.h>
#include <stdio.h>

namespace {

constexpr int DM = 640;
constexpr int NH = 32;
constexpr int DH = 192;
constexpr int SK = 32768;
constexpr int WIN = 4096;
constexpr int FF = 1536;
constexpr int NCTA = 128;
constexpr int NT = 256;
constexpr int TILE = 6144;
constexpr int NG = 64;
constexpr int DN0 = 64;
constexpr int NDN = 40;

constexpr uint32_t SB = 1024;
constexpr uint32_t SM_RING = SB;
constexpr uint32_t SM_B = SM_RING + 8 * 2 * TILE;
constexpr uint32_t SM_Q = SM_B + 61440;
constexpr uint32_t SM_XS = SM_Q + 61440;
constexpr uint32_t SM_R = SM_XS + 1280;
constexpr uint32_t SM_ST = SM_R + 4096;
constexpr uint32_t SM_QS = SM_R + 6272;
constexpr uint32_t SM_OS = SM_QS + 384;
constexpr uint32_t SM_CS = SM_OS + 384;
constexpr uint32_t SM_BAR = SM_CS + 768;
constexpr uint32_t SM_XBAR = SM_BAR + 24 * 8;
constexpr uint32_t SM_MISC = SM_XBAR + 8 * 8;
constexpr uint32_t SM_ONE = SM_MISC + 32;
constexpr uint32_t SM_ZERO = SM_ONE + 160;
constexpr uint32_t SM_TOTAL = SM_ZERO + 160 - SB;
static_assert(SM_TOTAL <= 232448, "shared memory");
constexpr uint32_t QBAR = SM_BAR + 16 * 8, FBAR = QBAR + 8, WBAR = QBAR + 16;

constexpr unsigned long long POL_EF = 0x12F0000000000000ull;
constexpr unsigned long long POL_EN = 0x1000000000000000ull;

#define RT_MASK 0x2DE0u
#define RT_MASK2 0x36E0u
#define RESET_AT 14
#define WO_AT 15
#define WO_AT1 7
#define FFN_PROMO CU_TENSOR_MAP_L2_PROMOTION_NONE
#define FFN_POL POL_EF
#define HAS_FFN (role < DN0 + NDN)
#define ACC_STR 1
#define NPRE 6

#define HOIST 0
#define PD_G 0
#define PD_R 0
#define PD_D 0
#define PD_D0 0
#define NWPRE 2
#define L1R 3
#define PRE1 5
#define HOLD 3
#define DNTH 23
#define KEEP4 1
#define NEARLY 6
#define XCH(w) ((0x83765210u >> (4 * (w))) & 15u)
#define LAYOUT 1
#define ROW0(w) ((h * SK + (SK - WIN) + c * 1024 + (w) * 128) * 3)
constexpr int TS = 48;
#define CAPL 19
constexpr int SPIN_CAP = 1 << CAPL;
constexpr uint32_t ONES = 0x3F803F80u;

struct Scratch {
    uint4 qx[NCTA * 48];
    uint4 qc[NCTA * 48];
    uint4 cx[NCTA * 56];
    uint4 pad0[160];
    uint4 acc[2][216 * 8];
    uint4 ay[160];
    uint4 ah[NG * 8];
    uint2 mx[NH * 32];
    uint32_t ticket[32];
    uint32_t pad1[32];
};
__device__ Scratch g_scr;
#define DBG(it, site)
#define PROF_T(i)
#define PROF_D(i)
#define PROF_X(i)
#define PC(i)

__device__ __forceinline__ uint32_t smem_u32(const void* p) { return (uint32_t)__cvta_generic_to_shared(p); }
__device__ __forceinline__ void mbar_init(uint32_t bar, uint32_t cnt) {
    asm volatile("mbarrier.init.shared::cta.b64 [%0], %1;" ::"r"(bar), "r"(cnt) : "memory");
}
__device__ __forceinline__ void mbar_expect_tx(uint32_t bar, uint32_t bytes) {
    asm volatile("mbarrier.arrive.expect_tx.shared::cta.b64 _, [%0], %1;" ::"r"(bar), "r"(bytes) : "memory");
}
__device__ __forceinline__ bool mbar_test(uint32_t bar, uint32_t parity) {
    uint32_t done;
    asm volatile("{\n.reg .pred p;\nmbarrier.try_wait.parity.shared::cta.b64 p, [%1], %2;\nselp.u32 %0, 1, 0, p;\n}"
                 : "=r"(done) : "r"(bar), "r"(parity) : "memory");
    return done;
}
__device__ __forceinline__ void mbar_wait(uint32_t bar, uint32_t parity) {
    asm volatile("{\n.reg .pred p;\n.reg .u32 n;\nmov.u32 n, 0;\n"
                 "W: mbarrier.try_wait.parity.shared::cta.b64 p, [%0], %1;\n@p bra D;\n"
                 "add.u32 n, n, 1;\nsetp.lt.u32 p, n, %2;\n@p bra W;\nD:\n}" ::"r"(bar), "r"(parity), "n"(SPIN_CAP) : "memory");
}
__device__ __forceinline__ void tma2d(uint32_t dst, const CUtensorMap* map, int c0, int c1, uint32_t bar, unsigned long long pol) {
    asm volatile("cp.async.bulk.tensor.2d.shared::cluster.global.mbarrier::complete_tx::bytes.L2::cache_hint [%0], [%1, {%3, %4}], [%2], %5;"
                 ::"r"(dst), "l"(map), "r"(bar), "r"(c0), "r"(c1), "l"(pol) : "memory");
}
__device__ __forceinline__ void tma3d(uint32_t dst, const CUtensorMap* map, int c0, int c1, int c2, uint32_t bar, unsigned long long pol) {
    asm volatile("cp.async.bulk.tensor.3d.shared::cluster.global.mbarrier::complete_tx::bytes.L2::cache_hint [%0], [%1, {%3, %4, %5}], [%2], %6;"
                 ::"r"(dst), "l"(map), "r"(bar), "r"(c0), "r"(c1), "r"(c2), "l"(pol) : "memory");
}
__device__ __forceinline__ void tma4d(uint32_t dst, const CUtensorMap* map, int c2, int c3, uint32_t bar, unsigned long long pol) {
    asm volatile("cp.async.bulk.tensor.4d.shared::cluster.global.mbarrier::complete_tx::bytes.L2::cache_hint [%0], [%1, {0, 0, %3, %4}], [%2], %5;"
                 ::"r"(dst), "l"(map), "r"(bar), "r"(c2), "r"(c3), "l"(pol) : "memory");
}
__device__ __forceinline__ void tma2d_pf(const CUtensorMap* map, int c0, int c1, unsigned long long pol) {
    asm volatile("cp.async.bulk.prefetch.tensor.2d.L2.global.L2::cache_hint [%0, {%1, %2}], %3;" ::"l"(map), "r"(c0), "r"(c1), "l"(pol) : "memory");
}
__device__ __forceinline__ void tile_load(uint32_t dst, const CUtensorMap* map, int row, uint32_t bar) {
    asm volatile("{\n.reg .pred p;\nelect.sync _|p, 0xffffffff;\n"
                 "@p mbarrier.arrive.expect_tx.shared::cta.b64 _, [%2], 6144;\n"
                 "@p cp.async.bulk.tensor.2d.shared::cluster.global.mbarrier::complete_tx::bytes.L2::cache_hint [%0], [%1, {0, %3}], [%2], %4;\n}"
                 ::"r"(dst), "l"(map), "r"(bar), "r"(row), "l"(POL_EF) : "memory");
}
__device__ __forceinline__ void tile_keep(const CUtensorMap* map, int row) {
    asm volatile("{\n.reg .pred p;\nelect.sync _|p, 0xffffffff;\n"
                 "@p cp.async.bulk.prefetch.tensor.2d.L2.global.L2::cache_hint [%0, {0, %1}], %2;\n}"
                 ::"l"(map), "r"(row), "l"(POL_EN) : "memory");
}
__device__ __forceinline__ void tile_load_l1(uint32_t dst, const void* base, int row, uint32_t bar, int lane) {
    const char* g = static_cast<const char*>(base) + (size_t)row * 128 + lane * 16;
    const uint32_t s0 = dst + (lane >> 3) * 128 + (((lane & 7) ^ (lane >> 3)) << 4), s1 = s0 ^ 64;
#pragma unroll
    for (int k = 0; k < 12; k++)
        asm volatile("cp.async.ca.shared.global.L2::cache_hint [%0], [%1], 16, %2;" ::"r"(((k & 1) ? s1 : s0) + k * 512), "l"(g + k * 512), "l"(POL_EF) : "memory");
    asm volatile("cp.async.mbarrier.arrive.shared::cta.b64 [%0];" ::"r"(bar) : "memory");
    __syncwarp();
    if (lane == 0) asm volatile("mbarrier.arrive.shared::cta.b64 _, [%0];" ::"r"(bar) : "memory");
}
__device__ __forceinline__ bool elect_one() {
    uint32_t p;
    asm volatile("{\n.reg .pred p;\nelect.sync _|p, 0xffffffff;\nselp.u32 %0, 1, 0, p;\n}" : "=r"(p));
    return p;
}
__device__ __forceinline__ void lds128(uint32_t addr, uint32_t& a, uint32_t& b, uint32_t& c, uint32_t& d) {
    asm volatile("ld.shared.v4.u32 {%0,%1,%2,%3}, [%4];" : "=r"(a), "=r"(b), "=r"(c), "=r"(d) : "r"(addr) : "memory");
}
__device__ __forceinline__ void lds64(uint32_t addr, uint32_t& a, uint32_t& b) {
    asm volatile("ld.shared.v2.u32 {%0,%1}, [%2];" : "=r"(a), "=r"(b) : "r"(addr) : "memory");
}
__device__ __forceinline__ void ldsm4t(uint32_t addr, uint32_t (&a)[4]) {
    asm volatile("ldmatrix.sync.aligned.m8n8.x4.trans.shared.b16 {%0,%1,%2,%3}, [%4];" : "=r"(a[0]), "=r"(a[1]), "=r"(a[2]), "=r"(a[3]) : "r"(addr) : "memory");
}
__device__ __forceinline__ void mma16816(float (&c)[4], uint32_t a0, uint32_t a1, uint32_t a2, uint32_t a3, uint32_t b0, uint32_t b1) {
    asm("mma.sync.aligned.m16n8k16.row.col.f32.bf16.bf16.f32 {%0,%1,%2,%3}, {%4,%5,%6,%7}, {%8,%9}, {%0,%1,%2,%3};"
        : "+f"(c[0]), "+f"(c[1]), "+f"(c[2]), "+f"(c[3]) : "r"(a0), "r"(a1), "r"(a2), "r"(a3), "r"(b0), "r"(b1));
}
__device__ __forceinline__ void mma16816v(float (&c)[4], uint32_t a0, uint32_t a1, uint32_t a2, uint32_t a3, uint32_t b0, uint32_t b1) {
    asm volatile("mma.sync.aligned.m16n8k16.row.col.f32.bf16.bf16.f32 {%0,%1,%2,%3}, {%4,%5,%6,%7}, {%8,%9}, {%0,%1,%2,%3};"
        : "+f"(c[0]), "+f"(c[1]), "+f"(c[2]), "+f"(c[3]) : "r"(a0), "r"(a1), "r"(a2), "r"(a3), "r"(b0), "r"(b1));
}
__device__ __forceinline__ int xpos(int w) {
    const int seg = w / 40, r = w - 40 * seg;
    return 40 * seg + (r < 32 ? (r & 16) + 4 * (r & 3) + ((r >> 2) & 3) : 32 + 2 * (r & 3) + ((r >> 2) & 1));
}
#define NA_LD ""
#define NA_ST ""
__device__ __forceinline__ void st_pkt(uint4* p, uint32_t a, uint32_t b, uint32_t c, uint32_t d) {
    asm volatile("{\n.reg .b128 t;\n.reg .b64 lo, hi;\nmov.b64 lo, {%1,%2};\nmov.b64 hi, {%3,%4};\nmov.b128 t, {lo,hi};\nst.relaxed.gpu.global" NA_ST ".b128 [%0], t;\n}"
                 ::"l"(p), "r"(a), "r"(b), "r"(c), "r"(d) : "memory");
}
__device__ __forceinline__ void st_pktf(uint4* p, float a, float b, float c, float d, uint32_t bit) {
    st_pkt(p, __float_as_uint(a), __float_as_uint(b), __float_as_uint(c), (__float_as_uint(d) & ~1u) | bit);
}
__device__ __forceinline__ void red_pkt(uint4* p, float a, float b, float c) {
    asm volatile("red.relaxed.gpu.global.add.v4.f32 [%0], {%1,%2,%3,%4};" ::"l"(p), "f"(a), "f"(b), "f"(c), "f"(1.0f) : "memory");
}
__device__ __forceinline__ uint4 ld_pkt(const uint4* p) {
    uint4 v;
    asm volatile("{\n.reg .b128 t;\n.reg .b64 lo, hi;\nld.relaxed.gpu.global" NA_LD ".b128 t, [%4];\nmov.b128 {lo,hi}, t;\nmov.b64 {%0,%1}, lo;\nmov.b64 {%2,%3}, hi;\n}"
                 : "=r"(v.x), "=r"(v.y), "=r"(v.z), "=r"(v.w) : "l"(p) : "memory");
    return v;
}
__device__ __forceinline__ uint2 ld_pkt2(const uint2* p) {
    unsigned long long v;
    asm volatile("ld.relaxed.gpu.global" NA_LD ".b64 %0, [%1];" : "=l"(v) : "l"(p) : "memory");
    return make_uint2((uint32_t)v, (uint32_t)(v >> 32));
}
__device__ __forceinline__ void st_pkt2(uint2* p, uint32_t a, uint32_t b) {
    asm volatile("st.relaxed.gpu.global" NA_ST ".b64 [%0], %1;" ::"l"(p), "l"((unsigned long long)a | ((unsigned long long)b << 32)) : "memory");
}
__device__ __forceinline__ float ex2(float x) { float y; asm("ex2.approx.ftz.f32 %0, %1;" : "=f"(y) : "f"(x)); return y; }
__device__ __forceinline__ float rcp(float x) { float y; asm("rcp.approx.ftz.f32 %0, %1;" : "=f"(y) : "f"(x)); return y; }
__device__ __forceinline__ uint32_t pack2(float lo, float hi) {
    uint32_t r; asm("cvt.rn.bf16x2.f32 %0, %1, %2;" : "=r"(r) : "f"(hi), "f"(lo)); return r;
}
__device__ __forceinline__ float bf_lo(uint32_t w) { return __uint_as_float(w << 16); }
__device__ __forceinline__ float bf_hi(uint32_t w) { return __uint_as_float(w & 0xffff0000u); }
__device__ __forceinline__ float bfr(float x) { return bf_lo(pack2(x, 0.f)); }
__device__ __forceinline__ float f_(uint32_t u) { return __uint_as_float(u); }

__device__ __forceinline__ uint32_t add2(uint32_t a, uint32_t b) { uint32_t r; asm("add.rn.bf16x2 %0, %1, %2;" : "=r"(r) : "r"(a), "r"(b)); return r; }
__device__ __forceinline__ uint32_t mul2(uint32_t a, uint32_t b) { uint32_t r; asm("mul.rn.bf16x2 %0, %1, %2;" : "=r"(r) : "r"(a), "r"(b)); return r; }
__device__ __forceinline__ uint32_t f2key(float f) { const uint32_t u = __float_as_uint(f); return u ^ ((uint32_t)((int)u >> 31) | 0x80000000u); }
__device__ __forceinline__ float key2f(uint32_t k) { return __uint_as_float(k ^ ((uint32_t)((int)~k >> 31) | 0x80000000u)); }
__device__ __forceinline__ float4 lds128f(uint32_t a) {
    float4 v; asm volatile("ld.shared.v4.f32 {%0,%1,%2,%3}, [%4];" : "=f"(v.x), "=f"(v.y), "=f"(v.z), "=f"(v.w) : "r"(a) : "memory"); return v;
}
__device__ __forceinline__ float2 lds64f(uint32_t a) { float2 v; asm volatile("ld.shared.v2.f32 {%0,%1}, [%2];" : "=f"(v.x), "=f"(v.y) : "r"(a) : "memory"); return v; }
__device__ __forceinline__ uint32_t lds32(uint32_t a) { uint32_t v; asm volatile("ld.shared.u32 %0, [%1];" : "=r"(v) : "r"(a) : "memory"); return v; }
__device__ __forceinline__ uint32_t lds16(uint32_t a) { uint32_t v; asm volatile("ld.shared.u16 %0, [%1];" : "=r"(v) : "r"(a) : "memory"); return v; }
__device__ __forceinline__ void sts16(uint32_t a, uint32_t v) { asm volatile("st.shared.u16 [%0], %1;" ::"r"(a), "r"(v) : "memory"); }
__device__ __forceinline__ void sts32(uint32_t a, uint32_t v) { asm volatile("st.shared.u32 [%0], %1;" ::"r"(a), "r"(v) : "memory"); }
__device__ __forceinline__ void sts32(uint32_t a, float v) { asm volatile("st.shared.f32 [%0], %1;" ::"r"(a), "f"(v) : "memory"); }
__device__ __forceinline__ void sts128(uint32_t a, float x, float y, float z, float w) {
    asm volatile("st.shared.v4.f32 [%0], {%1,%2,%3,%4};" ::"r"(a), "f"(x), "f"(y), "f"(z), "f"(w) : "memory");
}
__device__ __forceinline__ int opq(int x) { asm volatile("" : "+r"(x)); return x; }
__device__ __forceinline__ uint32_t opq(uint32_t x) { asm volatile("" : "+r"(x)); return x; }
__device__ __forceinline__ uint32_t pin(uint32_t x) { x = opq(x); sts32(SM_MISC + 12, x); return x; }
__device__ __forceinline__ float pin(float x) { sts32(SM_MISC + 12, x); return x; }
template <typename T> __device__ __forceinline__ T* pin(T* p) {
    asm volatile("{\n.reg .b32 lo, hi;\nmov.b64 {lo, hi}, %0;\nst.shared.v2.b32 [%1], {lo, hi};\n}" : "+l"(p) : "r"(SM_MISC + 16) : "memory");
    return p;
}
template <typename T> __device__ __forceinline__ T* opq(T* p) { asm volatile("" : "+l"(p)); return p; }

__device__ __forceinline__ void ln_stats(float& mean, float& inv) {
    const float4 a = lds128f(SM_ST), b = lds128f(SM_ST + 16), c = lds128f(SM_ST + 32), d = lds128f(SM_ST + 48);
    const float s2 = ((a.x + a.z) + (b.x + b.z)) + ((c.x + c.z) + (d.x + d.z));
    const float md = (((a.y + a.w) + (b.y + b.w)) + ((c.y + c.w) + (d.y + d.w))) * (1.0f / DM);
    const float var = fmaxf(s2 * (1.0f / DM) - md * md, 0.f);
    mean = bfr(md);
    asm("rsqrt.approx.ftz.f32 %0, %1;" : "=f"(inv) : "f"(var + 1e-5f));
}
template <int SK, bool GRAM, typename AddrF>
__device__ __forceinline__ void gemv15(float (&cc)[3][4], float (&gr)[4], uint32_t (&pre)[9][4], AddrF ad, uint32_t px, uint32_t px2) {
    uint32_t x0[4], x1[4];
    lds128(px, x0[0], x0[1], x0[2], x0[3]);
    lds128(px + 64, x1[0], x1[1], x1[2], x1[3]);
    gr[0] = gr[1] = gr[2] = gr[3] = 0.f;
#pragma unroll
    for (int i = 0; i < 3; i++) {
        cc[i][0] = cc[i][1] = cc[i][2] = cc[i][3] = 0.f;
        mma16816v(cc[i], pre[i][0], pre[i][1], pre[i][2], pre[i][3], x0[0], x0[1]);
    }
#pragma unroll
    for (int i = 0; i < 3; i++) ldsm4t(ad(i) + 3 * SK, pre[i]);
    if (GRAM) mma16816v(gr, x0[0], 0u, x0[1], 0u, x0[0], x0[1]);
#pragma unroll
    for (int i = 0; i < 3; i++) mma16816v(cc[i], pre[3 + i][0], pre[3 + i][1], pre[3 + i][2], pre[3 + i][3], x0[2], x0[3]);
#pragma unroll
    for (int i = 0; i < 3; i++) ldsm4t(ad(i) + 4 * SK, pre[3 + i]);
    lds64(px2, x0[0], x0[1]);
    if (GRAM) mma16816v(gr, x0[2], 0u, x0[3], 0u, x0[2], x0[3]);
#pragma unroll
    for (int i = 0; i < 3; i++) mma16816v(cc[i], pre[6 + i][0], pre[6 + i][1], pre[6 + i][2], pre[6 + i][3], x1[0], x1[1]);
    if (GRAM) mma16816v(gr, x1[0], 0u, x1[1], 0u, x1[0], x1[1]);
#pragma unroll
    for (int i = 0; i < 3; i++) mma16816v(cc[i], pre[i][0], pre[i][1], pre[i][2], pre[i][3], x1[2], x1[3]);
    if (GRAM) mma16816v(gr, x1[2], 0u, x1[3], 0u, x1[2], x1[3]);
    if (GRAM) mma16816v(gr, x0[0], 0u, x0[1], 0u, x0[0], x0[1]);
#pragma unroll
    for (int i = 0; i < 3; i++) mma16816v(cc[i], pre[3 + i][0], pre[3 + i][1], pre[3 + i][2], pre[3 + i][3], x0[0], x0[1]);
}
__device__ __forceinline__ void gemv15r(float (&cc)[3][4], float (&gr)[4], const uint32_t (&pre)[9][4], const uint32_t (&ext)[12][4], uint32_t px, uint32_t px2) {
    uint32_t x0[4], x1[4], x2[2];
    lds128(px, x0[0], x0[1], x0[2], x0[3]);
    lds128(px + 64, x1[0], x1[1], x1[2], x1[3]);
    lds64(px2, x2[0], x2[1]);
    gr[0] = gr[1] = gr[2] = gr[3] = 0.f;
#pragma unroll
    for (int ks = 0; ks < 5; ks++) {
        const uint32_t b0 = ks < 2 ? x0[2 * (ks & 1)] : ks < 4 ? x1[2 * (ks & 1)] : x2[0], b1 = ks < 2 ? x0[2 * (ks & 1) + 1] : ks < 4 ? x1[2 * (ks & 1) + 1] : x2[1];
        mma16816v(gr, b0, 0u, b1, 0u, b0, b1);
#pragma unroll
        for (int i = 0; i < 3; i++) {
            if (ks == 0) cc[i][0] = cc[i][1] = cc[i][2] = cc[i][3] = 0.f;
            const uint32_t (&f)[4] = ks < 3 ? pre[ks < 3 ? 3 * ks + i : 0] : ext[ks < 3 ? 0 : 3 * (ks - 3) + i];
            mma16816v(cc[i], f[0], f[1], f[2], f[3], b0, b1);
        }
    }
}

struct Maps { CUtensorMap k, v, wq, wo, w1, w3, w2, ks, vs; const void* vp;
};
#define RT_SEL ((wu & 1) ? RT_MASK2 : RT_MASK)
#define K4D_G 0
#define K4D_R 1500
#define PWA -1
#define PWS 0
#define PWP 0
#define K4LATE 0

__device__ __forceinline__ void load_ffn(const Maps& maps, int b, uint32_t dst, uint32_t bar) {
    const bool gu = b < NG;
    mbar_expect_tx(bar, gu ? 61440 : 49152);
    tma3d(dst, gu ? (b < NG / 2 ? &maps.w1 : &maps.w3) : &maps.w2, gu ? 48 * (b & (NG / 2 - 1)) : 16 * (b - DN0), 0, 0, bar, FFN_POL);
}

__device__ __forceinline__ void load_wo(const Maps& maps, uint32_t dst, int h, int c, uint32_t bar, int nbox) {
#pragma unroll 1
    for (int i = 0; i < nbox; i++) {
        mbar_expect_tx(bar + 8 * i, 12288);
        tma3d(dst + i * 12288, &maps.wo, 0, h * DH, 5 * c + i, bar + 8 * i, POL_EF);
    }
}

__global__ void __launch_bounds__(NT, 1)
decode_kernel(const __grid_constant__ Maps maps, const __nv_bfloat16* __restrict__ x_in, __nv_bfloat16* __restrict__ out) {
    extern __shared__ __align__(1024) unsigned char smem[];
    const int tid = threadIdx.x;
    const int wu = __shfl_sync(0xffffffffu, tid >> 5, 0);
    const int b = blockIdx.x, h = b >> 2, c = b & 3;
    if (smem_u32(smem) != SB) return;

    PROF_T(0);
    {
        const int warp = tid >> 5, lane = tid & 31;
        const uint32_t rbar = SM_BAR + warp * 16;
        if (lane == 0) {
            mbar_init(rbar, 1); mbar_init(rbar + 8, 1); mbar_init(SM_XBAR + warp * 8, 1);
            if (warp == 0) {
                mbar_init(QBAR, 1); mbar_init(FBAR, 1);
#pragma unroll
                for (int i = 0; i < 5; i++) mbar_init(WBAR + 8 * i, 1);
                asm volatile("fence.mbarrier_init.release.cluster;" ::: "memory");
                mbar_expect_tx(QBAR, 61440);
                tma4d(SM_Q, &maps.wq, 3 * h, 10 * c, QBAR, POL_EF);
            }
            asm volatile("fence.mbarrier_init.release.cluster;" ::: "memory");
            if (warp >= 1 && warp < 7) {
                const CUtensorMap* mp = warp == 1 ? &maps.k : warp == 2 ? &maps.v : warp == 3 ? &maps.wo : warp == 4 ? &maps.w1 : warp == 5 ? &maps.w3 : &maps.w2;
                asm volatile("prefetch.tensormap [%0];" ::"l"(mp) : "memory");
            }
        }
        if (tid == 96) sts32(SM_MISC + 8, 0u);
        if (tid >= 128 && tid < 148) {
            const float v = f_(tid < 138 ? ONES : 0u);
            sts128(SM_ONE + 16 * (tid - 128), v, v, v, v);
        }
        if (b == 0 && tid == 255) asm volatile("st.relaxed.gpu.global.u32 [%0], %1;" ::"l"(g_scr.ticket), "r"(0) : "memory");
        if (tid < 52) st_pkt(tid < 48 ? &g_scr.qx[b * 48 + tid] : reinterpret_cast<uint4*>(&g_scr.mx[h * 32 + c * 8]) + (tid - 48), 0, 0, 0, 0);
        if (tid >= 64 && tid < 66 && b < 108) st_pkt(&g_scr.acc[1][(2 * b + tid - 64) * ACC_STR], 0, 0, 0, 0);
        __syncthreads();
        PROF_D(14);
        if (lane == 0) {
            const int row = ROW0(warp);
            mbar_expect_tx(rbar, TILE);
            tma2d(SM_RING + warp * 2 * TILE, &maps.k, 0, row, rbar, POL_EF);
            mbar_expect_tx(rbar + 8, TILE);
            tma2d(SM_RING + (warp * 2 + 1) * TILE, &maps.k, 0, row + TS, rbar + 8, POL_EF);
        }
    }

    uint32_t kr[4][12][4];
    const float SC = 0.07216878364870322f * 1.4426950408889634f;
    int role = 0;

#pragma unroll 1
    for (int layer = 0; layer < 2; layer++) {
        const uint32_t tag = layer + 1, tbit = layer ^ 1;
        PROF_D(1 + layer * 16);
        uint2 xv = make_uint2(0u, 0u);
        uint32_t qo;
        {
            const int tl = opq(tid), warp = tl >> 5, lane = tl & 31, g = lane >> 2, t = lane & 3, mat = lane >> 3, r8 = lane & 7;
            const int kh = warp >> 2, mg = warp & 3;
            const uint32_t aq = SM_Q + kh * 5 * TILE + ((mat >> 1) * 8 + r8) * 128 + (((2 * mg + (mat & 1)) ^ r8) << 4);
            if (layer == 0 && tl < 160) xv = reinterpret_cast<const uint2*>(x_in)[tl];
            mbar_wait(QBAR, 0);
            uint32_t pre[9][4];
#pragma unroll
            for (int n = 0; n < 9; n++) ldsm4t(aq + (n % 3) * 2048 + (n / 3) * TILE, pre[n]);
            if (layer == 1) {
                __syncthreads();
                if (K4D_G | K4D_R) {
                    const uint32_t d = role < NG ? K4D_G : role >= DN0 + NDN ? K4D_R : 0;
                    uint32_t t0, t1; asm volatile("mov.u32 %0, %%clock;" : "=r"(t0));
                    do asm volatile("mov.u32 %0, %%clock;" : "=r"(t1)); while (t1 - t0 < d);
                }
                if (wu < NEARLY) tile_load(SM_Q + XCH(wu) * TILE, &maps.k, ROW0(wu) + 4 * TS, SM_XBAR + wu * 8);
            }
            const uint32_t pm = opq(g == 1 ? SM_ONE : SM_XS + 160 * (2 * c + kh) + 16 * t), pm2 = opq(pm + 128 - (g == 1 ? 0 : 8 * t));
            const uint32_t dq = opq(SM_R + 768 * kh + 4 * (16 * mg + g));
            qo = HOIST & 1 ? pin(16u * (b * 48 + (tl & 63) + (tl >= 64 ? NCTA * 48 : 0))) : 0;
            if (tl < 160) {
                const uint32_t xa0 = opq(SM_XS + 4 * xpos(2 * tl)), xa1 = opq(SM_XS + 4 * xpos(2 * tl + 1));
                if (layer == 1) {
                    const uint4* px = opq(&g_scr.ay[tl]);
                    uint4 v;
                    int it = 0;
                    bool more;
                    if (PD_G | PD_R) {
                        const uint32_t d = role < NG ? PD_G : role >= DN0 + NDN ? PD_R : 0;
                        uint32_t t0, t1; asm volatile("mov.u32 %0, %%clock;" : "=r"(t0));
                        do asm volatile("mov.u32 %0, %%clock;" : "=r"(t1)); while (t1 - t0 < d);
                    }
                    do { v = ld_pkt(px); more = ++it < SPIN_CAP; } while (!__all_sync(0xffffffffu, (v.y & v.w) == 1) && more);
                    DBG(it, 1);
                    xv = make_uint2(v.x, v.z);
                }
                sts32(xa0, xv.x); sts32(xa1, xv.y);
            }
            if (layer) PC(24);
            __syncthreads();
            if (layer) PC(25);
            PROF_T(13 + layer * 16);
            float cc[3][4], gr[4];
            gemv15<TILE, false>(cc, gr, pre, [&](int i) { return aq + i * 2048; }, pm, pm2);
            if (t == 0) {
#pragma unroll
                for (int i = 0; i < 3; i++) { sts32(dq + 256 * i, cc[i][0]); sts32(dq + 256 * i + 32, cc[i][2]); }
                if (layer == 0) {
#pragma unroll
                    for (int i = 0; i < 3; i++) { sts32(dq + 256 * i + 1536, cc[i][1]); sts32(dq + 256 * i + 1568, cc[i][3]); }
                }
            }
        }
        {
            const int tl = opq(tid), j = tl & 63;
            const bool snd = j < 48 && (tl < 64 || (tl < 128 && layer == 0));
            const uint32_t fa = opq(SM_R + 16 * tl + (tl >= 64 ? 512 : 0));
            if (!(HOIST & 1)) qo = 16u * (b * 48 + (tl & 63) + (tl >= 64 ? NCTA * 48 : 0));
            uint4* pq = reinterpret_cast<uint4*>(reinterpret_cast<char*>(g_scr.qx) + qo);
            if (layer) PC(26);
            __syncthreads();
            if (layer) PC(27);
            PROF_D(33 + layer * 16);
            if (snd) {
                const float4 u = lds128f(fa), v = lds128f(fa + 768);
                st_pktf(pq, u.x + v.x, u.y + v.y, u.z + v.z, u.w + v.w, tbit);
            }
            if (layer) PC(28);
            if (layer == 1 && wu >= NEARLY) tile_load(SM_Q + XCH(wu) * TILE, &maps.k, ROW0(wu) + 4 * TS, SM_XBAR + wu * 8);
            if (layer == 1 && tl >= 192 && tl < 194 && b < 108) st_pkt(&g_scr.acc[0][(2 * b + tl - 192) * ACC_STR], 0, 0, 0, 0);
            const float e0 = bf_lo(xv.x), e1 = bf_hi(xv.x), e2 = bf_lo(xv.y), e3 = bf_hi(xv.y);
            const float s1 = (e0 + e1) + (e2 + e3), s2 = (e0 * e0 + e1 * e1) + (e2 * e2 + e3 * e3);
            const bool lo = !(tl & 16);
            float sv = (lo ? s1 : s2) + __shfl_xor_sync(0xffffffffu, lo ? s2 : s1, 16);
#pragma unroll
            for (int o = 8; o > 0; o >>= 1) sv += __shfl_xor_sync(0xffffffffu, sv, o);
            if ((tl & 15) == 0) sts32(SM_ST + 8 * (tl >> 5) + (lo ? 4 : 0), sv);
        }

        float sc0 = -INFINITY, sc1 = -INFINITY, sc2 = 0.f, sc3 = 0.f, mw;
        uint32_t pk0, pk1;
        float acc[3][4];
        {
            const uint32_t ring = SM_RING + wu * 2 * TILE, rb = SM_BAR + wu * 16;
            const uint32_t xtile = SM_Q + XCH(wu) * TILE, xb = SM_XBAR + wu * 8;
            const int row0 = ROW0(wu);
            auto issue1 = [&](int n, bool vph = false) {
                const CUtensorMap* mp = n < 8 ? &maps.k : &maps.v;
                const int row = row0 + ((n + (n >= 8 ? 2 : 0)) & 7) * TS;
                if (vph && wu < L1R && n == 12 - (wu & 1)) {
                    tile_load_l1(ring + (n & 1) * TILE, maps.vp, row, rb + (n & 1) * 8, opq(tid) & 31);
                    return;
                }
                tile_load(ring + (n & 1) * TILE, mp, row, rb + (n & 1) * 8);
                if ((RT_SEL >> n) & 1) tile_keep(n < 8 ? &maps.ks : &maps.vs, row);
            };
            auto refill1 = [&](int s, bool vph = false) { issue1(s + 2, vph); };
#define K_OFF(i) ((uint32_t)((3 * ((g >> 1) + 4 * (g & 1)) + ((i) >> 1)) * 128 + ((t ^ ((3 * ((g >> 1) + 4 * (g & 1)) + ((i) >> 1)) & 7) ^ (((i) & 1) << 2)) << 4)))
#define V_OFF(i) ((uint32_t)((6 * t + (i)) * 128 + ((g ^ ((6 * t + (i)) & 7)) << 4)))
#define LANE_IDS const int tl = opq(tid), lane = tl & 31, g = lane >> 2, t = lane & 3; (void)tl; (void)lane; (void)g; (void)t;
            if (layer == 0) {
                LANE_IDS
#pragma unroll
                for (int s = 0; s < 4; s++) {
                    mbar_wait(rb + (s & 1) * 8, (s >> 1) & 1);
                    if (s == 0) PROF_D(52);
                    if (s == 3) PROF_D(53);
#pragma unroll
                    for (int i = 0; i < 6; i++) {
                        const uint32_t a = ring + (s & 1) * TILE + K_OFF(i);
                        lds128(a, kr[s][i][0], kr[s][i][1], kr[s][i][2], kr[s][i][3]);
                        lds128(a + 3072, kr[s][6 + i][0], kr[s][6 + i][1], kr[s][6 + i][2], kr[s][6 + i][3]);
                    }
                    __syncwarp();
                    refill1(s);
                }
                if (tl >= 64 && tl < 112) {
                    const uint4* p = &g_scr.qc[h * 4 * 48 + tl - 64];
                    uint4 v[4];
                    int it = 0;
                    do {
#pragma unroll
                        for (int k = 0; k < 4; k++) v[k] = ld_pkt(p + 48 * k);
                    } while (!(v[0].w & v[1].w & v[2].w & v[3].w & 1) && ++it < SPIN_CAP);
                    DBG(it, 2);
                    sts128(SM_CS + 16 * (tl - 64), (f_(v[0].x) + f_(v[1].x)) + (f_(v[2].x) + f_(v[3].x)), (f_(v[0].y) + f_(v[1].y)) + (f_(v[2].y) + f_(v[3].y)),
                           (f_(v[0].z) + f_(v[1].z)) + (f_(v[2].z) + f_(v[3].z)), (f_(v[0].w) + f_(v[1].w)) + (f_(v[2].w) + f_(v[3].w)));
                }
            }
            uint32_t qa, ka[6];
            {
                LANE_IDS
                const uint4* p = pin(&g_scr.qx[h * 4 * 48 + min(tl, 47)]);
                qa = pin(SM_QS + (2 * t + (g & 1)) * 48);
#pragma unroll
                for (int i = 0; i < 6; i++) ka[i] = pin(xtile + K_OFF(i));
                __syncthreads();
                if (wu < 2) {
                    uint4 v[4];
#pragma unroll
                    for (int k = 0; k < 4; k++) v[k] = ld_pkt(p + 48 * k);
                    float mean, inv;
                    ln_stats(mean, inv);
                    const int tc = min(tl, 47);
                    const float4 cs = lds128f(SM_CS + 16 * tc);
                    mean *= -inv;
                    const float m0 = pin(mean * cs.x), m1 = pin(mean * cs.y), m2 = pin(mean * cs.z), m3 = pin(mean * cs.w);
                    const int w = 2 * tc;
                    const uint32_t qd = pin(SM_QS + 4 * (((w >> 2) & 3) * 24 + 2 * (w >> 4) + ((w >> 1) & 1)));
                    int it = 0;
                    bool more = true;
                    while (__any_sync(0xffffffffu, ((v[0].w ^ tbit) | (v[1].w ^ tbit) | (v[2].w ^ tbit) | (v[3].w ^ tbit)) & 1) && more) {
#pragma unroll
                        for (int k = 0; k < 4; k++) v[k] = ld_pkt(p + 48 * k);
                        more = ++it < SPIN_CAP;
                    }
                    DBG(it, 3 + 100 * layer);
                    sts32(qd, pack2(fmaf(inv, (f_(v[0].x) + f_(v[1].x)) + (f_(v[2].x) + f_(v[3].x)), m0), fmaf(inv, (f_(v[0].y) + f_(v[1].y)) + (f_(v[2].y) + f_(v[3].y)), m1)));
                    sts32(qd + 48, pack2(fmaf(inv, (f_(v[0].z) + f_(v[1].z)) + (f_(v[2].z) + f_(v[3].z)), m2), fmaf(inv, (f_(v[0].w) + f_(v[1].w)) + (f_(v[2].w) + f_(v[3].w)), m3)));
                }
            }
            if (layer) PC(29);
            __syncthreads();
            if (layer) PC(30);
            PROF_T(2 + layer * 16);
            {
                uint32_t qf[12];
#pragma unroll
                for (int i = 0; i < 3; i++) lds128(qa + 16 * i, qf[4 * i], qf[4 * i + 1], qf[4 * i + 2], qf[4 * i + 3]);
                const int t = opq(tid) & 3;
#define KR_SCORES(T0) { \
                _Pragma("unroll") for (int tau = T0; tau < T0 + 2; tau++) { \
                    float cA[4] = {0.f, 0.f, 0.f, 0.f}, cB[4] = {0.f, 0.f, 0.f, 0.f}; \
                    _Pragma("unroll") for (int i = 0; i < 6; i++) { \
                        mma16816(cA, kr[tau][i][0], kr[tau][i][1], kr[tau][i][2], kr[tau][i][3], qf[2 * i], qf[2 * i + 1]); \
                        mma16816(cB, kr[tau][6 + i][0], kr[tau][6 + i][1], kr[tau][6 + i][2], kr[tau][6 + i][3], qf[2 * i], qf[2 * i + 1]); \
                    } \
                    if (t == tau) { sc0 = cA[0] + cA[3]; sc1 = cB[0] + cB[3]; } \
                } }
                if (layer == 1) {
                    mbar_wait(xb, 0);
                    PROF_D(34);
                    float cA[4] = {0.f, 0.f, 0.f, 0.f}, cB[4] = {0.f, 0.f, 0.f, 0.f};
                    uint32_t f[6][4];
#pragma unroll
                    for (int i = 0; i < 3; i++) {
                        lds128(ka[i], f[2 * i][0], f[2 * i][1], f[2 * i][2], f[2 * i][3]);
                        lds128(ka[i] + 3072, f[2 * i + 1][0], f[2 * i + 1][1], f[2 * i + 1][2], f[2 * i + 1][3]);
                    }
#pragma unroll
                    for (int i = 0; i < 3; i++) {
                        mma16816v(cA, f[2 * i][0], f[2 * i][1], f[2 * i][2], f[2 * i][3], qf[2 * i], qf[2 * i + 1]);
                        lds128(ka[3 + i], f[2 * i][0], f[2 * i][1], f[2 * i][2], f[2 * i][3]);
                        mma16816v(cB, f[2 * i + 1][0], f[2 * i + 1][1], f[2 * i + 1][2], f[2 * i + 1][3], qf[2 * i], qf[2 * i + 1]);
                        lds128(ka[3 + i] + 3072, f[2 * i + 1][0], f[2 * i + 1][1], f[2 * i + 1][2], f[2 * i + 1][3]);
                    }
                    __syncwarp();
                    tile_load(xtile, &maps.k, row0 + 5 * TS, xb);
#pragma unroll
                    for (int i = 0; i < 3; i++) {
                        mma16816v(cA, f[2 * i][0], f[2 * i][1], f[2 * i][2], f[2 * i][3], qf[6 + 2 * i], qf[7 + 2 * i]);
                        mma16816v(cB, f[2 * i + 1][0], f[2 * i + 1][1], f[2 * i + 1][2], f[2 * i + 1][3], qf[6 + 2 * i], qf[7 + 2 * i]);
                    }
                    sc2 = cA[0] + cA[3]; sc3 = cB[0] + cB[3];
                }
                KR_SCORES(0)
                if (layer == 1) {
                    const int lane = opq(tid) & 31, g = lane >> 2, t = lane & 3;
#pragma unroll
                    for (int s = 0; s < 2; s++) {
#pragma unroll
                        for (int i = 0; i < 6; i++) {
                            const uint32_t a = ring + s * TILE + V_OFF(i);
                            lds128(a, kr[s][i][0], kr[s][i][1], kr[s][i][2], kr[s][i][3]);
                            lds128(a + 3072, kr[s][6 + i][0], kr[s][6 + i][1], kr[s][6 + i][2], kr[s][6 + i][3]);
                        }
                        __syncwarp();
                        tile_load(ring + s * TILE, &maps.k, row0 + (6 + s) * TS, rb + s * 8);
                    }
                }
                KR_SCORES(2)
#undef KR_SCORES
                if (layer == 0) {
                    LANE_IDS
#pragma unroll 1
                    for (int s = 4; s < 8; s++) {
                        mbar_wait(rb + (s & 1) * 8, (s >> 1) & 1);
                        const uint32_t tile = ring + (s & 1) * TILE;
                        float cA[4] = {0.f, 0.f, 0.f, 0.f}, cB[4] = {0.f, 0.f, 0.f, 0.f};
#pragma unroll
                        for (int i = 0; i < 6; i++) {
                            uint32_t a0, a1, a2, a3;
                            lds128(tile + K_OFF(i), a0, a1, a2, a3);
                            mma16816(cA, a0, a1, a2, a3, qf[2 * i], qf[2 * i + 1]);
                            lds128(tile + K_OFF(i) + 3072, a0, a1, a2, a3);
                            mma16816(cB, a0, a1, a2, a3, qf[2 * i], qf[2 * i + 1]);
                        }
                        if (t == (s & 3)) { sc2 = cA[0] + cA[3]; sc3 = cB[0] + cB[3]; }
                        __syncwarp();
                        refill1(s);
                    }
                } else {
                    LANE_IDS
#pragma unroll 1
                    for (int i = 1; i < 4; i++) {
                        const int sl = i - 1;
                        const uint32_t tile = sl ? ring + (sl - 1) * TILE : xtile, tb = sl ? rb + (sl - 1) * 8 : xb;
                        mbar_wait(tb, i == 1);
                        PROF_D(34 + i);
#pragma unroll
                        for (int k = 0; k < 6; k++) {
                            const uint32_t a = tile + K_OFF(k);
                            lds128(a, kr[2][k][0], kr[2][k][1], kr[2][k][2], kr[2][k][3]);
                            lds128(a + 3072, kr[2][6 + k][0], kr[2][6 + k][1], kr[2][6 + k][2], kr[2][6 + k][3]);
                        }
                        float cA[4] = {0.f, 0.f, 0.f, 0.f}, cB[4] = {0.f, 0.f, 0.f, 0.f}, cC[4] = {0.f, 0.f, 0.f, 0.f}, cD[4] = {0.f, 0.f, 0.f, 0.f};
#pragma unroll
                        for (int k = 0; k < 3; k++) {
                            mma16816(cA, kr[2][k][0], kr[2][k][1], kr[2][k][2], kr[2][k][3], qf[2 * k], qf[2 * k + 1]);
                            mma16816(cB, kr[2][6 + k][0], kr[2][6 + k][1], kr[2][6 + k][2], kr[2][6 + k][3], qf[2 * k], qf[2 * k + 1]);
                            mma16816(cC, kr[2][3 + k][0], kr[2][3 + k][1], kr[2][3 + k][2], kr[2][3 + k][3], qf[6 + 2 * k], qf[7 + 2 * k]);
                            mma16816(cD, kr[2][9 + k][0], kr[2][9 + k][1], kr[2][9 + k][2], kr[2][9 + k][3], qf[6 + 2 * k], qf[7 + 2 * k]);
                        }
                        __syncwarp();
                        tile_load(tile, &maps.v, row0 + (i + 1) * TS, tb);
                        if (t == i) { sc2 = (cA[0] + cC[0]) + (cA[3] + cC[3]); sc3 = (cB[0] + cD[0]) + (cB[3] + cD[3]); }
                    }
                }
            }
            {
                const uint32_t mk = __reduce_max_sync(0xffffffffu, f2key(fmaxf(fmaxf(sc0, sc1), fmaxf(sc2, sc3))));
                if ((opq(tid) & 31) == 0) st_pkt2(&g_scr.mx[h * 32 + c * 8 + wu], mk, tag);
                mw = key2f(mk);
            }
            pk0 = pack2(ex2((sc0 - mw) * SC), ex2((sc1 - mw) * SC));
            pk1 = pack2(ex2((sc2 - mw) * SC), ex2((sc3 - mw) * SC));
            sc2 = (bf_lo(pk0) + bf_hi(pk0)) + (bf_lo(pk1) + bf_hi(pk1));
#pragma unroll
            for (int o = 16; o > 0; o >>= 1) sc2 += __shfl_xor_sync(0xffffffffu, sc2, o);
#pragma unroll
            for (int s = 0; s < 3; s++) { acc[s][0] = acc[s][1] = acc[s][2] = acc[s][3] = 0.f; }
            auto head_ld = [&](int lane) { const uint2 mv = ld_pkt2(&g_scr.mx[h * 32 + lane]); sc0 = f_(mv.x); sc1 = f_(mv.y); };
            auto head_factor = [&](int lane) {
                int it = 0;
                while (!__all_sync(0xffffffffu, __float_as_uint(sc1) == tag) && ++it < SPIN_CAP) head_ld(lane);
                DBG(it, 4 + 100 * layer);
                sc3 = ex2((mw - key2f(__reduce_max_sync(0xffffffffu, __float_as_uint(sc0)))) * SC);
            };
#define P_CONSTS \
                const uint32_t sel0 = g == 0 ? 0x4410u : (g == 1 ? 0x1044u : 0x4444u); \
                const uint32_t sel1 = g == 2 ? 0x4410u : (g == 3 ? 0x1044u : 0x4444u); \
                const int src00 = 4 * (t < 2 ? 4 * t : 4 * (t - 2) + 1);
#define P_FRAGS(tau) \
                const uint32_t pk = ((tau) & 4) ? pk1 : pk0; \
                const uint32_t w0 = __shfl_sync(0xffffffffu, pk, src00 + ((tau) & 3)); \
                const uint32_t w1 = __shfl_sync(0xffffffffu, pk, src00 + ((tau) & 3) + 8); \
                uint32_t pb[4][2]; \
                _Pragma("unroll") for (int j = 0; j < 4; j++) { \
                    const uint32_t src = ((j & 1) ? w1 : w0) >> ((j >> 1) * 16); \
                    pb[j][0] = __byte_perm(src, 0, sel0); pb[j][1] = __byte_perm(src, 0, sel1); \
                }
            if (layer == 0) {
#pragma unroll 1
                for (int s = 8; s < 16; s++) {
                    LANE_IDS
                    P_CONSTS
                    if (RESET_AT == s) {
                        uint4* p = nullptr;
                        if (tl < 48) p = &g_scr.qx[b * 48 + tl];
                        else if (tl < 98) p = &g_scr.cx[b * 56 + tl - 48];
                        else if (tl < 145) {}
                        else if (tl >= 160) { if (tl < 208) p = &g_scr.qc[b * 48 + tl - 160]; }
                        else if (b < NG) { if (tl < 153) p = &g_scr.ah[b * 8 + tl - 145]; }
                        else if (b < DN0 + NDN && tl < 149) p = &g_scr.ay[(b - DN0) * 4 + tl - 145];
                        if (p) st_pkt(p, 0, 0, 0, tl < 48);
                    }
                    if (s == 13) head_ld(lane);
                    P_FRAGS((s + 2) & 7)
                    mbar_wait(rb + (s & 1) * 8, (s >> 1) & 1);
                    const uint32_t tile = ring + (s & 1) * TILE;
#pragma unroll
                    for (int j = 0; j < 4; j++) {
#pragma unroll
                        for (int u = 0; u < 3; u++) {
                            uint32_t a0, a1, a2, a3;
                            lds128(tile + (j >> 1) * 3072 + V_OFF(3 * (j & 1) + u), a0, a1, a2, a3);
                            mma16816(acc[u], a0, a1, a2, a3, pb[j][0], pb[j][1]);
                        }
                    }
                    __syncwarp();
                    if (s < 14) refill1(s, true);
                    if (s == 13) head_factor(lane);
                    if (wu == 7 && s == WO_AT && elect_one()) {
                        PROF_X(47);
                        load_wo(maps, SM_B, h, c, WBAR, 5);
                    }
                }
            } else {
                LANE_IDS
                P_CONSTS
#pragma unroll
                for (int s = 0; s < 2; s++) {
                    P_FRAGS(s)
#pragma unroll
                    for (int j = 0; j < 4; j++) {
#pragma unroll
                        for (int u = 0; u < 3; u++) {
                            const int k = 6 * (j >> 1) + 3 * (j & 1) + u;
                            mma16816(acc[u], kr[s][k][0], kr[s][k][1], kr[s][k][2], kr[s][k][3], pb[j][0], pb[j][1]);
                        }
                    }
                }
#pragma unroll 1
                for (int i = 4; i < 10; i++) {
                    const int sl = i == 4 ? 0 : 2 - (i & 1);
                    const uint32_t tile = sl ? ring + (sl - 1) * TILE : xtile, tb = sl ? rb + (sl - 1) * 8 : xb;
                    if (i == 8) head_ld(lane);
                    if (i == 9) head_factor(lane);
                    P_FRAGS(i - 2)
                    mbar_wait(tb, (0x260 >> i) & 1);
                    PROF_D(34 + i);
#pragma unroll
                    for (int k = 0; k < 6; k++) {
                        const uint32_t a = tile + V_OFF(k);
                        lds128(a, kr[2][k][0], kr[2][k][1], kr[2][k][2], kr[2][k][3]);
                        lds128(a + 3072, kr[2][6 + k][0], kr[2][6 + k][1], kr[2][6 + k][2], kr[2][6 + k][3]);
                    }
#pragma unroll
                    for (int j = 0; j < 4; j++) {
#pragma unroll
                        for (int u = 0; u < 3; u++) {
                            const int k = 6 * (j >> 1) + 3 * (j & 1) + u;
                            mma16816(acc[u], kr[2][k][0], kr[2][k][1], kr[2][k][2], kr[2][k][3], pb[j][0], pb[j][1]);
                        }
                    }
                    __syncwarp();
                    if (wu < L1R && i == 6 - (wu & 1)) tile_load_l1(tile, maps.vp, row0 + i * TS, tb, lane);
                    else if (i < 8 && i >= 5) tile_load(tile, &maps.v, row0 + i * TS, tb);
                    if (i == WO_AT1 && HAS_FFN && elect_one()) {
                        uint32_t n;
                        asm volatile("atom.shared.add.u32 %0, [%1], 1;" : "=r"(n) : "r"(SM_MISC + 8) : "memory");
                        if (n == 7u) {
                            PROF_X(63);
                            load_wo(maps, SM_Q, h, c, WBAR, KEEP4 && role >= DN0 ? 4 : 5);
                        }
                    }
                }
            }
#undef P_FRAGS
#undef P_CONSTS
#undef LANE_IDS
#undef K_OFF
#undef V_OFF
        }
        PROF_D(3 + layer * 16);
        PC(layer * 32 + 1);

        uint32_t ticket = 0;
        uint4* pr;
        {
            const int tl = opq(tid), warp = tl >> 5, lane = tl & 31, g = lane >> 2, t = lane & 3, mat = lane >> 3, r8 = lane & 7;
            {
                const uint32_t d = SM_R + 4 * (warp * 196 + 8 * g + 4 * t);
                if (t < 2) {
#pragma unroll
                    for (int u = 0; u < 3; u++) sts128(d + 256 * u, acc[u][0] * sc3, acc[u][1] * sc3, acc[u][2] * sc3, acc[u][3] * sc3);
                }
                if (lane == 0) sts128(d + 768, sc2 * sc3, 0.f, 0.f, 0.f);
            }
            const int tc = min(tl, 48);
            uint4* pc = opq(&g_scr.cx[h * 4 * 56 + tc]);
            uint4* po = opq(pc + c * 56);
            const uint32_t fa = opq(SM_R + 16 * tc);
            __syncthreads();
            PROF_T(4 + layer * 16);
            PC(layer * 32 + 2);
            const int kg = warp >> 1, mg = warp & 1;
            const bool wo2 = layer && HAS_FFN;
            const bool wo4 = wo2 && !(KEEP4 && role >= DN0);
            uint32_t aw, oa, ob0, dw;
            uint32_t* tk;
            auto addrs = [&]() {
                aw = pin((wo2 ? SM_Q : SM_B) + (48 * kg + (mat >> 1) * 8 + r8) * 64 + (((2 * mg + (mat & 1)) ^ ((r8 >> 1) & 3)) << 4));
                oa = pin(SM_OS + 96 * kg + 8 * t);
                ob0 = pin(oa + 8 * t);
                dw = pin(SM_R + 4 * (4 * (16 * mg + g) + kg));
                tk = opq(g_scr.ticket + 0);
                if (HOIST & 2) pr = pin(&g_scr.acc[layer][(54 * c + min(tl, 53)) * ACC_STR]);
            };
            uint32_t a[NWPRE][3][4];
            auto preload = [&]() {
#pragma unroll
                for (int i = 0; i < NWPRE; i++) {
                    mbar_wait(WBAR + 8 * i, wo2);
#pragma unroll
                    for (int ks = 0; ks < 3; ks++) ldsm4t(aw + i * 12288 + ks * 1024, a[i][ks]);
                }
            };
            if (wu < 2) {
                if (tl < 49) {
                    float4 v[8];
#pragma unroll
                    for (int w = 0; w < 8; w++) v[w] = lds128f(fa + w * 784);
                    st_pktf(po, ((v[0].x + v[1].x) + (v[2].x + v[3].x)) + ((v[4].x + v[5].x) + (v[6].x + v[7].x)),
                            ((v[0].y + v[1].y) + (v[2].y + v[3].y)) + ((v[4].y + v[5].y) + (v[6].y + v[7].y)),
                            ((v[0].z + v[1].z) + (v[2].z + v[3].z)) + ((v[4].z + v[5].z) + (v[6].z + v[7].z)),
                            ((v[0].w + v[1].w) + (v[2].w + v[3].w)) + ((v[4].w + v[5].w) + (v[6].w + v[7].w)), tbit);
                }
                __syncwarp();
                uint4 v[4];
#pragma unroll
                for (int k = 0; k < 4; k++) v[k] = ld_pkt(pc + k * 56);
                asm volatile("bar.arrive 1, 256;" ::: "memory");
                addrs();
                const int w = 2 * tc, k3 = w / 24, r = w - 24 * k3;
                const uint32_t d0 = pin(tl < 48 ? SM_OS + 4 * (24 * k3 + (r < 16 ? 4 * (r & 3) + (r >> 2) : 16 + 2 * (r & 3) + ((r >> 2) & 1))) : SM_MISC);
                const uint32_t d1 = pin(tl < 48 ? d0 + (r < 16 ? 16 : 8) : SM_MISC + 12);
                int it = 0;
                bool more = true;
                while (__any_sync(0xffffffffu, ((v[0].w ^ tbit) | (v[1].w ^ tbit) | (v[2].w ^ tbit) | (v[3].w ^ tbit)) & 1) && more) {
#pragma unroll
                    for (int k = 0; k < 4; k++) v[k] = ld_pkt(pc + k * 56);
                    more = ++it < SPIN_CAP;
                }
                DBG(it, 5 + 100 * layer);
                const float o0 = (f_(v[0].x) + f_(v[1].x)) + (f_(v[2].x) + f_(v[3].x));
                const uint32_t w0 = pack2(o0, (f_(v[0].y) + f_(v[1].y)) + (f_(v[2].y) + f_(v[3].y)));
                sts32(d1, pack2((f_(v[0].z) + f_(v[1].z)) + (f_(v[2].z) + f_(v[3].z)), (f_(v[0].w) + f_(v[1].w)) + (f_(v[2].w) + f_(v[3].w))));
                sts32(d0, tl < 48 ? w0 : __float_as_uint(o0));
                asm volatile("bar.arrive 2, 256;" ::: "memory");
                PC(layer * 32 + 3);
                preload();
                asm volatile("bar.sync 3, 64;" ::: "memory");
            } else {
                addrs();
                asm volatile("bar.sync 1, 256;" ::: "memory");
                preload();
                PC(layer * 32 + 3);
                asm volatile("bar.sync 2, 256;" ::: "memory");
            }
            PROF_T(5 + layer * 16);
            PC(layer * 32 + 5);
            uint32_t ob[6];
            lds128(ob0, ob[0], ob[1], ob[2], ob[3]);
            lds64(oa + 64, ob[4], ob[5]);
            if (tl == 224 && layer == 0)
                asm volatile("atom.relaxed.gpu.global.inc.u32 %0, [%1], 0x7fffffff;" : "=r"(ticket) : "l"(tk) : "memory");
            auto put = [&](int i, const float (&cc)[4]) { if (t == 0) { sts32(dw + 512 * i, cc[0]); sts32(dw + 512 * i + 128, cc[2]); } };
            {
                float c0[4] = {0.f, 0.f, 0.f, 0.f}, c1[4] = {0.f, 0.f, 0.f, 0.f}, c2[4] = {0.f, 0.f, 0.f, 0.f}, c3[4] = {0.f, 0.f, 0.f, 0.f};
                mbar_wait(WBAR + 16, wo2);
#pragma unroll
                for (int ks = 0; ks < 3; ks++) {
                    mma16816v(c0, a[0][ks][0], a[0][ks][1], a[0][ks][2], a[0][ks][3], ob[2 * ks], ob[2 * ks + 1]);
                    mma16816v(c1, a[1][ks][0], a[1][ks][1], a[1][ks][2], a[1][ks][3], ob[2 * ks], ob[2 * ks + 1]);
                    if (ks == 0) mbar_wait(WBAR + 24, wo2);
                    if (ks == 1) mbar_wait(WBAR + 32, wo4);
#pragma unroll
                    for (int i = 0; i < 2; i++) ldsm4t(aw + (2 + i) * 12288 + ks * 1024, a[i][ks]);
                }
                const uint32_t aw4 = aw + (wo2 && !wo4 ? SM_B - SM_Q : 0) + 4 * 12288;
#pragma unroll
                for (int ks = 0; ks < 3; ks++) {
                    mma16816v(c2, a[0][ks][0], a[0][ks][1], a[0][ks][2], a[0][ks][3], ob[2 * ks], ob[2 * ks + 1]);
                    mma16816v(c3, a[1][ks][0], a[1][ks][1], a[1][ks][2], a[1][ks][3], ob[2 * ks], ob[2 * ks + 1]);
                    if (ks == 0) { ldsm4t(aw4, a[0][0]); ldsm4t(aw4 + 1024, a[1][0]); put(0, c0); put(1, c1); }
                    if (ks == 1) ldsm4t(aw4 + 2048, a[0][1]);
                }
                float c4[4] = {0.f, 0.f, 0.f, 0.f}, c5[4] = {0.f, 0.f, 0.f, 0.f};
                mma16816v(c4, a[0][0][0], a[0][0][1], a[0][0][2], a[0][0][3], ob[0], ob[1]);
                mma16816v(c5, a[1][0][0], a[1][0][1], a[1][0][2], a[1][0][3], ob[2], ob[3]);
                mma16816v(c4, a[0][1][0], a[0][1][1], a[0][1][2], a[0][1][3], ob[4], ob[5]);
                put(2, c2); put(3, c3);
                c4[0] += c5[0]; c4[2] += c5[2];
                put(4, c4);
            }
        }
        {
            const int tl = opq(tid);
            if (!(HOIST & 2)) pr = opq(&g_scr.acc[layer][(54 * c + min(tl, 53)) * ACC_STR]);
            const uint32_t fa = opq(SM_R + 48 * tl);
            const float il = rcp(f_(lds32(SM_MISC)));
            PC(layer * 32 + 6);
            __syncthreads();
            PROF_D(6 + layer * 16);
            PC(layer * 32 + 7);
            if (tl < 54) {
                const float4 v0 = lds128f(fa), v1 = lds128f(fa + 16), v2 = lds128f(fa + 32);
                const float y0 = il * ((v0.x + v0.y) + (v0.z + v0.w)), y1 = il * ((v1.x + v1.y) + (v1.z + v1.w)), y2 = il * ((v2.x + v2.y) + (v2.z + v2.w));
                red_pkt(pr, y0, tl == 53 ? 0.f : y1, tl == 53 ? 0.f : y2);
            }
            if (tl == 224 && layer == 0) {
                sts32(SM_MISC + 4, ticket);
                if (ticket < DN0 + NDN && (ticket < NG || !DNTH)) load_ffn(maps, ticket, SM_B, FBAR);
            }
        }
        PROF_T(7 + layer * 16);
        PC(layer * 32 + 8);
        __syncthreads();
        if (layer == 0) role = __shfl_sync(0xffffffffu, (int)lds32(SM_MISC + 4), 0);
        PC(layer * 32 + 9);
        const uint32_t DONE32 = 0x42000000u;
        if (role < NG) {
            const int tl = opq(tid), warp = tl >> 5, lane = tl & 31, g = lane >> 2, t = lane & 3, mat = lane >> 3, r8 = lane & 7;
            const uint32_t ag = SM_B + (80 * warp + (mat >> 1) * 8 + r8) * 96 + (((mat & 1) ^ (r8 >> 2)) << 4);
            constexpr int GI = 32, GK = 16 * 96;
            const bool on = (g & 1) == (t >> 1), isx = (on && g < 2) || g == 4;
            const uint32_t pm = opq(isx ? SM_XS + 160 * warp + 16 * t : (on || g == 5 ? SM_ONE : SM_ZERO)), pm2 = opq(pm + 128 - (isx ? 8 * t : 0));
            const uint32_t dg = opq(SM_R + 4 * (2 * (warp * 48 + g) + t));
            uint32_t ho = HOIST & 4 ? pin(16u * (role * 8 + 4 * warp + ((lane * 11) >> 5))) : 0;
            uint32_t fa = HOIST & 8 ? pin(SM_R + 8 * (24 * warp + 2 * min(lane, 11))) : 0;
            uint32_t pre[9][4];
            {
                bool hx = wu == 7;
                int it = 0;
                const uint4* px = opq(&g_scr.acc[layer][min(tl, 215) * ACC_STR]);
                const int cq = tl / 54, r = tl - 54 * cq, k0 = min(160 * cq + 3 * r, DM - 1);
                const uint32_t w0 = SM_XS + 4 * xpos(k0 >> 1), w1 = SM_XS + 4 * xpos(min((k0 >> 1) + 1, DM / 2 - 1));
                const bool two = tl < 216 && r != 53;
                const uint32_t e0 = opq(tl < 216 ? w0 + 2 * (k0 & 1) : SM_MISC + 12);
                const uint32_t e1 = opq(two ? ((k0 & 1) ? w1 : w0 + 2) : SM_MISC + 12), e2 = opq(two ? w1 + 2 * (k0 & 1) : SM_MISC + 12);
                const uint32_t x01 = opq(lds16(e0) | (lds16(e1) << 16)), x2 = lds16(e2);
                auto take_x = [&](const uint4 v) {
                    if (__all_sync(0xffffffffu, v.w == DONE32)) {
                        hx = true;
                        const uint32_t y01 = add2(x01, pack2(f_(v.x), f_(v.y))), y2 = add2(x2, pack2(f_(v.z), 0.f));
                        sts16(e0, y01); sts16(e1, y01 >> 16); sts16(e2, y2);
                    }
                };
                while (!mbar_test(FBAR, 0) && ++it < SPIN_CAP) { if (!hx) take_x(ld_pkt(px)); }
                uint4 v = make_uint4(0u, 0u, 0u, 0u);
                if (!hx) v = ld_pkt(px);
#pragma unroll
                for (int n = 0; n < 9; n++) ldsm4t(ag + (n % 3) * GI + (n / 3) * GK, pre[n]);
                if (layer) {
#pragma unroll
                    for (int n = 9; n < 15; n++) ldsm4t(ag + (n % 3) * GI + (n / 3) * GK, kr[0][n - 9]);
                }
                PC(layer * 32 + 10);
                if (!hx) {
                    bool more = true;
                    while (!__all_sync(0xffffffffu, v.w == DONE32) && more) { v = ld_pkt(px); more = ++it < SPIN_CAP; }
                    const uint32_t y01 = add2(x01, pack2(f_(v.x), f_(v.y))), y2 = add2(x2, pack2(f_(v.z), 0.f));
                    sts16(e0, y01); sts16(e1, y01 >> 16); sts16(e2, y2);
                }
                DBG(it, 6 + 100 * layer);
                PC(layer * 32 + 11);
            }
            __syncthreads();
            PC(layer * 32 + 12);
            PROF_T(9 + layer * 16);
            {
                float cc[3][4], gr[4];
                if (layer) gemv15r(cc, gr, pre, kr[0], pm, pm2);
                else gemv15<GK, true>(cc, gr, pre, [&](int i) { return ag + i * GI; }, pm, pm2);
                if (t < 2) {
#pragma unroll
                    for (int i = 0; i < 3; i++) { sts32(dg + 128 * i, cc[i][0] + cc[i][3]); sts32(dg + 128 * i + 64, cc[i][1] + cc[i][2]); }
                }
                if ((lane | 4) == 22) sts32(SM_ST + 8 * warp + (g & 1) * 4, gr[0]);
            }
            if (!(HOIST & 8)) fa = opq(SM_R + 8 * (24 * warp + 2 * min(lane, 11)));
            if (!(HOIST & 4)) ho = 16u * (role * 8 + 4 * warp + ((lane * 11) >> 5));
            uint4* ph = reinterpret_cast<uint4*>(reinterpret_cast<char*>(g_scr.ah) + ho);
            const bool snd = (0x249 >> lane) & 1;
            PC(layer * 32 + 13);
            __syncthreads();
            PC(layer * 32 + 14);
            PROF_D(43 + layer * 16);
            if (wu < 2) {
                float mean, inv;
                float4 v[8];
#pragma unroll
                for (int w = 0; w < 8; w++) v[w] = lds128f(fa + w * 384);
                ln_stats(mean, inv);
                const float ga = inv * ((((v[0].x + v[1].x) + (v[2].x + v[3].x)) + ((v[4].x + v[5].x) + (v[6].x + v[7].x))) -
                                        mean * (((v[0].y + v[1].y) + (v[2].y + v[3].y)) + ((v[4].y + v[5].y) + (v[6].y + v[7].y))));
                const float gb = inv * ((((v[0].z + v[1].z) + (v[2].z + v[3].z)) + ((v[4].z + v[5].z) + (v[6].z + v[7].z))) -
                                        mean * (((v[0].w + v[1].w) + (v[2].w + v[3].w)) + ((v[4].w + v[5].w) + (v[6].w + v[7].w))));
                uint32_t wd = pack2(ga, gb);
                if (role < NG / 2) {
                    const float g0 = bf_lo(wd), g1 = bf_hi(wd);
                    wd = pack2(g0 * rcp(1.0f + ex2(-1.4426950408889634f * g0)), g1 * rcp(1.0f + ex2(-1.4426950408889634f * g1)));
                }
                const uint32_t wa = __shfl_down_sync(0xffffffffu, wd, 1), wb = __shfl_down_sync(0xffffffffu, wd, 2);
                if (snd) st_pkt(ph, wd, wa, wb, tag);
            }
            if (HOLD & 2) __syncthreads();
            PROF_T(10 + layer * 16);
            PC(layer * 32 + 15);
        } else if (role < DN0 + NDN) {
            const int j = role - DN0;
            const int tl = opq(tid), warp = tl >> 5, lane = tl & 31, g = lane >> 2, t = lane & 3, mat = lane >> 3, r8 = lane & 7;
            float xr0 = 0.f, xr1 = 0.f;
            if (wu == 0) {
                const int col = 16 * j + (lane & 15), cc = col / 160, r = col - 160 * cc, e = r % 3;
                const uint4* px = &g_scr.acc[layer][(54 * cc + r / 3) * ACC_STR];
                const float x0 = bf_lo(lds16(SM_XS + 4 * xpos(col >> 1) + 2 * (col & 1)));
                uint4 v;
                int it = 0;
                bool ld = DNTH && layer == 0;
                do {
                    v = ld_pkt(px);
                    if (ld && f_(__shfl_sync(0xffffffffu, v.w, 0)) >= (float)DNTH) { ld = false; if (lane == 0) load_ffn(maps, role, SM_B, FBAR); }
                } while (!__all_sync(0xffffffffu, v.w == DONE32) && ++it < SPIN_CAP);
                DBG(it, 7 + 100 * layer);
                if (ld && lane == 0) load_ffn(maps, role, SM_B, FBAR);
                const float xres = bfr(x0 + bfr(f_(e == 0 ? v.x : (e == 1 ? v.y : v.z))));
                xr0 = __shfl_sync(0xffffffffu, xres, 2 * (lane & 7));
                xr1 = __shfl_sync(0xffffffffu, xres, 2 * (lane & 7) + 1);
            }
            PC(layer * 32 + 17);
            PROF_T(9 + layer * 16);
            const uint32_t ad = SM_B + (192 * warp + (mat >> 1) * 8 + r8) * 32 + (((mat & 1) ^ (r8 >> 2)) << 4);
            const uint32_t hs = SM_R + 384 * warp, hb = opq(hs + 16 * t), dd = opq(SM_R + 3072 + 4 * (warp * 16 + g));
            uint32_t pre[NPRE][4];
            uint32_t pos[3];
#pragma unroll
            for (int i = 0; i < 3; i++) { const int w = 3 * lane + i; pos[i] = opq(hs + 4 * ((w & ~15) + 4 * (w & 3) + ((w >> 2) & 1) + ((w >> 2) & 2))); }
            const uint4* ph = opq(&g_scr.ah[tl]);
            const uint32_t fa = opq(SM_R + 3072 + 8 * (lane & 7));
            uint2* py = opq(reinterpret_cast<uint2*>(g_scr.ay) + 8 * j + (lane & 7));
            uint32_t* po = opq(reinterpret_cast<uint32_t*>(out) + 8 * j + (lane & 7));
            mbar_wait(FBAR, 0);
#pragma unroll
            for (int n = 0; n < NPRE; n++) ldsm4t(ad + n * 512, pre[n]);
            PC(layer * 32 + 18);
            {
                uint4 v, u;
                int it = 0;
                bool more;
                if (PD_D) {
                    uint32_t t0, t1; asm volatile("mov.u32 %0, %%clock;" : "=r"(t0));
                    do asm volatile("mov.u32 %0, %%clock;" : "=r"(t1)); while (t1 - t0 < (layer ? PD_D : PD_D0));
                }
                do { v = ld_pkt(ph); u = ld_pkt(ph + 256); more = ++it < SPIN_CAP; }
                while (!__all_sync(0xffffffffu, v.w == tag && u.w == tag) && more);
                DBG(it, 8 + 100 * layer);
                PC(layer * 32 + 19);
                sts32(pos[0], mul2(v.x, u.x)); sts32(pos[1], mul2(v.y, u.y)); sts32(pos[2], mul2(v.z, u.z));
            }
            __syncwarp();
            PROF_T(11 + layer * 16);
            PC(layer * 32 + 20);
            {
                float cc[4][4];
                uint32_t hv[3][4];
#pragma unroll
                for (int jj = 0; jj < 3; jj++) lds128(hb + 64 * jj, hv[jj][0], hv[jj][1], hv[jj][2], hv[jj][3]);
#pragma unroll
                for (int n = 0; n < 12; n++) {
                    const int s = n < NPRE ? n : n - NPRE;
                    if (n < 4) cc[n][0] = cc[n][1] = cc[n][2] = cc[n][3] = 0.f;
                    mma16816v(cc[n & 3], pre[s][0], pre[s][1], pre[s][2], pre[s][3], hv[(n >> 1) % 3][2 * (n & 1)], hv[(n >> 1) % 3][2 * (n & 1) + 1]);
                    if (n + NPRE < 12) ldsm4t(ad + (n + NPRE) * 512, pre[n]);
                    if ((n & 1) && n < 6) lds128(hb + 64 * ((n >> 1) + 3), hv[n >> 1][0], hv[n >> 1][1], hv[n >> 1][2], hv[n >> 1][3]);
                }
                if (t == 0) { sts32(dd, (cc[0][0] + cc[1][0]) + (cc[2][0] + cc[3][0])); sts32(dd + 32, (cc[0][2] + cc[1][2]) + (cc[2][2] + cc[3][2])); }
            }
            PC(layer * 32 + 21);
            __syncthreads();
            PC(layer * 32 + 22);
            if (tl < 8) {
                float2 v[8];
#pragma unroll
                for (int w = 0; w < 8; w++) v[w] = lds64f(fa + 64 * w);
                const uint32_t y = pack2(((v[0].x + v[1].x) + (v[2].x + v[3].x)) + ((v[4].x + v[5].x) + (v[6].x + v[7].x)),
                                         ((v[0].y + v[1].y) + (v[2].y + v[3].y)) + ((v[4].y + v[5].y) + (v[6].y + v[7].y)));
                const uint32_t wd = pack2(xr0 + bf_lo(y), xr1 + bf_hi(y));
                if (layer) asm volatile("st.global.u32 [%0], %1;" ::"l"(po), "r"(wd) : "memory");
                st_pkt2(py, wd, tag);
            }
            if (HOLD & 1) __syncthreads();
            PROF_T(12 + layer * 16);
            PC(layer * 32 + 23);
        }
    }
}

typedef CUresult (*EncodeFn)(CUtensorMap*, CUtensorMapDataType, cuuint32_t, void*, const cuuint64_t*, const cuuint64_t*, const cuuint32_t*,
                             const cuuint32_t*, CUtensorMapInterleave, CUtensorMapSwizzle, CUtensorMapL2promotion, CUtensorMapFloatOOBfill);

void make_map(EncodeFn enc, CUtensorMap* m, const void* base, int rank, uint64_t d0, uint64_t d1, uint64_t d2, uint64_t s1, uint64_t s2,
              uint32_t b0, uint32_t b1, uint32_t b2, CUtensorMapSwizzle sw, CUtensorMapL2promotion pr = CU_TENSOR_MAP_L2_PROMOTION_NONE) {
    cuuint64_t dims[3] = {d0, d1, d2};
    cuuint64_t strides[2] = {s1, s2};
    cuuint32_t box[3] = {b0, b1, b2};
    cuuint32_t es[3] = {1, 1, 1};
    enc(m, CU_TENSOR_MAP_DATA_TYPE_BFLOAT16, rank, const_cast<void*>(base), dims, strides, box, es, CU_TENSOR_MAP_INTERLEAVE_NONE, sw,
        pr, CU_TENSOR_MAP_FLOAT_OOB_FILL_NONE);
}

}

extern "C" void kernel_launch(void* const* d_in, const int* in_sizes, int n_in, void* d_out, int out_size) {
    (void)in_sizes; (void)n_in; (void)out_size;
    static EncodeFn enc = nullptr;
    if (!enc) {
        void* fn = nullptr;
        cudaDriverEntryPointQueryResult qr;
        cudaGetDriverEntryPoint("cuTensorMapEncodeTiled", &fn, cudaEnableDefault, &qr);
        enc = reinterpret_cast<EncodeFn>(fn);
        cudaFuncSetAttribute(decode_kernel, cudaFuncAttributeMaxDynamicSharedMemorySize, SM_TOTAL);
    }
    Maps maps;
    make_map(enc, &maps.k, d_in[1], 2, 64, (uint64_t)NH * SK * 3, 1, 128, 0, 64, 48, 1, CU_TENSOR_MAP_SWIZZLE_128B);
    make_map(enc, &maps.v, d_in[2], 2, 64, (uint64_t)NH * SK * 3, 1, 128, 0, 64, 48, 1, CU_TENSOR_MAP_SWIZZLE_128B);
    {
        cuuint64_t dims[4] = {64, 16, NH * DH / 64, DM / 16};
        cuuint64_t strides[3] = {NH * DH * 2, 128, 16 * NH * DH * 2};
        cuuint32_t box[4] = {64, 16, 3, 10};
        cuuint32_t es[4] = {1, 1, 1, 1};
        enc(&maps.wq, CU_TENSOR_MAP_DATA_TYPE_BFLOAT16, 4, d_in[3], dims, strides, box, es, CU_TENSOR_MAP_INTERLEAVE_NONE, CU_TENSOR_MAP_SWIZZLE_128B,
            CU_TENSOR_MAP_L2_PROMOTION_NONE, CU_TENSOR_MAP_FLOAT_OOB_FILL_NONE);
    }
    make_map(enc, &maps.wo, d_in[4], 3, 32, NH * DH, DM / 32, DM * 2, 64, 32, 192, 1, CU_TENSOR_MAP_SWIZZLE_64B);
    constexpr int GW = 48;
    make_map(enc, &maps.w1, d_in[6], 3, FF, 160, 4, FF * 2, 160 * FF * 2, GW, 160, 4, CU_TENSOR_MAP_SWIZZLE_NONE, FFN_PROMO);
    make_map(enc, &maps.w3, d_in[7], 3, FF, 160, 4, FF * 2, 160 * FF * 2, GW, 160, 4, CU_TENSOR_MAP_SWIZZLE_NONE, FFN_PROMO);
    make_map(enc, &maps.w2, d_in[8], 3, DM, 256, 6, DM * 2, 256 * DM * 2, 16, 256, 6, CU_TENSOR_MAP_SWIZZLE_32B, FFN_PROMO);
    maps.vp = d_in[2];
#define KWD 16
    const int KW = KWD;
    make_map(enc, &maps.ks, d_in[1], 2, 64, (uint64_t)NH * SK * 3, 1, 128, 0, KW, 48, 1, CU_TENSOR_MAP_SWIZZLE_NONE);
    make_map(enc, &maps.vs, d_in[2], 2, 64, (uint64_t)NH * SK * 3, 1, 128, 0, KW, 48, 1, CU_TENSOR_MAP_SWIZZLE_NONE);
    decode_kernel<<<NCTA, NT, SM_TOTAL, cudaStreamPerThread>>>(maps, (const __nv_bfloat16*)d_in[0], (__nv_bfloat16*)d_out);
}
```

```cpp
#include <cuda_runtime.h>
#include <cuda_bf16.h>
#include <cuda.h>
#include <stdint.h>
#include <math.h>
#include <stdlib.h>
#include <stdio.h>

namespace {

constexpr int DM = 640;
constexpr int NH = 32;
constexpr int DH = 192;
constexpr int SK = 32768;
constexpr int WIN = 4096;
constexpr int FF = 1536;
constexpr int NCTA = 128;
constexpr int NT = 256;
constexpr int TILE = 6144;
constexpr int NG = 64;
constexpr int DN0 = 64;
constexpr int NDN = 40;

constexpr uint32_t SB = 1024;
constexpr uint32_t SM_RING = SB;
constexpr uint32_t SM_B = SM_RING + 8 * 2 * TILE;
constexpr uint32_t SM_Q = SM_B + 61440;
constexpr uint32_t SM_XS = SM_Q + 61440;
constexpr uint32_t SM_R = SM_XS + 1280;
constexpr uint32_t SM_ST = SM_R + 4096;
constexpr uint32_t SM_QS = SM_R + 6272;
constexpr uint32_t SM_OS = SM_QS + 384;
constexpr uint32_t SM_CS = SM_OS + 384;
constexpr uint32_t SM_BAR = SM_CS + 768;
constexpr uint32_t SM_XBAR = SM_BAR + 24 * 8;
constexpr uint32_t SM_MISC = SM_XBAR + 8 * 8;
constexpr uint32_t SM_ONE = SM_MISC + 32;
constexpr uint32_t SM_ZERO = SM_ONE + 160;
constexpr uint32_t SM_KX = SM_ZERO + 160;
constexpr uint32_t SM_TOTAL = SM_KX + 8 * 96 - SB;
constexpr int NEXC = 16;
static_assert(SM_TOTAL <= 232448, "shared memory");
constexpr uint32_t QBAR = SM_BAR + 16 * 8, FBAR = QBAR + 8, WBAR = QBAR + 16, QRDY = QBAR + 56;

constexpr unsigned long long POL_EF = 0x12F0000000000000ull;
constexpr unsigned long long POL_EN = 0x1000000000000000ull;

#define RT_MASK 0x2DE0u
#define RT_MASK2 0x36E0u
#define RESET_AT 14
#define WO_AT 15
#define WO_AT1 7
#define FFN_PROMO CU_TENSOR_MAP_L2_PROMOTION_NONE
#define FFN_POL POL_EF
#define HAS_FFN (role < DN0 + NDN)
#define ACC_STR 1
#define NPRE 6

#define HOIST 0
#define PD_G 0
#define PD_R 0
#define PD_D 0
#define PD_D0 0
#define AYS 0
#define G1W 0
#define EARLYQ 3
#define PADN 0
#define PCG 1
#define PCR 1
#define PCD 0
#define L1T 0
#define QAT 3
#define NWPRE 2
#define L1R 3
#define PRE1 5
#define HOLD 3
#define DNTH 23
#define KEEP4 1
#define PRE4 0
#define NEARLY (PRE4 ? 8 : 6)
#define EARLY4 1
#define XCH(w) (w)
#define LAYOUT 1
#define ROW0(w) ((h * SK + (SK - WIN) + c * 1024 + (w) * 128) * 3)
constexpr int TS = 48;
#define CAPL 19
constexpr int SPIN_CAP = 1 << CAPL;
constexpr uint32_t ONES = 0x3F803F80u;

struct Scratch {
    uint4 qx[NCTA * 48];
    uint4 qc[NCTA * 48];
    uint4 cx[NCTA * 56];
    uint4 pad0[160];
    uint4 acc[2][216 * 8];
    uint4 ay[320];
    uint4 ah[NG * 8];
    uint2 mx[NH * 32];
    uint32_t ticket[32];
    uint32_t pad1[32];
};
__device__ Scratch g_scr;
#define DBG(it, site)
#define PROF_T(i)
#define PROF_D(i)
#define PROF_X(i)
#define PC(i)

__device__ __forceinline__ uint32_t smem_u32(const void* p) { return (uint32_t)__cvta_generic_to_shared(p); }
__device__ __forceinline__ void mbar_init(uint32_t bar, uint32_t cnt) {
    asm volatile("mbarrier.init.shared::cta.b64 [%0], %1;" ::"r"(bar), "r"(cnt) : "memory");
}
__device__ __forceinline__ void mbar_expect_tx(uint32_t bar, uint32_t bytes) {
    asm volatile("mbarrier.arrive.expect_tx.shared::cta.b64 _, [%0], %1;" ::"r"(bar), "r"(bytes) : "memory");
}
__device__ __forceinline__ bool mbar_test(uint32_t bar, uint32_t parity) {
    uint32_t done;
    asm volatile("{\n.reg .pred p;\nmbarrier.try_wait.parity.shared::cta.b64 p, [%1], %2;\nselp.u32 %0, 1, 0, p;\n}"
                 : "=r"(done) : "r"(bar), "r"(parity) : "memory");
    return done;
}
__device__ __forceinline__ void mbar_wait(uint32_t bar, uint32_t parity) {
    asm volatile("{\n.reg .pred p;\n.reg .u32 n;\nmov.u32 n, 0;\n"
                 "W: mbarrier.try_wait.parity.shared::cta.b64 p, [%0], %1;\n@p bra D;\n"
                 "add.u32 n, n, 1;\nsetp.lt.u32 p, n, %2;\n@p bra W;\nD:\n}" ::"r"(bar), "r"(parity), "n"(SPIN_CAP) : "memory");
}
__device__ __forceinline__ void tma2d(uint32_t dst, const CUtensorMap* map, int c0, int c1, uint32_t bar, unsigned long long pol) {
    asm volatile("cp.async.bulk.tensor.2d.shared::cluster.global.mbarrier::complete_tx::bytes.L2::cache_hint [%0], [%1, {%3, %4}], [%2], %5;"
                 ::"r"(dst), "l"(map), "r"(bar), "r"(c0), "r"(c1), "l"(pol) : "memory");
}
__device__ __forceinline__ void tma3d(uint32_t dst, const CUtensorMap* map, int c0, int c1, int c2, uint32_t bar, unsigned long long pol) {
    asm volatile("cp.async.bulk.tensor.3d.shared::cluster.global.mbarrier::complete_tx::bytes.L2::cache_hint [%0], [%1, {%3, %4, %5}], [%2], %6;"
                 ::"r"(dst), "l"(map), "r"(bar), "r"(c0), "r"(c1), "r"(c2), "l"(pol) : "memory");
}
__device__ __forceinline__ void tma5d(uint32_t dst, const CUtensorMap* map, int c2, int c3, uint32_t bar, unsigned long long pol) {
    asm volatile("cp.async.bulk.tensor.5d.shared::cluster.global.mbarrier::complete_tx::bytes.L2::cache_hint [%0], [%1, {0, 0, %3, %4, 0}], [%2], %5;"
                 ::"r"(dst), "l"(map), "r"(bar), "r"(c2), "r"(c3), "l"(pol) : "memory");
}
__device__ __forceinline__ void tma2d_pf(const CUtensorMap* map, int c0, int c1, unsigned long long pol) {
    asm volatile("cp.async.bulk.prefetch.tensor.2d.L2.global.L2::cache_hint [%0, {%1, %2}], %3;" ::"l"(map), "r"(c0), "r"(c1), "l"(pol) : "memory");
}
__device__ __forceinline__ void tile_load(uint32_t dst, const CUtensorMap* map, int row, uint32_t bar) {
    asm volatile("{\n.reg .pred p;\nelect.sync _|p, 0xffffffff;\n"
                 "@p mbarrier.arrive.expect_tx.shared::cta.b64 _, [%2], 6144;\n"
                 "@p cp.async.bulk.tensor.2d.shared::cluster.global.mbarrier::complete_tx::bytes.L2::cache_hint [%0], [%1, {0, %3}], [%2], %4;\n}"
                 ::"r"(dst), "l"(map), "r"(bar), "r"(row), "l"(POL_EF) : "memory");
}
__device__ __forceinline__ void tile_keep(const CUtensorMap* map, int row) {
    asm volatile("{\n.reg .pred p;\nelect.sync _|p, 0xffffffff;\n"
                 "@p cp.async.bulk.prefetch.tensor.2d.L2.global.L2::cache_hint [%0, {0, %1}], %2;\n}"
                 ::"l"(map), "r"(row), "l"(POL_EN) : "memory");
}
__device__ __forceinline__ void tile_load_l1(uint32_t dst, const void* base, int row, uint32_t bar, int lane) {
    const char* g = static_cast<const char*>(base) + (size_t)row * 128 + lane * 16;
    const uint32_t s0 = dst + (lane >> 3) * 128 + (((lane & 7) ^ (lane >> 3)) << 4), s1 = s0 ^ 64;
#pragma unroll
    for (int k = 0; k < 12; k++)
        asm volatile("cp.async.ca.shared.global.L2::cache_hint [%0], [%1], 16, %2;" ::"r"(((k & 1) ? s1 : s0) + k * 512), "l"(g + k * 512), "l"(POL_EF) : "memory");
    asm volatile("cp.async.mbarrier.arrive.shared::cta.b64 [%0];" ::"r"(bar) : "memory");
    __syncwarp();
    if (lane == 0) asm volatile("mbarrier.arrive.shared::cta.b64 _, [%0];" ::"r"(bar) : "memory");
}
__device__ __forceinline__ bool elect_one() {
    uint32_t p;
    asm volatile("{\n.reg .pred p;\nelect.sync _|p, 0xffffffff;\nselp.u32 %0, 1, 0, p;\n}" : "=r"(p));
    return p;
}
__device__ __forceinline__ void lds128(uint32_t addr, uint32_t& a, uint32_t& b, uint32_t& c, uint32_t& d) {
    asm volatile("ld.shared.v4.u32 {%0,%1,%2,%3}, [%4];" : "=r"(a), "=r"(b), "=r"(c), "=r"(d) : "r"(addr) : "memory");
}
__device__ __forceinline__ void lds64(uint32_t addr, uint32_t& a, uint32_t& b) {
    asm volatile("ld.shared.v2.u32 {%0,%1}, [%2];" : "=r"(a), "=r"(b) : "r"(addr) : "memory");
}
__device__ __forceinline__ void ldsm4t(uint32_t addr, uint32_t (&a)[4]) {
    asm volatile("ldmatrix.sync.aligned.m8n8.x4.trans.shared.b16 {%0,%1,%2,%3}, [%4];" : "=r"(a[0]), "=r"(a[1]), "=r"(a[2]), "=r"(a[3]) : "r"(addr) : "memory");
}
__device__ __forceinline__ void mma16816(float (&c)[4], uint32_t a0, uint32_t a1, uint32_t a2, uint32_t a3, uint32_t b0, uint32_t b1) {
    asm("mma.sync.aligned.m16n8k16.row.col.f32.bf16.bf16.f32 {%0,%1,%2,%3}, {%4,%5,%6,%7}, {%8,%9}, {%0,%1,%2,%3};"
        : "+f"(c[0]), "+f"(c[1]), "+f"(c[2]), "+f"(c[3]) : "r"(a0), "r"(a1), "r"(a2), "r"(a3), "r"(b0), "r"(b1));
}
__device__ __forceinline__ void mma16816v(float (&c)[4], uint32_t a0, uint32_t a1, uint32_t a2, uint32_t a3, uint32_t b0, uint32_t b1) {
    asm volatile("mma.sync.aligned.m16n8k16.row.col.f32.bf16.bf16.f32 {%0,%1,%2,%3}, {%4,%5,%6,%7}, {%8,%9}, {%0,%1,%2,%3};"
        : "+f"(c[0]), "+f"(c[1]), "+f"(c[2]), "+f"(c[3]) : "r"(a0), "r"(a1), "r"(a2), "r"(a3), "r"(b0), "r"(b1));
}
__device__ __forceinline__ int xpos(int w) {
    const int seg = w / 40, r = w - 40 * seg;
    return 40 * seg + (r < 32 ? (r & 16) + 4 * (r & 3) + ((r >> 2) & 3) : 32 + 2 * (r & 3) + ((r >> 2) & 1));
}
#define NA 0
#define NA_LD ""
#define NA_ST ""
__device__ __forceinline__ void st_pkt(uint4* p, uint32_t a, uint32_t b, uint32_t c, uint32_t d) {
    asm volatile("{\n.reg .b128 t;\n.reg .b64 lo, hi;\nmov.b64 lo, {%1,%2};\nmov.b64 hi, {%3,%4};\nmov.b128 t, {lo,hi};\nst.relaxed.gpu.global" NA_ST ".b128 [%0], t;\n}"
                 ::"l"(p), "r"(a), "r"(b), "r"(c), "r"(d) : "memory");
}
__device__ __forceinline__ void st_pktf(uint4* p, float a, float b, float c, float d, uint32_t bit) {
    st_pkt(p, __float_as_uint(a), __float_as_uint(b), __float_as_uint(c), (__float_as_uint(d) & ~1u) | bit);
}
__device__ __forceinline__ void red_pkt(uint4* p, float a, float b, float c) {
    asm volatile("red.relaxed.gpu.global.add.v4.f32 [%0], {%1,%2,%3,%4};" ::"l"(p), "f"(a), "f"(b), "f"(c), "f"(1.0f) : "memory");
}
__device__ __forceinline__ uint4 ld_pkt(const uint4* p) {
    uint4 v;
    asm volatile("{\n.reg .b128 t;\n.reg .b64 lo, hi;\nld.relaxed.gpu.global" NA_LD ".b128 t, [%4];\nmov.b128 {lo,hi}, t;\nmov.b64 {%0,%1}, lo;\nmov.b64 {%2,%3}, hi;\n}"
                 : "=r"(v.x), "=r"(v.y), "=r"(v.z), "=r"(v.w) : "l"(p) : "memory");
    return v;
}
__device__ __forceinline__ uint2 ld_pkt2(const uint2* p) {
    unsigned long long v;
    asm volatile("ld.relaxed.gpu.global" NA_LD ".b64 %0, [%1];" : "=l"(v) : "l"(p) : "memory");
    return make_uint2((uint32_t)v, (uint32_t)(v >> 32));
}
__device__ __forceinline__ void st_pkt2(uint2* p, uint32_t a, uint32_t b) {
    asm volatile("st.relaxed.gpu.global" NA_ST ".b64 [%0], %1;" ::"l"(p), "l"((unsigned long long)a | ((unsigned long long)b << 32)) : "memory");
}
__device__ __forceinline__ float ex2(float x) { float y; asm("ex2.approx.ftz.f32 %0, %1;" : "=f"(y) : "f"(x)); return y; }
__device__ __forceinline__ float rcp(float x) { float y; asm("rcp.approx.ftz.f32 %0, %1;" : "=f"(y) : "f"(x)); return y; }
__device__ __forceinline__ uint32_t pack2(float lo, float hi) {
    uint32_t r; asm("cvt.rn.bf16x2.f32 %0, %1, %2;" : "=r"(r) : "f"(hi), "f"(lo)); return r;
}
__device__ __forceinline__ float bf_lo(uint32_t w) { return __uint_as_float(w << 16); }
__device__ __forceinline__ float bf_hi(uint32_t w) { return __uint_as_float(w & 0xffff0000u); }
__device__ __forceinline__ float bfr(float x) { return bf_lo(pack2(x, 0.f)); }
__device__ __forceinline__ float f_(uint32_t u) { return __uint_as_float(u); }

__device__ __forceinline__ uint32_t add2(uint32_t a, uint32_t b) { uint32_t r; asm("add.rn.bf16x2 %0, %1, %2;" : "=r"(r) : "r"(a), "r"(b)); return r; }
__device__ __forceinline__ uint32_t mul2(uint32_t a, uint32_t b) { uint32_t r; asm("mul.rn.bf16x2 %0, %1, %2;" : "=r"(r) : "r"(a), "r"(b)); return r; }
__device__ __forceinline__ uint32_t f2key(float f) { const uint32_t u = __float_as_uint(f); return u ^ ((uint32_t)((int)u >> 31) | 0x80000000u); }
__device__ __forceinline__ float key2f(uint32_t k) { return __uint_as_float(k ^ ((uint32_t)((int)~k >> 31) | 0x80000000u)); }
__device__ __forceinline__ float4 lds128f(uint32_t a) {
    float4 v; asm volatile("ld.shared.v4.f32 {%0,%1,%2,%3}, [%4];" : "=f"(v.x), "=f"(v.y), "=f"(v.z), "=f"(v.w) : "r"(a) : "memory"); return v;
}
__device__ __forceinline__ float2 lds64f(uint32_t a) { float2 v; asm volatile("ld.shared.v2.f32 {%0,%1}, [%2];" : "=f"(v.x), "=f"(v.y) : "r"(a) : "memory"); return v; }
__device__ __forceinline__ uint32_t lds32(uint32_t a) { uint32_t v; asm volatile("ld.shared.u32 %0, [%1];" : "=r"(v) : "r"(a) : "memory"); return v; }
__device__ __forceinline__ uint32_t lds16(uint32_t a) { uint32_t v; asm volatile("ld.shared.u16 %0, [%1];" : "=r"(v) : "r"(a) : "memory"); return v; }
__device__ __forceinline__ void sts16(uint32_t a, uint32_t v) { asm volatile("st.shared.u16 [%0], %1;" ::"r"(a), "r"(v) : "memory"); }
__device__ __forceinline__ void sts32(uint32_t a, uint32_t v) { asm volatile("st.shared.u32 [%0], %1;" ::"r"(a), "r"(v) : "memory"); }
__device__ __forceinline__ void sts32(uint32_t a, float v) { asm volatile("st.shared.f32 [%0], %1;" ::"r"(a), "f"(v) : "memory"); }
__device__ __forceinline__ void sts128(uint32_t a, float x, float y, float z, float w) {
    asm volatile("st.shared.v4.f32 [%0], {%1,%2,%3,%4};" ::"r"(a), "f"(x), "f"(y), "f"(z), "f"(w) : "memory");
}
template <int N> struct IC { static constexpr int value = N; };
__device__ __forceinline__ int opq(int x) { asm volatile("" : "+r"(x)); return x; }
__device__ __forceinline__ uint32_t opq(uint32_t x) { asm volatile("" : "+r"(x)); return x; }
__device__ __forceinline__ uint32_t pin(uint32_t x) { x = opq(x); sts32(SM_MISC + 12, x); return x; }
__device__ __forceinline__ float pin(float x) { sts32(SM_MISC + 12, x); return x; }
template <typename T> __device__ __forceinline__ T* pin(T* p) {
    asm volatile("{\n.reg .b32 lo, hi;\nmov.b64 {lo, hi}, %0;\nst.shared.v2.b32 [%1], {lo, hi};\n}" : "+l"(p) : "r"(SM_MISC + 16) : "memory");
    return p;
}
template <typename T> __device__ __forceinline__ T* opq(T* p) { asm volatile("" : "+l"(p)); return p; }

__device__ __forceinline__ void ln_stats(float& mean, float& inv) {
    const float4 a = lds128f(SM_ST), b = lds128f(SM_ST + 16), c = lds128f(SM_ST + 32), d = lds128f(SM_ST + 48);
    const float s2 = ((a.x + a.z) + (b.x + b.z)) + ((c.x + c.z) + (d.x + d.z));
    const float md = (((a.y + a.w) + (b.y + b.w)) + ((c.y + c.w) + (d.y + d.w))) * (1.0f / DM);
    const float var = fmaxf(s2 * (1.0f / DM) - md * md, 0.f);
    mean = bfr(md);
    asm("rsqrt.approx.ftz.f32 %0, %1;" : "=f"(inv) : "f"(var + 1e-5f));
}
template <int SK, bool GRAM, typename AddrF>
__device__ __forceinline__ void gemv15(float (&cc)[3][4], float (&gr)[4], uint32_t (&pre)[9][4], AddrF ad, uint32_t px, uint32_t px2) {
    uint32_t x0[4], x1[4];
    lds128(px, x0[0], x0[1], x0[2], x0[3]);
    lds128(px + 64, x1[0], x1[1], x1[2], x1[3]);
    gr[0] = gr[1] = gr[2] = gr[3] = 0.f;
#pragma unroll
    for (int i = 0; i < 3; i++) {
        cc[i][0] = cc[i][1] = cc[i][2] = cc[i][3] = 0.f;
        mma16816v(cc[i], pre[i][0], pre[i][1], pre[i][2], pre[i][3], x0[0], x0[1]);
    }
#pragma unroll
    for (int i = 0; i < 3; i++) ldsm4t(ad(i) + 3 * SK, pre[i]);
    if (GRAM) mma16816v(gr, x0[0], 0u, x0[1], 0u, x0[0], x0[1]);
#pragma unroll
    for (int i = 0; i < 3; i++) mma16816v(cc[i], pre[3 + i][0], pre[3 + i][1], pre[3 + i][2], pre[3 + i][3], x0[2], x0[3]);
#pragma unroll
    for (int i = 0; i < 3; i++) ldsm4t(ad(i) + 4 * SK, pre[3 + i]);
    lds64(px2, x0[0], x0[1]);
    if (GRAM) mma16816v(gr, x0[2], 0u, x0[3], 0u, x0[2], x0[3]);
#pragma unroll
    for (int i = 0; i < 3; i++) mma16816v(cc[i], pre[6 + i][0], pre[6 + i][1], pre[6 + i][2], pre[6 + i][3], x1[0], x1[1]);
    if (GRAM) mma16816v(gr, x1[0], 0u, x1[1], 0u, x1[0], x1[1]);
#pragma unroll
    for (int i = 0; i < 3; i++) mma16816v(cc[i], pre[i][0], pre[i][1], pre[i][2], pre[i][3], x1[2], x1[3]);
    if (GRAM) mma16816v(gr, x1[2], 0u, x1[3], 0u, x1[2], x1[3]);
    if (GRAM) mma16816v(gr, x0[0], 0u, x0[1], 0u, x0[0], x0[1]);
#pragma unroll
    for (int i = 0; i < 3; i++) mma16816v(cc[i], pre[3 + i][0], pre[3 + i][1], pre[3 + i][2], pre[3 + i][3], x0[0], x0[1]);
}
template <int SK, typename AddrF, typename AddrG>
__device__ __forceinline__ void gemv15p4(float (&cc)[3][4], uint32_t (&pre)[12][4], AddrF ad, uint32_t px, AddrG px2) {
    uint32_t x0[4], x1[4];
    lds128(px, x0[0], x0[1], x0[2], x0[3]);
#pragma unroll
    for (int i = 0; i < 3; i++) {
        cc[i][0] = cc[i][1] = cc[i][2] = cc[i][3] = 0.f;
        mma16816v(cc[i], pre[i][0], pre[i][1], pre[i][2], pre[i][3], x0[0], x0[1]);
    }
    lds128(px + 64, x1[0], x1[1], x1[2], x1[3]);
#pragma unroll
    for (int i = 0; i < 3; i++) mma16816v(cc[i], pre[3 + i][0], pre[3 + i][1], pre[3 + i][2], pre[3 + i][3], x0[2], x0[3]);
#pragma unroll
    for (int i = 0; i < 3; i++) ldsm4t(ad(i) + 4 * SK, pre[i]);
    lds64(px2(), x0[0], x0[1]);
#pragma unroll
    for (int i = 0; i < 3; i++) mma16816v(cc[i], pre[6 + i][0], pre[6 + i][1], pre[6 + i][2], pre[6 + i][3], x1[0], x1[1]);
#pragma unroll
    for (int i = 0; i < 3; i++) mma16816v(cc[i], pre[9 + i][0], pre[9 + i][1], pre[9 + i][2], pre[9 + i][3], x1[2], x1[3]);
#pragma unroll
    for (int i = 0; i < 3; i++) mma16816v(cc[i], pre[i][0], pre[i][1], pre[i][2], pre[i][3], x0[0], x0[1]);
}
__device__ __forceinline__ void gemv15r(float (&cc)[3][4], float (&gr)[4], const uint32_t (&pre)[9][4], const uint32_t (&ext)[45][4], uint32_t px, uint32_t px2) {
    uint32_t x0[4], x1[4], x2[2];
    lds128(px, x0[0], x0[1], x0[2], x0[3]);
    lds128(px + 64, x1[0], x1[1], x1[2], x1[3]);
    lds64(px2, x2[0], x2[1]);
    gr[0] = gr[1] = gr[2] = gr[3] = 0.f;
#pragma unroll
    for (int ks = 0; ks < 5; ks++) {
        const uint32_t b0 = ks < 2 ? x0[2 * (ks & 1)] : ks < 4 ? x1[2 * (ks & 1)] : x2[0], b1 = ks < 2 ? x0[2 * (ks & 1) + 1] : ks < 4 ? x1[2 * (ks & 1) + 1] : x2[1];
        mma16816v(gr, b0, 0u, b1, 0u, b0, b1);
#pragma unroll
        for (int i = 0; i < 3; i++) {
            if (ks == 0) cc[i][0] = cc[i][1] = cc[i][2] = cc[i][3] = 0.f;
            const uint32_t (&f)[4] = ks < 3 ? pre[ks < 3 ? 3 * ks + i : 0] : ext[ks < 3 ? 0 : 3 * (ks - 3) + i];
            mma16816v(cc[i], f[0], f[1], f[2], f[3], b0, b1);
        }
    }
}

struct Maps { CUtensorMap k, v, wq, wo, w1, w3, w2, ks, vs; const void *kp, *vp;
};
#define RT67 0
#define RT_SEL (((wu & 1) ? RT_MASK2 : RT_MASK) ^ (wu >= 6 ? RT67 : 0))
#define K4D_G 0
#define K4D_R 1500
#define PWA -1
#define PWS 0
#define PWP 0
#define K4LATE 0

__device__ __forceinline__ void load_ffn(const Maps& maps, int b, uint32_t dst, uint32_t bar) {
    const bool gu = b < NG;
    mbar_expect_tx(bar, gu ? 61440 : 49152);
    tma3d(dst, gu ? (b < NG / 2 ? &maps.w1 : &maps.w3) : &maps.w2, gu ? 48 * (b & (NG / 2 - 1)) : 16 * (b - DN0), 0, 0, bar, FFN_POL);
}

__device__ __forceinline__ void load_wo(const Maps& maps, uint32_t dst, int h, int c, uint32_t bar, int nbox) {
#pragma unroll 1
    for (int i = 0; i < nbox; i++) {
        mbar_expect_tx(bar + 8 * i, 12288);
        tma3d(dst + i * 12288, &maps.wo, 0, h * DH, 5 * c + i, bar + 8 * i, POL_EF);
    }
}

__global__ void __launch_bounds__(NT, 1)
decode_kernel(const __grid_constant__ Maps maps, const __nv_bfloat16* __restrict__ x_in, __nv_bfloat16* __restrict__ out) {
    extern __shared__ __align__(1024) unsigned char smem[];
    const int tid = threadIdx.x;
    const int wu = __shfl_sync(0xffffffffu, tid >> 5, 0);
    const int b = blockIdx.x, h = b >> 2, c = b & 3;
    if (smem_u32(smem) != SB) return;

    PROF_T(0);
    {
        const int warp = tid >> 5, lane = tid & 31;
        const uint32_t rbar = SM_BAR + warp * 16;
        if (lane == 0) {
            mbar_init(rbar, 1); mbar_init(rbar + 8, 1); mbar_init(SM_XBAR + warp * 8, 1);
            if (warp == 0) {
                mbar_init(QBAR, 1); mbar_init(FBAR, 1); mbar_init(QRDY, 2);
#pragma unroll
                for (int i = 0; i < 5; i++) mbar_init(WBAR + 8 * i, 1);
                asm volatile("fence.mbarrier_init.release.cluster;" ::: "memory");
                mbar_expect_tx(QBAR, 61440);
                tma5d(SM_Q, &maps.wq, 3 * h, 2 * c, QBAR, POL_EF);
            }
            asm volatile("fence.mbarrier_init.release.cluster;" ::: "memory");
            if (warp >= 1 && warp < 7) {
                const CUtensorMap* mp = warp == 1 ? &maps.k : warp == 2 ? &maps.v : warp == 3 ? &maps.wo : warp == 4 ? &maps.w1 : warp == 5 ? &maps.w3 : &maps.w2;
                asm volatile("prefetch.tensormap [%0];" ::"l"(mp) : "memory");
            }
        }
        if (tid == 96) sts32(SM_MISC + 8, 0u);
        if (lane < 2) sts32(SM_KX + warp * 96 + 4 * lane, 0u);
        if (tid >= 128 && tid < 148) {
            const float v = f_(tid < 138 ? ONES : 0u);
            sts128(SM_ONE + 16 * (tid - 128), v, v, v, v);
        }
        if (b == 0 && tid == 255) asm volatile("st.relaxed.gpu.global.u32 [%0], %1;" ::"l"(g_scr.ticket), "r"(0) : "memory");
        if (tid < 52) st_pkt(tid < 48 ? &g_scr.qx[b * 48 + tid] : reinterpret_cast<uint4*>(&g_scr.mx[h * 32 + c * 8]) + (tid - 48), 0, 0, 0, 0);
        if (tid >= 64 && tid < 66 && b < 108) st_pkt(&g_scr.acc[1][(2 * b + tid - 64) * ACC_STR], 0, 0, 0, 0);
        __syncthreads();
        PROF_D(14);
        if (lane == 0) {
            const int row = ROW0(warp);
            mbar_expect_tx(rbar, TILE);
            tma2d(SM_RING + warp * 2 * TILE, &maps.k, 0, row, rbar, POL_EF);
            mbar_expect_tx(rbar + 8, TILE);
            tma2d(SM_RING + (warp * 2 + 1) * TILE, &maps.k, 0, row + TS, rbar + 8, POL_EF);
        }
    }

    uint32_t kr[45][4];
#define KR(n) kr[(n) >> 2][(n) & 3]
    const float SC = 0.07216878364870322f * 1.4426950408889634f;
    int role = 0;

#pragma unroll 1
    for (int layer = 0; layer < 2; layer++) {
        const uint32_t tag = layer + 1, tbit = layer ^ 1;
        PROF_D(1 + layer * 16);
        uint2 xv = make_uint2(0u, 0u);
        uint32_t qo;
        {
            const int tl = opq(tid), warp = tl >> 5, lane = tl & 31, g = lane >> 2, t = lane & 3, mat = lane >> 3, r8 = lane & 7;
            const int kh = warp >> 2, mg = warp & 3;
            const uint32_t aq = SM_Q + kh * TILE + ((mat >> 1) * 8 + r8) * 128 + (((2 * mg + (mat & 1)) ^ r8) << 4);
            if (layer == 0 && tl < 160) xv = reinterpret_cast<const uint2*>(x_in)[tl];
            mbar_wait(QBAR, 0);
            uint32_t pre[PRE4 ? 12 : 9][4];
#pragma unroll
            for (int n = 0; n < (PRE4 ? 12 : 9); n++) ldsm4t(aq + (n % 3) * 2048 + (n / 3) * 2 * TILE, pre[n]);
            if (layer == 1) {
                __syncthreads();
                if (K4D_G | K4D_R) {
                    const uint32_t d = role < NG ? K4D_G : role >= DN0 + NDN ? K4D_R : 0;
                    uint32_t t0, t1; asm volatile("mov.u32 %0, %%clock;" : "=r"(t0));
                    do asm volatile("mov.u32 %0, %%clock;" : "=r"(t1)); while (t1 - t0 < d);
                }
                const uint32_t pc = role < NG ? PCG : role >= DN0 + NDN ? PCR : PCD;
                if (!(PCG | PCR | PCD) || !pc) {
                    if (wu < NEARLY) tile_load(SM_Q + XCH(wu) * TILE, &maps.k, ROW0(wu) + 5 * TS, SM_XBAR + wu * 8);
                } else if (wu == 7) {
                    uint32_t t0, t1; asm volatile("mov.u32 %0, %%clock;" : "=r"(t0));
#pragma unroll 1
                    for (int w = 0; w < NEARLY; w++) {
                        do asm volatile("mov.u32 %0, %%clock;" : "=r"(t1)); while (t1 - t0 < w * pc);
                        tile_load(SM_Q + XCH(w) * TILE, &maps.k, ROW0(w) + 5 * TS, SM_XBAR + w * 8);
                    }
                }
            }
            const uint32_t pm = opq(g == 1 ? SM_ONE : SM_XS + 160 * (2 * c + kh) + 16 * t);
            const uint32_t pm2 = opq(pm + 128 - (g == 1 ? 0 : 8 * t));
            const uint32_t dq = opq(SM_R + 768 * kh + 4 * (16 * mg + g));
            qo = HOIST & 1 ? pin(16u * (b * 48 + (tl & 63) + (tl >= 64 ? NCTA * 48 : 0))) : 0;
            if (tl < 160) {
                const uint32_t xa0 = opq(SM_XS + 4 * xpos(2 * tl));
                const bool xl = tl % 20 < 16;
                if (layer == 1) {
                    const uint4* px = opq(&g_scr.ay[tl]);
                    uint4 v;
                    int it = 0;
                    bool more;
                    if (PD_G | PD_R) {
                        const uint32_t d = role < NG ? PD_G : role >= DN0 + NDN ? PD_R : 0;
                        uint32_t t0, t1; asm volatile("mov.u32 %0, %%clock;" : "=r"(t0));
                        do asm volatile("mov.u32 %0, %%clock;" : "=r"(t1)); while (t1 - t0 < d);
                    }
                    do { v = ld_pkt(px); more = ++it < SPIN_CAP; } while (!__all_sync(0xffffffffu, (v.y & v.w) == 1) && more);
                    DBG(it, 1);
                    xv = make_uint2(v.x, v.z);
                }
                sts32(xa0, xv.x);
                if (xl) sts32(xa0 + 16, xv.y); else sts32(xa0 + 8, xv.y);
            }
            if (layer) PC(24);
            __syncthreads();
            if (layer) PC(25);
            PROF_T(13 + layer * 16);
            float cc[3][4], gr[4];
            gemv15<2 * TILE, false>(cc, gr, pre, [&](int i) { return aq + i * 2048; }, pm, pm2);
            if (t == 0) {
#pragma unroll
                for (int i = 0; i < 3; i++) { sts32(dq + 256 * i, cc[i][0]); sts32(dq + 256 * i + 32, cc[i][2]); }
                if (layer == 0) {
#pragma unroll
                    for (int i = 0; i < 3; i++) { sts32(dq + 256 * i + 1536, cc[i][1]); sts32(dq + 256 * i + 1568, cc[i][3]); }
                }
            }
        }
        {
            const int tl = opq(tid), j = tl & 63;
            const bool snd = j < 48 && (tl < 64 || (tl < 128 && layer == 0));
            const uint32_t fa = opq(SM_R + 16 * tl + (tl >= 64 ? 512 : 0));
            if (!(HOIST & 1)) qo = 16u * (b * 48 + (tl & 63) + (tl >= 64 ? NCTA * 48 : 0));
            uint4* pq = reinterpret_cast<uint4*>(reinterpret_cast<char*>(g_scr.qx) + qo);
            if (layer) PC(26);
            __syncthreads();
            if (layer) PC(27);
            PROF_D(33 + layer * 16);
            if (snd) {
                const float4 u = lds128f(fa), v = lds128f(fa + 768);
                st_pktf(pq, u.x + v.x, u.y + v.y, u.z + v.z, u.w + v.w, tbit);
            }
            if (layer) PC(28);
            if (layer == 1 && wu >= NEARLY) tile_load(SM_Q + XCH(wu) * TILE, &maps.k, ROW0(wu) + 5 * TS, SM_XBAR + wu * 8);
            if (EARLY4 == 1 && layer == 1 && wu == 5 && role < NG && elect_one()) {
                mbar_expect_tx(WBAR + 32, 12288);
                tma3d(SM_Q + 4 * 12288, &maps.wo, 0, h * DH, 5 * c + 4, WBAR + 32, POL_EF);
            }
            if (layer == 1 && tl >= 192 && tl < 194 && b < 108) st_pkt(&g_scr.acc[0][(2 * b + tl - 192) * ACC_STR], 0, 0, 0, 0);
            lds64(tl < 160 ? SM_XS + 8 * tl : SM_ZERO, xv.x, xv.y);
            const float e0 = bf_lo(xv.x), e1 = bf_hi(xv.x), e2 = bf_lo(xv.y), e3 = bf_hi(xv.y);
            const float s1 = (e0 + e1) + (e2 + e3), s2 = (e0 * e0 + e1 * e1) + (e2 * e2 + e3 * e3);
            const bool lo = !(tl & 16);
            float sv = (lo ? s1 : s2) + __shfl_xor_sync(0xffffffffu, lo ? s2 : s1, 16);
#pragma unroll
            for (int o = 8; o > 0; o >>= 1) sv += __shfl_xor_sync(0xffffffffu, sv, o);
            if ((tl & 15) == 0) sts32(SM_ST + 8 * (tl >> 5) + (lo ? 4 : 0), sv);
            __syncthreads();
        }

        float sc0 = -INFINITY, sc1 = -INFINITY, sc2 = 0.f, sc3 = 0.f, mw;
        uint32_t pk0, pk1;
        float acc[3][4];
        {
            const uint32_t ring = SM_RING + wu * 2 * TILE, rb = SM_BAR + wu * 16;
            const uint32_t xtile = SM_Q + XCH(wu) * TILE, xb = SM_XBAR + wu * 8;
            const int row0 = ROW0(wu);
            auto issue1 = [&](int n, bool vph = false) {
                const CUtensorMap* mp = n < 8 ? &maps.k : &maps.v;
                const int row = row0 + ((n + (n >= 8 ? 2 : 0)) & 7) * TS;
                if (vph && wu < L1R && n == 12 - (wu & 1)) {
                    tile_load_l1(ring + (n & 1) * TILE, maps.vp, row, rb + (n & 1) * 8, opq(tid) & 31);
                    return;
                }
                tile_load(ring + (n & 1) * TILE, mp, row, rb + (n & 1) * 8);
                if ((RT_SEL >> n) & 1) tile_keep(n < 8 ? &maps.ks : &maps.vs, row);
            };
            auto refill1 = [&](int s, bool vph = false) { issue1(s + 2, vph); };
#define K_OFF(i) ((uint32_t)((3 * ((g >> 1) + 4 * (g & 1)) + ((i) >> 1)) * 128 + ((t ^ ((3 * ((g >> 1) + 4 * (g & 1)) + ((i) >> 1)) & 7) ^ (((i) & 1) << 2)) << 4)))
#define V_OFF(i) ((uint32_t)((6 * t + (i)) * 128 + ((g ^ ((6 * t + (i)) & 7)) << 4)))
#define LANE_IDS const int tl = opq(tid), lane = tl & 31, g = lane >> 2, t = lane & 3; (void)tl; (void)lane; (void)g; (void)t;
            const uint32_t kx = SM_KX + wu * 96;
#pragma unroll 1
            for (int s = layer ? 5 : 0; s < 5 + layer; s++) {
                if (s < 5) {
                    LANE_IDS
                    mbar_wait(rb + (s & 1) * 8, (s >> 1) & 1);
                    if (s == 0) PROF_D(52);
                    if (s == 3) PROF_D(53);
                    const uint32_t tile = ring + (s & 1) * TILE;
                    uint32_t mx = 0u, mn = 0x7fff7fffu;
#pragma unroll
                    for (int q = 0; q < 12; q++) {
                        uint32_t a0, a1, a2, a3;
                        lds128(tile + K_OFF(q % 6) + (q / 6) * 3072, a0, a1, a2, a3);
                        a0 &= 0x7fff7fffu; a1 &= 0x7fff7fffu; a2 &= 0x7fff7fffu; a3 &= 0x7fff7fffu;
                        mx = __vimax3_u16x2(__vimax3_u16x2(mx, a0, a1), a2, a3);
                        mn = __vimin3_u16x2(__vimin3_u16x2(mn, a0, a1), a2, a3);
                    }
                    const uint32_t emax = __reduce_max_sync(0xffffffffu, max(mx & 0xffffu, mx >> 16)) >> 7;
                    const uint32_t base = (max(emax, 16u) - 15u) << 7;
                    bool raw = emax < 80u || emax > 190u;
                    if (!raw && __reduce_min_sync(0xffffffffu, min(mn & 0xffffu, mn >> 16)) < base) {
                        const uint32_t n0 = lds32(kx);
                        __syncwarp();
#pragma unroll 1
                        for (int q = 0; q < 12; q++) {
                            const int i = q >= 6 ? q - 6 : q;
                            const uint32_t a = tile + K_OFF(i) + (q >= 6 ? 3072 : 0);
                            uint32_t a0, a1, a2, a3;
                            lds128(a, a0, a1, a2, a3);
                            const uint32_t m = __vimin3_u16x2(__vminu2(a0 & 0x7fff7fffu, a1 & 0x7fff7fffu), a2 & 0x7fff7fffu, a3 & 0x7fff7fffu);
                            if (min(m & 0xffffu, m >> 16) < base) {
#pragma unroll 1
                                for (int e = 0; e < 8; e++) {
                                    const uint32_t x = lds16(a + 2 * e);
                                    if ((x & 0x7fffu) < base) {
                                        uint32_t n;
                                        asm volatile("atom.shared.add.u32 %0, [%1], 1;" : "=r"(n) : "r"(kx) : "memory");
                                        if (n < NEXC) sts32(kx + 32 + 4 * n, x | (2 * ((2 * t + ((e >> 1) & 1)) * 12 + 2 * i + (e >> 2)) + (e & 1)) << 16 | (16 * s + (q >= 6 ? 8 : 0) + g) << 24);
                                        sts16(a + 2 * e, base);
                                    }
                                }
                            }
                        }
                        __syncwarp();
                        raw = lds32(kx) > NEXC;
                        __syncwarp();
                        if (raw && lane == 0) sts32(kx, n0);
                        asm volatile("fence.proxy.async.shared::cta;" ::: "memory");
                    }
                    if (lane == 0) {
                        sts32(kx + 8 + 4 * s, (base + (15u << 7)) << 16);
                        if (raw) sts32(kx + 4, lds32(kx + 4) | 1u << s);
                    }
                    const uint32_t b2 = base * 0x10001u;
                    auto pack = [&](auto S) {
                        constexpr int n0 = 36 * decltype(S)::value;
#pragma unroll
                        for (int q = 0; q < 12; q++) {
                            uint32_t a0, a1, a2, a3;
                            lds128(tile + K_OFF(q % 6) + (q / 6) * 3072, a0, a1, a2, a3);
                            a0 -= b2; a1 -= b2; a2 -= b2; a3 -= b2;
                            KR(n0 + 3 * q) = __byte_perm(a0, a1, 0x6420);
                            KR(n0 + 3 * q + 1) = __byte_perm(a2, a3, 0x6420);
                            const uint32_t ho = __byte_perm(a2, a3, 0x7531);
                            KR(n0 + 3 * q + 2) = __byte_perm(a0, a1, 0x7531) | __funnelshift_r(ho, ho, 4);
                        }
                    };
                    switch (s) {
                        case 0: pack(IC<0>()); break;
                        case 1: pack(IC<1>()); break;
                        case 2: pack(IC<2>()); break;
                        case 3: pack(IC<3>()); break;
                        default: pack(IC<4>()); break;
                    }
                    __syncwarp();
                    refill1(s);
                }
                if (wu < 2 && (s == QAT || layer)) {
                    const int tc = min(opq(tid), 47);
                    const uint4* pq = opq(&g_scr.qx[h * 4 * 48 + tc]);
                    uint4 v[4];
                    int it = 0;
                    bool more = true;
#pragma unroll
                    for (int k = 0; k < 4; k++) v[k] = ld_pkt(pq + 48 * k);
                    if (layer == 0) {
                        uint4 u[4];
                        do {
#pragma unroll
                            for (int k = 0; k < 4; k++) u[k] = ld_pkt(pq + NCTA * 48 + 48 * k);
                            more = ++it < SPIN_CAP;
                        } while (!__all_sync(0xffffffffu, u[0].w & u[1].w & u[2].w & u[3].w & 1) && more);
                        DBG(it, 2);
                        sts128(SM_CS + 16 * tc, (f_(u[0].x) + f_(u[1].x)) + (f_(u[2].x) + f_(u[3].x)), (f_(u[0].y) + f_(u[1].y)) + (f_(u[2].y) + f_(u[3].y)),
                               (f_(u[0].z) + f_(u[1].z)) + (f_(u[2].z) + f_(u[3].z)), (f_(u[0].w) + f_(u[1].w)) + (f_(u[2].w) + f_(u[3].w)));
                    }
                    float mean, inv;
                    ln_stats(mean, inv);
                    const float4 cs = lds128f(SM_CS + 16 * tc);
                    mean *= -inv;
                    const float m0 = pin(mean * cs.x), m1 = pin(mean * cs.y), m2 = pin(mean * cs.z), m3 = pin(mean * cs.w);
                    const int w = 2 * tc;
                    const uint32_t qd = pin(SM_QS + 4 * (((w >> 2) & 3) * 24 + 2 * (w >> 4) + ((w >> 1) & 1)));
                    while (__any_sync(0xffffffffu, ((v[0].w ^ tbit) | (v[1].w ^ tbit) | (v[2].w ^ tbit) | (v[3].w ^ tbit)) & 1) && more) {
#pragma unroll
                        for (int k = 0; k < 4; k++) v[k] = ld_pkt(pq + 48 * k);
                        more = ++it < SPIN_CAP;
                    }
                    DBG(it, 3 + 100 * layer);
                    sts32(qd, pack2(fmaf(inv, (f_(v[0].x) + f_(v[1].x)) + (f_(v[2].x) + f_(v[3].x)), m0), fmaf(inv, (f_(v[0].y) + f_(v[1].y)) + (f_(v[2].y) + f_(v[3].y)), m1)));
                    sts32(qd + 48, pack2(fmaf(inv, (f_(v[0].z) + f_(v[1].z)) + (f_(v[2].z) + f_(v[3].z)), m2), fmaf(inv, (f_(v[0].w) + f_(v[1].w)) + (f_(v[2].w) + f_(v[3].w)), m3)));
                    __syncwarp();
                    if (elect_one()) asm volatile("mbarrier.arrive.shared::cta.b64 _, [%0];" ::"r"(QRDY) : "memory");
                }
            }
            uint32_t qa, ka[6];
            {
                LANE_IDS
                qa = opq(SM_QS + (2 * t + (g & 1)) * 48);
#pragma unroll
                for (int i = 0; i < 6; i++) ka[i] = opq(xtile + K_OFF(i));
            }
            if (layer) PC(29);
            mbar_wait(QRDY, layer);
            if (layer) PC(30);
            PROF_T(2 + layer * 16);
            {
                uint32_t qf[12];
#pragma unroll
                for (int i = 0; i < 3; i++) lds128(qa + 16 * i, qf[4 * i], qf[4 * i + 1], qf[4 * i + 2], qf[4 * i + 3]);
                const int t = opq(tid) & 3;
                auto kr_scores = [&](auto TAU, float& sa, float& sb) {
                    constexpr int tau = decltype(TAU)::value;
                    float cc[2][4] = {{0.f, 0.f, 0.f, 0.f}, {0.f, 0.f, 0.f, 0.f}};
#pragma unroll
                    for (int n = 0; n < 12; n++) {
                        const int q = (n & 1) * 6 + (n >> 1), i = n >> 1;
                        const uint32_t l0 = KR(36 * tau + 3 * q), l1 = KR(36 * tau + 3 * q + 1), hh = KR(36 * tau + 3 * q + 2);
                        const uint32_t h0 = (hh & 0x87878787u) | 0x38383838u, h1 = (__funnelshift_l(hh, hh, 4) & 0x87878787u) | 0x38383838u;
                        mma16816(cc[n & 1], __byte_perm(l0, h0, 0x5140), __byte_perm(l0, h0, 0x7362), __byte_perm(l1, h1, 0x5140), __byte_perm(l1, h1, 0x7362), qf[2 * i], qf[2 * i + 1]);
                    }
                    if (t == (tau & 3)) { sa = cc[0][0] + cc[0][3]; sb = cc[1][0] + cc[1][3]; }
                };
                auto stage_v = [&](auto S) {
                    constexpr int s = decltype(S)::value;
                    const int lane = opq(tid) & 31, g = lane >> 2, t = lane & 3;
#pragma unroll
                    for (int i = 0; i < 6; i++) {
                        const uint32_t a = ring + s * TILE + V_OFF(i);
                        lds128(a, kr[12 * s + i][0], kr[12 * s + i][1], kr[12 * s + i][2], kr[12 * s + i][3]);
                        lds128(a + 3072, kr[12 * s + 6 + i][0], kr[12 * s + 6 + i][1], kr[12 * s + 6 + i][2], kr[12 * s + 6 + i][3]);
                    }
                    __syncwarp();
                    tile_load(ring + s * TILE, s ? &maps.v : &maps.k, row0 + (s ? 2 : 7) * TS, rb + s * 8);
                };
                if (layer == 1) {
                    mbar_wait(xb, 0);
                    PROF_D(34);
                    float cA[4] = {0.f, 0.f, 0.f, 0.f}, cB[4] = {0.f, 0.f, 0.f, 0.f};
                    uint32_t f[6][4];
#pragma unroll
                    for (int i = 0; i < 3; i++) {
                        lds128(ka[i], f[2 * i][0], f[2 * i][1], f[2 * i][2], f[2 * i][3]);
                        lds128(ka[i] + 3072, f[2 * i + 1][0], f[2 * i + 1][1], f[2 * i + 1][2], f[2 * i + 1][3]);
                    }
#pragma unroll
                    for (int i = 0; i < 3; i++) {
                        mma16816v(cA, f[2 * i][0], f[2 * i][1], f[2 * i][2], f[2 * i][3], qf[2 * i], qf[2 * i + 1]);
                        lds128(ka[3 + i], f[2 * i][0], f[2 * i][1], f[2 * i][2], f[2 * i][3]);
                        mma16816v(cB, f[2 * i + 1][0], f[2 * i + 1][1], f[2 * i + 1][2], f[2 * i + 1][3], qf[2 * i], qf[2 * i + 1]);
                        lds128(ka[3 + i] + 3072, f[2 * i + 1][0], f[2 * i + 1][1], f[2 * i + 1][2], f[2 * i + 1][3]);
                    }
                    __syncwarp();
                    tile_load(xtile, &maps.k, row0 + 6 * TS, xb);
#pragma unroll
                    for (int i = 0; i < 3; i++) {
                        mma16816v(cA, f[2 * i][0], f[2 * i][1], f[2 * i][2], f[2 * i][3], qf[6 + 2 * i], qf[7 + 2 * i]);
                        mma16816v(cB, f[2 * i + 1][0], f[2 * i + 1][1], f[2 * i + 1][2], f[2 * i + 1][3], qf[6 + 2 * i], qf[7 + 2 * i]);
                    }
                    sc2 = cA[0] + cA[3]; sc3 = cB[0] + cB[3];
                }
                kr_scores(IC<0>(), sc0, sc1);
                kr_scores(IC<1>(), sc0, sc1);
                if (layer == 1) stage_v(IC<0>());
                kr_scores(IC<2>(), sc0, sc1);
                if (layer == 1) stage_v(IC<1>());
                kr_scores(IC<3>(), sc0, sc1);
                kr_scores(IC<4>(), sc2, sc3);
                {
                    LANE_IDS
                    const float sa = f_(lds32(kx + 8 + 4 * t)), sb = t == 0 ? f_(lds32(kx + 24)) : 1.0f;
                    const int nx = (int)lds32(kx);
                    uint32_t rm = lds32(kx + 4);
                    sc0 *= sa; sc1 *= sa; sc2 *= sb; sc3 *= sb;
#pragma unroll 1
                    for (int n = 0; n < nx; n++) {
                        const uint32_t w = lds32(kx + 32 + 4 * n);
                        const int tau = w >> 28;
                        const float d = bf_lo(lds16(SM_QS + ((w >> 15) & 0x1fe))) * (bf_lo(w) - f_(lds32(kx + 8 + 4 * tau)) * 0x1p-15f);
                        if (((w >> 24) & 7) == g && (tau & 3) == t) {
                            const int k = ((w >> 27) & 1) + (tau >> 2) * 2;
                            if (k == 0) sc0 += d; else if (k == 1) sc1 += d; else if (k == 2) sc2 += d; else sc3 += d;
                        }
                    }
#pragma unroll 1
                    for (; rm; rm &= rm - 1) {
                        const int tau = __ffs(rm) - 1;
#pragma unroll 1
                        for (int hf = 0; hf < 2; hf++) {
                            const char* gp = static_cast<const char*>(maps.kp) + (size_t)(row0 + tau * TS) * 128 + (8 * hf + (g >> 1) + 4 * (g & 1)) * 384 + 16 * t;
                            float cA[4] = {0.f, 0.f, 0.f, 0.f};
#pragma unroll
                            for (int i = 0; i < 6; i++) {
                                const uint4 a = __ldcg(reinterpret_cast<const uint4*>(gp + 64 * i));
                                mma16816(cA, a.x, a.y, a.z, a.w, qf[2 * i], qf[2 * i + 1]);
                            }
                            if ((tau & 3) == t) {
                                const int k = hf + (tau >> 2) * 2;
                                const float d = cA[0] + cA[3];
                                if (k == 0) sc0 = d; else if (k == 1) sc1 = d; else if (k == 2) sc2 = d; else sc3 = d;
                            }
                        }
                    }
                }
                if (layer == 0) {
                    LANE_IDS
#pragma unroll 1
                    for (int s = 5; s < 8; s++) {
                        mbar_wait(rb + (s & 1) * 8, (s >> 1) & 1);
                        const uint32_t tile = ring + (s & 1) * TILE;
                        float cA[4] = {0.f, 0.f, 0.f, 0.f}, cB[4] = {0.f, 0.f, 0.f, 0.f};
#pragma unroll
                        for (int i = 0; i < 6; i++) {
                            uint32_t a0, a1, a2, a3;
                            lds128(tile + K_OFF(i), a0, a1, a2, a3);
                            mma16816(cA, a0, a1, a2, a3, qf[2 * i], qf[2 * i + 1]);
                            lds128(tile + K_OFF(i) + 3072, a0, a1, a2, a3);
                            mma16816(cB, a0, a1, a2, a3, qf[2 * i], qf[2 * i + 1]);
                        }
                        if (t == (s & 3)) { sc2 = cA[0] + cA[3]; sc3 = cB[0] + cB[3]; }
                        __syncwarp();
                        refill1(s);
                    }
                } else {
                    LANE_IDS
#pragma unroll 1
                    for (int i = 2; i < 4; i++) {
                        const uint32_t tile = i == 3 ? ring : xtile, tb = i == 3 ? rb : xb;
                        mbar_wait(tb, i == 2);
                        PROF_D(34 + i);
#pragma unroll
                        for (int k = 0; k < 6; k++) {
                            const uint32_t a = tile + K_OFF(k);
                            lds128(a, kr[24 + k][0], kr[24 + k][1], kr[24 + k][2], kr[24 + k][3]);
                            lds128(a + 3072, kr[24 + 6 + k][0], kr[24 + 6 + k][1], kr[24 + 6 + k][2], kr[24 + 6 + k][3]);
                        }
                        float cA[4] = {0.f, 0.f, 0.f, 0.f}, cB[4] = {0.f, 0.f, 0.f, 0.f}, cC[4] = {0.f, 0.f, 0.f, 0.f}, cD[4] = {0.f, 0.f, 0.f, 0.f};
#pragma unroll
                        for (int k = 0; k < 3; k++) {
                            mma16816(cA, kr[24 + k][0], kr[24 + k][1], kr[24 + k][2], kr[24 + k][3], qf[2 * k], qf[2 * k + 1]);
                            mma16816(cB, kr[24 + 6 + k][0], kr[24 + 6 + k][1], kr[24 + 6 + k][2], kr[24 + 6 + k][3], qf[2 * k], qf[2 * k + 1]);
                            mma16816(cC, kr[24 + 3 + k][0], kr[24 + 3 + k][1], kr[24 + 3 + k][2], kr[24 + 3 + k][3], qf[6 + 2 * k], qf[7 + 2 * k]);
                            mma16816(cD, kr[24 + 9 + k][0], kr[24 + 9 + k][1], kr[24 + 9 + k][2], kr[24 + 9 + k][3], qf[6 + 2 * k], qf[7 + 2 * k]);
                        }
                        __syncwarp();
                        tile_load(tile, &maps.v, row0 + (i + 1) * TS, tb);
                        if (t == i) { sc2 = (cA[0] + cC[0]) + (cA[3] + cC[3]); sc3 = (cB[0] + cD[0]) + (cB[3] + cD[3]); }
                    }
                }
            }
            {
                const uint32_t mk = __reduce_max_sync(0xffffffffu, f2key(fmaxf(fmaxf(sc0, sc1), fmaxf(sc2, sc3))));
                if ((opq(tid) & 31) == 0) st_pkt2(&g_scr.mx[h * 32 + c * 8 + wu], mk, tag);
                mw = key2f(mk);
            }
            pk0 = pack2(ex2((sc0 - mw) * SC), ex2((sc1 - mw) * SC));
            pk1 = pack2(ex2((sc2 - mw) * SC), ex2((sc3 - mw) * SC));
            sc2 = (bf_lo(pk0) + bf_hi(pk0)) + (bf_lo(pk1) + bf_hi(pk1));
#pragma unroll
            for (int o = 16; o > 0; o >>= 1) sc2 += __shfl_xor_sync(0xffffffffu, sc2, o);
#pragma unroll
            for (int s = 0; s < 3; s++) { acc[s][0] = acc[s][1] = acc[s][2] = acc[s][3] = 0.f; }
            auto head_ld = [&](int lane) { const uint2 mv = ld_pkt2(&g_scr.mx[h * 32 + lane]); sc0 = f_(mv.x); sc1 = f_(mv.y); };
            auto head_factor = [&](int lane) {
                int it = 0;
                while (!__all_sync(0xffffffffu, __float_as_uint(sc1) == tag) && ++it < SPIN_CAP) head_ld(lane);
                DBG(it, 4 + 100 * layer);
                sc3 = ex2((mw - key2f(__reduce_max_sync(0xffffffffu, __float_as_uint(sc0)))) * SC);
            };
#define P_CONSTS \
                const uint32_t sel0 = g == 0 ? 0x4410u : (g == 1 ? 0x1044u : 0x4444u); \
                const uint32_t sel1 = g == 2 ? 0x4410u : (g == 3 ? 0x1044u : 0x4444u); \
                const int src00 = 4 * (t < 2 ? 4 * t : 4 * (t - 2) + 1);
#define P_FRAGS(tau) \
                const uint32_t pk = ((tau) & 4) ? pk1 : pk0; \
                const uint32_t w0 = __shfl_sync(0xffffffffu, pk, src00 + ((tau) & 3)); \
                const uint32_t w1 = __shfl_sync(0xffffffffu, pk, src00 + ((tau) & 3) + 8); \
                uint32_t pb[4][2]; \
                _Pragma("unroll") for (int j = 0; j < 4; j++) { \
                    const uint32_t src = ((j & 1) ? w1 : w0) >> ((j >> 1) * 16); \
                    pb[j][0] = __byte_perm(src, 0, sel0); pb[j][1] = __byte_perm(src, 0, sel1); \
                }
            if (layer == 0) {
#pragma unroll 1
                for (int s = 8; s < 16; s++) {
                    LANE_IDS
                    P_CONSTS
                    if (RESET_AT == s) {
                        uint4* p = nullptr;
                        if (tl < 48) p = &g_scr.qx[b * 48 + tl];
                        else if (tl < 98) p = &g_scr.cx[b * 56 + tl - 48];
                        else if (tl < 145) {}
                        else if (tl >= 160) { if (tl < 208) p = &g_scr.qc[b * 48 + tl - 160]; }
                        else if (b < NG) { if (tl < 153) p = &g_scr.ah[b * 8 + tl - 145]; }
                        else if (b < DN0 + NDN && tl < 149) p = &g_scr.ay[(b - DN0) * (AYS ? 8 : 4) + tl - 145];
                        if (p) st_pkt(p, 0, 0, 0, tl < 48);
                    }
                    if (s == 13) head_ld(lane);
                    P_FRAGS((s + 2) & 7)
                    mbar_wait(rb + (s & 1) * 8, (s >> 1) & 1);
                    const uint32_t tile = ring + (s & 1) * TILE;
#pragma unroll
                    for (int j = 0; j < 4; j++) {
#pragma unroll
                        for (int u = 0; u < 3; u++) {
                            uint32_t a0, a1, a2, a3;
                            lds128(tile + (j >> 1) * 3072 + V_OFF(3 * (j & 1) + u), a0, a1, a2, a3);
                            mma16816(acc[u], a0, a1, a2, a3, pb[j][0], pb[j][1]);
                        }
                    }
                    __syncwarp();
                    if (s < 14) refill1(s, true);
                    if (s == 13) head_factor(lane);
                    if (wu == 7 && s == WO_AT && elect_one()) {
                        PROF_X(47);
                        load_wo(maps, SM_B, h, c, WBAR, 5);
                    }
                }
            } else {
                LANE_IDS
                P_CONSTS
#pragma unroll
                for (int s = 0; s < 2; s++) {
                    P_FRAGS(s)
#pragma unroll
                    for (int j = 0; j < 4; j++) {
#pragma unroll
                        for (int u = 0; u < 3; u++) {
                            const int k = 6 * (j >> 1) + 3 * (j & 1) + u;
                            mma16816(acc[u], kr[12 * s + k][0], kr[12 * s + k][1], kr[12 * s + k][2], kr[12 * s + k][3], pb[j][0], pb[j][1]);
                        }
                    }
                }
#pragma unroll 1
                for (int i = 4; i < 10; i++) {
                    const int sl = i == 5 ? 0 : (i == 6 || i == 8 ? 1 : 2);
                    const uint32_t tile = sl ? ring + (sl - 1) * TILE : xtile, tb = sl ? rb + (sl - 1) * 8 : xb;
                    if (i == 8) head_ld(lane);
                    if (i == 9) head_factor(lane);
                    P_FRAGS(i - 2)
                    mbar_wait(tb, (0xC0 >> i) & 1);
                    PROF_D(34 + i);
#pragma unroll
                    for (int k = 0; k < 6; k++) {
                        const uint32_t a = tile + V_OFF(k);
                        lds128(a, kr[24 + k][0], kr[24 + k][1], kr[24 + k][2], kr[24 + k][3]);
                        lds128(a + 3072, kr[24 + 6 + k][0], kr[24 + 6 + k][1], kr[24 + 6 + k][2], kr[24 + 6 + k][3]);
                    }
#pragma unroll
                    for (int j = 0; j < 4; j++) {
#pragma unroll
                        for (int u = 0; u < 3; u++) {
                            const int k = 6 * (j >> 1) + 3 * (j & 1) + u;
                            mma16816(acc[u], kr[24 + k][0], kr[24 + k][1], kr[24 + k][2], kr[24 + k][3], pb[j][0], pb[j][1]);
                        }
                    }
                    __syncwarp();
                    if (wu < L1R && i == 6 - 2 * (wu & 1)) tile_load_l1(tile, maps.vp, row0 + (6 - (wu & 1)) * TS, tb, lane);
                    else if (i == 4 || i == 6 || i == 7) tile_load(tile, &maps.v, row0 + (i == 4 ? 5 : i) * TS, tb);
                    if (EARLY4 >= 4 && i == EARLY4 && wu == 5 && role < NG && elect_one()) {
                        mbar_expect_tx(WBAR + 32, 12288);
                        tma3d(SM_Q + 4 * 12288, &maps.wo, 0, h * DH, 5 * c + 4, WBAR + 32, POL_EF);
                    }
                    if (i == WO_AT1 && HAS_FFN && elect_one()) {
                        uint32_t n;
                        asm volatile("atom.shared.add.u32 %0, [%1], 1;" : "=r"(n) : "r"(SM_MISC + 8) : "memory");
                        if (n == 7u) {
                            PROF_X(63);
                            load_wo(maps, SM_Q, h, c, WBAR, EARLY4 || (KEEP4 && role >= DN0) ? 4 : 5);
                        }
                    }
                }
            }
#undef P_FRAGS
#undef P_CONSTS
#undef LANE_IDS
#undef K_OFF
#undef V_OFF
        }
        PROF_D(3 + layer * 16);
        PC(layer * 32 + 1);

        uint32_t ticket = 0;
        uint4* pr;
        {
            const int tl = opq(tid), warp = tl >> 5, lane = tl & 31, g = lane >> 2, t = lane & 3, mat = lane >> 3, r8 = lane & 7;
            {
                const uint32_t d = SM_R + 4 * (warp * 196 + 8 * g + 4 * t);
                if (t < 2) {
#pragma unroll
                    for (int u = 0; u < 3; u++) sts128(d + 256 * u, acc[u][0] * sc3, acc[u][1] * sc3, acc[u][2] * sc3, acc[u][3] * sc3);
                }
                if (lane == 0) sts128(d + 768, sc2 * sc3, 0.f, 0.f, 0.f);
            }
            const int tc = min(tl, 48);
            uint4* pc = opq(&g_scr.cx[h * 4 * 56 + tc]);
            uint4* po = opq(pc + c * 56);
            const uint32_t fa = opq(SM_R + 16 * tc);
            __syncthreads();
            PROF_T(4 + layer * 16);
            PC(layer * 32 + 2);
            const int kg = warp >> 1, mg = warp & 1;
            const bool wo2 = layer && HAS_FFN;
            const bool wo4 = wo2 && !(KEEP4 && role >= DN0);
            uint32_t aw, oa, ob0, dw;
            uint32_t* tk;
            auto addrs = [&]() {
                aw = pin((wo2 ? SM_Q : SM_B) + (48 * kg + (mat >> 1) * 8 + r8) * 64 + (((2 * mg + (mat & 1)) ^ ((r8 >> 1) & 3)) << 4));
                oa = pin(SM_OS + 96 * kg + 8 * t);
                ob0 = pin(oa + 8 * t);
                dw = pin(SM_R + 4 * (4 * (16 * mg + g) + kg));
                tk = opq(g_scr.ticket + 0);
                if (HOIST & 2) pr = pin(&g_scr.acc[layer][(54 * c + min(tl, 53)) * ACC_STR]);
            };
            uint32_t a[NWPRE][3][4];
            auto preload = [&]() {
#pragma unroll
                for (int i = 0; i < NWPRE; i++) {
                    mbar_wait(WBAR + 8 * i, wo2);
#pragma unroll
                    for (int ks = 0; ks < 3; ks++) ldsm4t(aw + i * 12288 + ks * 1024, a[i][ks]);
                }
            };
            if (wu < 2) {
                if (tl < 49) {
                    float4 v[8];
#pragma unroll
                    for (int w = 0; w < 8; w++) v[w] = lds128f(fa + w * 784);
                    st_pktf(po, ((v[0].x + v[1].x) + (v[2].x + v[3].x)) + ((v[4].x + v[5].x) + (v[6].x + v[7].x)),
                            ((v[0].y + v[1].y) + (v[2].y + v[3].y)) + ((v[4].y + v[5].y) + (v[6].y + v[7].y)),
                            ((v[0].z + v[1].z) + (v[2].z + v[3].z)) + ((v[4].z + v[5].z) + (v[6].z + v[7].z)),
                            ((v[0].w + v[1].w) + (v[2].w + v[3].w)) + ((v[4].w + v[5].w) + (v[6].w + v[7].w)), tbit);
                }
                __syncwarp();
                uint4 v[4];
#pragma unroll
                for (int k = 0; k < 4; k++) v[k] = ld_pkt(pc + k * 56);
                asm volatile("bar.arrive 1, 256;" ::: "memory");
                addrs();
                const int w = 2 * tc, k3 = w / 24, r = w - 24 * k3;
                const uint32_t d0 = pin(tl < 48 ? SM_OS + 4 * (24 * k3 + (r < 16 ? 4 * (r & 3) + (r >> 2) : 16 + 2 * (r & 3) + ((r >> 2) & 1))) : SM_MISC);
                const uint32_t d1 = pin(tl < 48 ? d0 + (r < 16 ? 16 : 8) : SM_MISC + 12);
                int it = 0;
                bool more = true;
                while (__any_sync(0xffffffffu, ((v[0].w ^ tbit) | (v[1].w ^ tbit) | (v[2].w ^ tbit) | (v[3].w ^ tbit)) & 1) && more) {
#pragma unroll
                    for (int k = 0; k < 4; k++) v[k] = ld_pkt(pc + k * 56);
                    more = ++it < SPIN_CAP;
                }
                DBG(it, 5 + 100 * layer);
                const float o0 = (f_(v[0].x) + f_(v[1].x)) + (f_(v[2].x) + f_(v[3].x));
                const uint32_t w0 = pack2(o0, (f_(v[0].y) + f_(v[1].y)) + (f_(v[2].y) + f_(v[3].y)));
                sts32(d1, pack2((f_(v[0].z) + f_(v[1].z)) + (f_(v[2].z) + f_(v[3].z)), (f_(v[0].w) + f_(v[1].w)) + (f_(v[2].w) + f_(v[3].w))));
                sts32(d0, tl < 48 ? w0 : __float_as_uint(o0));
                asm volatile("bar.arrive 2, 256;" ::: "memory");
                PC(layer * 32 + 3);
                preload();
                asm volatile("bar.sync 3, 64;" ::: "memory");
            } else {
                addrs();
                asm volatile("bar.sync 1, 256;" ::: "memory");
                preload();
                PC(layer * 32 + 3);
                asm volatile("bar.sync 2, 256;" ::: "memory");
            }
            PROF_T(5 + layer * 16);
            PC(layer * 32 + 5);
            uint32_t ob[6];
            lds128(ob0, ob[0], ob[1], ob[2], ob[3]);
            lds64(oa + 64, ob[4], ob[5]);
            if (tl == 224 && layer == 0)
                asm volatile("atom.relaxed.gpu.global.inc.u32 %0, [%1], 0x7fffffff;" : "=r"(ticket) : "l"(tk) : "memory");
            auto put = [&](int i, const float (&cc)[4]) { if (t == 0) { sts32(dw + 512 * i, cc[0]); sts32(dw + 512 * i + 128, cc[2]); } };
            {
                float c0[4] = {0.f, 0.f, 0.f, 0.f}, c1[4] = {0.f, 0.f, 0.f, 0.f}, c2[4] = {0.f, 0.f, 0.f, 0.f}, c3[4] = {0.f, 0.f, 0.f, 0.f};
                mbar_wait(WBAR + 16, wo2);
#pragma unroll
                for (int ks = 0; ks < 3; ks++) {
                    mma16816v(c0, a[0][ks][0], a[0][ks][1], a[0][ks][2], a[0][ks][3], ob[2 * ks], ob[2 * ks + 1]);
                    mma16816v(c1, a[1][ks][0], a[1][ks][1], a[1][ks][2], a[1][ks][3], ob[2 * ks], ob[2 * ks + 1]);
                    if (ks == 0) mbar_wait(WBAR + 24, wo2);
                    if (ks == 1) mbar_wait(WBAR + 32, wo4);
#pragma unroll
                    for (int i = 0; i < 2; i++) ldsm4t(aw + (2 + i) * 12288 + ks * 1024, a[i][ks]);
                }
                const uint32_t aw4 = aw + (wo2 && !wo4 ? SM_B - SM_Q : 0) + 4 * 12288;
#pragma unroll
                for (int ks = 0; ks < 3; ks++) {
                    mma16816v(c2, a[0][ks][0], a[0][ks][1], a[0][ks][2], a[0][ks][3], ob[2 * ks], ob[2 * ks + 1]);
                    mma16816v(c3, a[1][ks][0], a[1][ks][1], a[1][ks][2], a[1][ks][3], ob[2 * ks], ob[2 * ks + 1]);
                    if (ks == 0) { ldsm4t(aw4, a[0][0]); ldsm4t(aw4 + 1024, a[1][0]); put(0, c0); put(1, c1); }
                    if (ks == 1) ldsm4t(aw4 + 2048, a[0][1]);
                }
                float c4[4] = {0.f, 0.f, 0.f, 0.f}, c5[4] = {0.f, 0.f, 0.f, 0.f};
                mma16816v(c4, a[0][0][0], a[0][0][1], a[0][0][2], a[0][0][3], ob[0], ob[1]);
                mma16816v(c5, a[1][0][0], a[1][0][1], a[1][0][2], a[1][0][3], ob[2], ob[3]);
                mma16816v(c4, a[0][1][0], a[0][1][1], a[0][1][2], a[0][1][3], ob[4], ob[5]);
                put(2, c2); put(3, c3);
                c4[0] += c5[0]; c4[2] += c5[2];
                put(4, c4);
            }
        }
        {
            const int tl = opq(tid);
            if (!(HOIST & 2)) pr = opq(&g_scr.acc[layer][(54 * c + min(tl, 53)) * ACC_STR]);
            const uint32_t fa = opq(SM_R + 48 * tl);
            const float il = rcp(f_(lds32(SM_MISC)));
            PC(layer * 32 + 6);
            __syncthreads();
            PROF_D(6 + layer * 16);
            PC(layer * 32 + 7);
            if (tl < 54) {
                const float4 v0 = lds128f(fa), v1 = lds128f(fa + 16), v2 = lds128f(fa + 32);
                const float y0 = il * ((v0.x + v0.y) + (v0.z + v0.w)), y1 = il * ((v1.x + v1.y) + (v1.z + v1.w)), y2 = il * ((v2.x + v2.y) + (v2.z + v2.w));
                red_pkt(pr, y0, tl == 53 ? 0.f : y1, tl == 53 ? 0.f : y2);
            }
            if (tl == 224 && layer == 0) {
                sts32(SM_MISC + 4, ticket);
                if (ticket < DN0 + NDN && (ticket < NG || !DNTH)) load_ffn(maps, ticket, SM_B, FBAR);
            }
        }
        PROF_T(7 + layer * 16);
        PC(layer * 32 + 8);
        __syncthreads();
        if (layer == 0) role = __shfl_sync(0xffffffffu, (int)lds32(SM_MISC + 4), 0);
        PC(layer * 32 + 9);
        const uint32_t DONE32 = 0x42000000u;
        if (role < NG) {
            const int tl = opq(tid), warp = tl >> 5, lane = tl & 31, g = lane >> 2, t = lane & 3, mat = lane >> 3, r8 = lane & 7;
            const uint32_t ag = SM_B + (80 * warp + (mat >> 1) * 8 + r8) * 96 + (((mat & 1) ^ (r8 >> 2)) << 4);
            constexpr int GI = 32, GK = 16 * 96;
            const bool on = (g & 1) == (t >> 1), isx = (on && g < 2) || g == 4;
            const uint32_t pm = opq(isx ? SM_XS + 160 * warp + 16 * t : (on || g == 5 ? SM_ONE : SM_ZERO)), pm2 = opq(pm + 128 - (isx ? 8 * t : 0));
            const uint32_t dg = opq(SM_R + 4 * (2 * (warp * 48 + g) + t));
            uint32_t ho = HOIST & 4 ? pin(16u * (role * 8 + 4 * warp + ((lane * 11) >> 5))) : 0;
            uint32_t fa = HOIST & 8 ? pin(SM_R + 8 * (24 * warp + 2 * min(lane, 11))) : 0;
            uint32_t pre[9][4];
            {
                bool hx = wu == 7;
                int it = 0;
                const uint4* px = opq(&g_scr.acc[layer][min(tl, 215) * ACC_STR]);
                const int cq = tl / 54, r = tl - 54 * cq, k0 = min(160 * cq + 3 * r, DM - 1);
                const uint32_t w0 = SM_XS + 4 * xpos(k0 >> 1), w1 = SM_XS + 4 * xpos(min((k0 >> 1) + 1, DM / 2 - 1));
                const bool two = tl < 216 && r != 53;
                const uint32_t e0 = opq(tl < 216 ? w0 + 2 * (k0 & 1) : SM_MISC + 12);
                const uint32_t e1 = opq(two ? ((k0 & 1) ? w1 : w0 + 2) : SM_MISC + 12), e2 = opq(two ? w1 + 2 * (k0 & 1) : SM_MISC + 12);
                const uint32_t x01 = opq(lds16(e0) | (lds16(e1) << 16)), x2 = lds16(e2);
                auto take_x = [&](const uint4 v) {
                    if (__all_sync(0xffffffffu, v.w == DONE32)) {
                        hx = true;
                        const uint32_t y01 = add2(x01, pack2(f_(v.x), f_(v.y))), y2 = add2(x2, pack2(f_(v.z), 0.f));
                        sts16(e0, y01); sts16(e1, y01 >> 16); sts16(e2, y2);
                    }
                };
                while (!mbar_test(FBAR, 0) && ++it < SPIN_CAP) { if (!hx) take_x(ld_pkt(px)); }
                uint4 v = make_uint4(0u, 0u, 0u, 0u);
                if (!hx) v = ld_pkt(px);
#pragma unroll
                for (int n = 0; n < 9; n++) ldsm4t(ag + (n % 3) * GI + (n / 3) * GK, pre[n]);
                if (layer) {
#pragma unroll
                    for (int n = 9; n < 15; n++) ldsm4t(ag + (n % 3) * GI + (n / 3) * GK, kr[n - 9]);
                }
                PC(layer * 32 + 10);
                if (!hx) {
                    bool more = true;
                    while (!__all_sync(0xffffffffu, v.w == DONE32) && more) { v = ld_pkt(px); more = ++it < SPIN_CAP; }
                    const uint32_t y01 = add2(x01, pack2(f_(v.x), f_(v.y))), y2 = add2(x2, pack2(f_(v.z), 0.f));
                    sts16(e0, y01); sts16(e1, y01 >> 16); sts16(e2, y2);
                }
                DBG(it, 6 + 100 * layer);
                PC(layer * 32 + 11);
            }
            __syncthreads();
            PC(layer * 32 + 12);
            PROF_T(9 + layer * 16);
            {
                float cc[3][4], gr[4];
                if (layer) gemv15r(cc, gr, pre, kr, pm, pm2);
                else gemv15<GK, true>(cc, gr, pre, [&](int i) { return ag + i * GI; }, pm, pm2);
                if (t < 2) {
#pragma unroll
                    for (int i = 0; i < 3; i++) { sts32(dg + 128 * i, cc[i][0] + cc[i][3]); sts32(dg + 128 * i + 64, cc[i][1] + cc[i][2]); }
                }
                if ((lane | 4) == 22) sts32(SM_ST + 8 * warp + (g & 1) * 4, gr[0]);
            }
            if (!(HOIST & 8)) fa = opq(G1W ? SM_R + 16 * min(lane, 23) : SM_R + 8 * (24 * warp + 2 * min(lane, 11)));
            if (!(HOIST & 4)) ho = 16u * (role * 8 + 4 * warp + ((lane * 11) >> 5));
            uint4* ph = reinterpret_cast<uint4*>(reinterpret_cast<char*>(g_scr.ah) + ho);
            const bool snd = ((G1W ? 0x249249 : 0x249) >> lane) & 1;
            PC(layer * 32 + 13);
            __syncthreads();
            PC(layer * 32 + 14);
            PROF_D(43 + layer * 16);
            if (wu < (G1W ? 1 : 2)) {
                float mean, inv;
                float4 v[8];
#pragma unroll
                for (int w = 0; w < 8; w++) v[w] = lds128f(fa + w * 384);
                ln_stats(mean, inv);
                const float ga = inv * ((((v[0].x + v[1].x) + (v[2].x + v[3].x)) + ((v[4].x + v[5].x) + (v[6].x + v[7].x))) -
                                        mean * (((v[0].y + v[1].y) + (v[2].y + v[3].y)) + ((v[4].y + v[5].y) + (v[6].y + v[7].y))));
                const float gb = inv * ((((v[0].z + v[1].z) + (v[2].z + v[3].z)) + ((v[4].z + v[5].z) + (v[6].z + v[7].z))) -
                                        mean * (((v[0].w + v[1].w) + (v[2].w + v[3].w)) + ((v[4].w + v[5].w) + (v[6].w + v[7].w))));
                uint32_t wd = pack2(ga, gb);
                if (role < NG / 2) {
                    const float g0 = bf_lo(wd), g1 = bf_hi(wd);
                    wd = pack2(g0 * rcp(1.0f + ex2(-1.4426950408889634f * g0)), g1 * rcp(1.0f + ex2(-1.4426950408889634f * g1)));
                }
                const uint32_t wa = __shfl_down_sync(0xffffffffu, wd, 1), wb = __shfl_down_sync(0xffffffffu, wd, 2);
                if (snd) st_pkt(ph, wd, wa, wb, tag);
            }
            if (HOLD & 2) __syncthreads();
            PROF_T(10 + layer * 16);
            PC(layer * 32 + 15);
        } else if (role < DN0 + NDN) {
            const int j = role - DN0;
            const int tl = opq(tid), warp = tl >> 5, lane = tl & 31, g = lane >> 2, t = lane & 3, mat = lane >> 3, r8 = lane & 7;
            float xr0 = 0.f, xr1 = 0.f;
            if (wu == 0) {
                const int col = 16 * j + (lane & 15), cc = col / 160, r = col - 160 * cc, e = r % 3;
                const uint4* px = &g_scr.acc[layer][(54 * cc + r / 3) * ACC_STR];
                const float x0 = bf_lo(lds16(SM_XS + 4 * xpos(col >> 1) + 2 * (col & 1)));
                uint4 v;
                int it = 0;
                bool ld = DNTH && layer == 0;
                do {
                    v = ld_pkt(px);
                    if (ld && f_(__shfl_sync(0xffffffffu, v.w, 0)) >= (float)DNTH) { ld = false; if (lane == 0) load_ffn(maps, role, SM_B, FBAR); }
                } while (!__all_sync(0xffffffffu, v.w == DONE32) && ++it < SPIN_CAP);
                DBG(it, 7 + 100 * layer);
                if (ld && lane == 0) load_ffn(maps, role, SM_B, FBAR);
                const float xres = bfr(x0 + bfr(f_(e == 0 ? v.x : (e == 1 ? v.y : v.z))));
                xr0 = __shfl_sync(0xffffffffu, xres, 2 * (lane & 7));
                xr1 = __shfl_sync(0xffffffffu, xres, 2 * (lane & 7) + 1);
            }
            PC(layer * 32 + 17);
            PROF_T(9 + layer * 16);
            const uint32_t ad = SM_B + (192 * warp + (mat >> 1) * 8 + r8) * 32 + (((mat & 1) ^ (r8 >> 2)) << 4);
            const uint32_t hs = SM_R + 384 * warp, hb = opq(hs + 16 * t), dd = opq(SM_R + 3072 + 4 * (warp * 16 + g));
            uint32_t pre[NPRE][4];
            uint32_t pos[3];
#pragma unroll
            for (int i = 0; i < 3; i++) { const int w = 3 * lane + i; pos[i] = opq(hs + 4 * ((w & ~15) + 4 * (w & 3) + ((w >> 2) & 1) + ((w >> 2) & 2))); }
            const uint4* ph = opq(&g_scr.ah[tl]);
            const uint32_t fa = opq(SM_R + 3072 + 8 * (lane & 7));
            uint2* py = opq(reinterpret_cast<uint2*>(g_scr.ay) + (AYS ? 16 : 8) * j + (lane & 7));
            uint32_t* po = opq(reinterpret_cast<uint32_t*>(out) + 8 * j + (lane & 7));
            mbar_wait(FBAR, 0);
#pragma unroll
            for (int n = 0; n < NPRE; n++) ldsm4t(ad + n * 512, pre[n]);
            PC(layer * 32 + 18);
            {
                uint4 v, u;
                int it = 0;
                bool more;
                if (PD_D) {
                    uint32_t t0, t1; asm volatile("mov.u32 %0, %%clock;" : "=r"(t0));
                    do asm volatile("mov.u32 %0, %%clock;" : "=r"(t1)); while (t1 - t0 < (layer ? PD_D : PD_D0));
                }
                do { v = ld_pkt(ph); u = ld_pkt(ph + 256); more = ++it < SPIN_CAP; }
                while (!__all_sync(0xffffffffu, v.w == tag && u.w == tag) && more);
                DBG(it, 8 + 100 * layer);
                PC(layer * 32 + 19);
                sts32(pos[0], mul2(v.x, u.x)); sts32(pos[1], mul2(v.y, u.y)); sts32(pos[2], mul2(v.z, u.z));
            }
            __syncwarp();
            PROF_T(11 + layer * 16);
            PC(layer * 32 + 20);
            {
                float cc[4][4];
                uint32_t hv[3][4];
#pragma unroll
                for (int jj = 0; jj < 3; jj++) lds128(hb + 64 * jj, hv[jj][0], hv[jj][1], hv[jj][2], hv[jj][3]);
#pragma unroll
                for (int n = 0; n < 12; n++) {
                    const int s = n < NPRE ? n : n - NPRE;
                    if (n < 4) cc[n][0] = cc[n][1] = cc[n][2] = cc[n][3] = 0.f;
                    mma16816v(cc[n & 3], pre[s][0], pre[s][1], pre[s][2], pre[s][3], hv[(n >> 1) % 3][2 * (n & 1)], hv[(n >> 1) % 3][2 * (n & 1) + 1]);
                    if (n + NPRE < 12) ldsm4t(ad + (n + NPRE) * 512, pre[n]);
                    if ((n & 1) && n < 6) lds128(hb + 64 * ((n >> 1) + 3), hv[n >> 1][0], hv[n >> 1][1], hv[n >> 1][2], hv[n >> 1][3]);
                }
                if (t == 0) { sts32(dd, (cc[0][0] + cc[1][0]) + (cc[2][0] + cc[3][0])); sts32(dd + 32, (cc[0][2] + cc[1][2]) + (cc[2][2] + cc[3][2])); }
            }
            PC(layer * 32 + 21);
            __syncthreads();
            PC(layer * 32 + 22);
            if (tl < 8) {
                float2 v[8];
#pragma unroll
                for (int w = 0; w < 8; w++) v[w] = lds64f(fa + 64 * w);
                const uint32_t y = pack2(((v[0].x + v[1].x) + (v[2].x + v[3].x)) + ((v[4].x + v[5].x) + (v[6].x + v[7].x)),
                                         ((v[0].y + v[1].y) + (v[2].y + v[3].y)) + ((v[4].y + v[5].y) + (v[6].y + v[7].y)));
                const uint32_t wd = pack2(xr0 + bf_lo(y), xr1 + bf_hi(y));
                if (layer) asm volatile("st.global.u32 [%0], %1;" ::"l"(po), "r"(wd) : "memory");
                st_pkt2(py, wd, tag);
            }
            if (HOLD & 1) __syncthreads();
            PROF_T(12 + layer * 16);
            PC(layer * 32 + 23);
        }
    }
}

typedef CUresult (*EncodeFn)(CUtensorMap*, CUtensorMapDataType, cuuint32_t, void*, const cuuint64_t*, const cuuint64_t*, const cuuint32_t*,
                             const cuuint32_t*, CUtensorMapInterleave, CUtensorMapSwizzle, CUtensorMapL2promotion, CUtensorMapFloatOOBfill);

void make_map(EncodeFn enc, CUtensorMap* m, const void* base, int rank, uint64_t d0, uint64_t d1, uint64_t d2, uint64_t s1, uint64_t s2,
              uint32_t b0, uint32_t b1, uint32_t b2, CUtensorMapSwizzle sw, CUtensorMapL2promotion pr = CU_TENSOR_MAP_L2_PROMOTION_NONE) {
    cuuint64_t dims[3] = {d0, d1, d2};
    cuuint64_t strides[2] = {s1, s2};
    cuuint32_t box[3] = {b0, b1, b2};
    cuuint32_t es[3] = {1, 1, 1};
    enc(m, CU_TENSOR_MAP_DATA_TYPE_BFLOAT16, rank, const_cast<void*>(base), dims, strides, box, es, CU_TENSOR_MAP_INTERLEAVE_NONE, sw,
        pr, CU_TENSOR_MAP_FLOAT_OOB_FILL_NONE);
}

}

extern "C" void kernel_launch(void* const* d_in, const int* in_sizes, int n_in, void* d_out, int out_size) {
    (void)in_sizes; (void)n_in; (void)out_size;
    static EncodeFn enc = nullptr;
    if (!enc) {
        void* fn = nullptr;
        cudaDriverEntryPointQueryResult qr;
        cudaGetDriverEntryPoint("cuTensorMapEncodeTiled", &fn, cudaEnableDefault, &qr);
        enc = reinterpret_cast<EncodeFn>(fn);
        cudaFuncSetAttribute(decode_kernel, cudaFuncAttributeMaxDynamicSharedMemorySize, SM_TOTAL);
    }
    Maps maps;
    make_map(enc, &maps.k, d_in[1], 2, 64, (uint64_t)NH * SK * 3, 1, 128, 0, 64, 48, 1, CU_TENSOR_MAP_SWIZZLE_128B);
    make_map(enc, &maps.v, d_in[2], 2, 64, (uint64_t)NH * SK * 3, 1, 128, 0, 64, 48, 1, CU_TENSOR_MAP_SWIZZLE_128B);
    {
        cuuint64_t dims[5] = {64, 16, NH * DH / 64, DM / 80, 5};
        cuuint64_t strides[4] = {NH * DH * 2, 128, 80 * NH * DH * 2, 16 * NH * DH * 2};
        cuuint32_t box[5] = {64, 16, 3, 2, 5};
        cuuint32_t es[5] = {1, 1, 1, 1, 1};
        enc(&maps.wq, CU_TENSOR_MAP_DATA_TYPE_BFLOAT16, 5, d_in[3], dims, strides, box, es, CU_TENSOR_MAP_INTERLEAVE_NONE, CU_TENSOR_MAP_SWIZZLE_128B,
            CU_TENSOR_MAP_L2_PROMOTION_NONE, CU_TENSOR_MAP_FLOAT_OOB_FILL_NONE);
    }
    make_map(enc, &maps.wo, d_in[4], 3, 32, NH * DH, DM / 32, DM * 2, 64, 32, 192, 1, CU_TENSOR_MAP_SWIZZLE_64B);
    constexpr int GW = 48;
    make_map(enc, &maps.w1, d_in[6], 3, FF, 160, 4, FF * 2, 160 * FF * 2, GW, 160, 4, CU_TENSOR_MAP_SWIZZLE_NONE, FFN_PROMO);
    make_map(enc, &maps.w3, d_in[7], 3, FF, 160, 4, FF * 2, 160 * FF * 2, GW, 160, 4, CU_TENSOR_MAP_SWIZZLE_NONE, FFN_PROMO);
    make_map(enc, &maps.w2, d_in[8], 3, DM, 256, 6, DM * 2, 256 * DM * 2, 16, 256, 6, CU_TENSOR_MAP_SWIZZLE_32B, FFN_PROMO);
    maps.kp = d_in[1];
    maps.vp = d_in[2];
#define KWD 16
    const int KW = KWD;
    make_map(enc, &maps.ks, d_in[1], 2, 64, (uint64_t)NH * SK * 3, 1, 128, 0, KW, 48, 1, CU_TENSOR_MAP_SWIZZLE_NONE);
    make_map(enc, &maps.vs, d_in[2], 2, 64, (uint64_t)NH * SK * 3, 1, 128, 0, KW, 48, 1, CU_TENSOR_MAP_SWIZZLE_NONE);
    decode_kernel<<<NCTA, NT, SM_TOTAL, cudaStreamPerThread>>>(maps, (const __nv_bfloat16*)d_in[0], (__nv_bfloat16*)d_out);
}
```

```cpp
#include <cuda_runtime.h>
#include <cuda_bf16.h>
#include <cuda.h>
#include <stdint.h>
#include <math.h>
#include <stdlib.h>
#include <stdio.h>

namespace {

constexpr int DM = 640;
constexpr int NH = 32;
constexpr int DH = 192;
constexpr int SK = 32768;
constexpr int WIN = 4096;
constexpr int FF = 1536;
constexpr int NCTA = 128;
constexpr int NT = 256;
constexpr int TILE = 6144;
constexpr int NG = 64;
constexpr int DN0 = 64;
constexpr int NDN = 40;

constexpr uint32_t SB = 1024;
constexpr uint32_t SM_RING = SB;
constexpr uint32_t SM_B = SM_RING + 8 * 2 * TILE;
constexpr uint32_t SM_Q = SM_B + 61440;
constexpr uint32_t SM_XS = SM_Q + 61440;
constexpr uint32_t SM_R = SM_XS + 1280;
constexpr uint32_t SM_ST = SM_R + 4096;
constexpr uint32_t SM_QS = SM_R + 6272;
constexpr uint32_t SM_OS = SM_QS + 384;
constexpr uint32_t SM_CS = SM_OS + 384;
constexpr uint32_t SM_BAR = SM_CS + 768;
constexpr uint32_t SM_XBAR = SM_BAR + 24 * 8;
constexpr uint32_t SM_MISC = SM_XBAR + 8 * 8;
constexpr uint32_t SM_ONE = SM_MISC + 32;
constexpr uint32_t SM_ZERO = SM_ONE + 160;
constexpr uint32_t SM_KX = SM_ZERO + 160;
constexpr uint32_t SM_TOTAL = SM_KX + 8 * 96 - SB;
constexpr int NEXC = 16;
static_assert(SM_TOTAL <= 232448, "shared memory");
constexpr uint32_t QBAR = SM_BAR + 16 * 8, FBAR = QBAR + 8, WBAR = QBAR + 16, QRDY = QBAR + 56;

constexpr unsigned long long POL_EF = 0x12F0000000000000ull;
constexpr unsigned long long POL_EN = 0x1000000000000000ull;

#define RT_MASK 0x2DE0u
#define RT_MASK2 0x36E0u
#define RESET_AT 14
#define WO_AT 15
#define WO_AT1 7
#define FFN_PROMO CU_TENSOR_MAP_L2_PROMOTION_NONE
#define FFN_POL POL_EF
#define HAS_FFN (role < DN0 + NDN)
#define ACC_STR 1
#define NPRE 6

#define HOIST 0
#define PD_G 0
#define PD_R 0
#define PD_D 0
#define PD_D0 0
#define AYS 0
#define G1W 0
#define EARLYQ 3
#define PADN 0
#define PCG 1
#define PCR 1
#define PCD 0
#define L1T 0
#define QAT 3
#define NWPRE 2
#define L1R 3
#define PRE1 5
#define HOLD 3
#define DNTH 23
#define KEEP4 1
#define PRE4 0
#define NEARLY (PRE4 ? 8 : 6)
#define EARLY4 1
#define XCH(w) (w)
#define LAYOUT 1
#define ROW0(w) ((h * SK + (SK - WIN) + c * 1024 + (w) * 128) * 3)
constexpr int TS = 48;
#define CAPL 19
constexpr int SPIN_CAP = 1 << CAPL;
constexpr uint32_t ONES = 0x3F803F80u;

struct Scratch {
    uint4 qx[NCTA * 48];
    uint4 qc[NCTA * 48];
    uint4 cx[NCTA * 56];
    uint4 pad0[160];
    uint4 acc[2][216 * 8];
    uint4 ay[320];
    uint4 ah[NG * 8];
    uint2 mx[NH * 32];
    uint32_t ticket[32];
    uint32_t pad1[32];
};
__device__ Scratch g_scr;
#define DBG(it, site)
#define PROF_T(i)
#define PROF_D(i)
#define PROF_X(i)
#define PC(i)

__device__ __forceinline__ uint32_t smem_u32(const void* p) { return (uint32_t)__cvta_generic_to_shared(p); }
__device__ __forceinline__ void mbar_init(uint32_t bar, uint32_t cnt) {
    asm volatile("mbarrier.init.shared::cta.b64 [%0], %1;" ::"r"(bar), "r"(cnt) : "memory");
}
__device__ __forceinline__ void mbar_expect_tx(uint32_t bar, uint32_t bytes) {
    asm volatile("mbarrier.arrive.expect_tx.shared::cta.b64 _, [%0], %1;" ::"r"(bar), "r"(bytes) : "memory");
}
__device__ __forceinline__ bool mbar_test(uint32_t bar, uint32_t parity) {
    uint32_t done;
    asm volatile("{\n.reg .pred p;\nmbarrier.try_wait.parity.shared::cta.b64 p, [%1], %2;\nselp.u32 %0, 1, 0, p;\n}"
                 : "=r"(done) : "r"(bar), "r"(parity) : "memory");
    return done;
}
__device__ __forceinline__ void mbar_wait(uint32_t bar, uint32_t parity) {
    asm volatile("{\n.reg .pred p;\n.reg .u32 n;\nmov.u32 n, 0;\n"
                 "W: mbarrier.try_wait.parity.shared::cta.b64 p, [%0], %1;\n@p bra D;\n"
                 "add.u32 n, n, 1;\nsetp.lt.u32 p, n, %2;\n@p bra W;\nD:\n}" ::"r"(bar), "r"(parity), "n"(SPIN_CAP) : "memory");
}
__device__ __forceinline__ void tma2d(uint32_t dst, const CUtensorMap* map, int c0, int c1, uint32_t bar, unsigned long long pol) {
    asm volatile("cp.async.bulk.tensor.2d.shared::cluster.global.mbarrier::complete_tx::bytes.L2::cache_hint [%0], [%1, {%3, %4}], [%2], %5;"
                 ::"r"(dst), "l"(map), "r"(bar), "r"(c0), "r"(c1), "l"(pol) : "memory");
}
__device__ __forceinline__ void tma3d(uint32_t dst, const CUtensorMap* map, int c0, int c1, int c2, uint32_t bar, unsigned long long pol) {
    asm volatile("cp.async.bulk.tensor.3d.shared::cluster.global.mbarrier::complete_tx::bytes.L2::cache_hint [%0], [%1, {%3, %4, %5}], [%2], %6;"
                 ::"r"(dst), "l"(map), "r"(bar), "r"(c0), "r"(c1), "r"(c2), "l"(pol) : "memory");
}
__device__ __forceinline__ void tma5d(uint32_t dst, const CUtensorMap* map, int c2, int c3, uint32_t bar, unsigned long long pol) {
    asm volatile("cp.async.bulk.tensor.5d.shared::cluster.global.mbarrier::complete_tx::bytes.L2::cache_hint [%0], [%1, {0, 0, %3, %4, 0}], [%2], %5;"
                 ::"r"(dst), "l"(map), "r"(bar), "r"(c2), "r"(c3), "l"(pol) : "memory");
}
__device__ __forceinline__ void tma2d_pf(const CUtensorMap* map, int c0, int c1, unsigned long long pol) {
    asm volatile("cp.async.bulk.prefetch.tensor.2d.L2.global.L2::cache_hint [%0, {%1, %2}], %3;" ::"l"(map), "r"(c0), "r"(c1), "l"(pol) : "memory");
}
__device__ __forceinline__ void tile_load(uint32_t dst, const CUtensorMap* map, int row, uint32_t bar) {
    asm volatile("{\n.reg .pred p;\nelect.sync _|p, 0xffffffff;\n"
                 "@p mbarrier.arrive.expect_tx.shared::cta.b64 _, [%2], 6144;\n"
                 "@p cp.async.bulk.tensor.2d.shared::cluster.global.mbarrier::complete_tx::bytes.L2::cache_hint [%0], [%1, {0, %3}], [%2], %4;\n}"
                 ::"r"(dst), "l"(map), "r"(bar), "r"(row), "l"(POL_EF) : "memory");
}
__device__ __forceinline__ void tile_keep(const CUtensorMap* map, int row) {
    asm volatile("{\n.reg .pred p;\nelect.sync _|p, 0xffffffff;\n"
                 "@p cp.async.bulk.prefetch.tensor.2d.L2.global.L2::cache_hint [%0, {0, %1}], %2;\n}"
                 ::"l"(map), "r"(row), "l"(POL_EN) : "memory");
}
__device__ __forceinline__ void tile_load_l1(uint32_t dst, const void* base, int row, uint32_t bar, int lane) {
    const char* g = static_cast<const char*>(base) + (size_t)row * 128 + lane * 16;
    const uint32_t s0 = dst + (lane >> 3) * 128 + (((lane & 7) ^ (lane >> 3)) << 4), s1 = s0 ^ 64;
#pragma unroll
    for (int k = 0; k < 12; k++)
        asm volatile("cp.async.ca.shared.global.L2::cache_hint [%0], [%1], 16, %2;" ::"r"(((k & 1) ? s1 : s0) + k * 512), "l"(g + k * 512), "l"(POL_EF) : "memory");
    asm volatile("cp.async.mbarrier.arrive.shared::cta.b64 [%0];" ::"r"(bar) : "memory");
    __syncwarp();
    if (lane == 0) asm volatile("mbarrier.arrive.shared::cta.b64 _, [%0];" ::"r"(bar) : "memory");
}
__device__ __forceinline__ bool elect_one() {
    uint32_t p;
    asm volatile("{\n.reg .pred p;\nelect.sync _|p, 0xffffffff;\nselp.u32 %0, 1, 0, p;\n}" : "=r"(p));
    return p;
}
__device__ __forceinline__ void lds128(uint32_t addr, uint32_t& a, uint32_t& b, uint32_t& c, uint32_t& d) {
    asm volatile("ld.shared.v4.u32 {%0,%1,%2,%3}, [%4];" : "=r"(a), "=r"(b), "=r"(c), "=r"(d) : "r"(addr) : "memory");
}
__device__ __forceinline__ void lds64(uint32_t addr, uint32_t& a, uint32_t& b) {
    asm volatile("ld.shared.v2.u32 {%0,%1}, [%2];" : "=r"(a), "=r"(b) : "r"(addr) : "memory");
}
__device__ __forceinline__ void ldsm4t(uint32_t addr, uint32_t (&a)[4]) {
    asm volatile("ldmatrix.sync.aligned.m8n8.x4.trans.shared.b16 {%0,%1,%2,%3}, [%4];" : "=r"(a[0]), "=r"(a[1]), "=r"(a[2]), "=r"(a[3]) : "r"(addr) : "memory");
}
__device__ __forceinline__ void mma16816(float (&c)[4], uint32_t a0, uint32_t a1, uint32_t a2, uint32_t a3, uint32_t b0, uint32_t b1) {
    asm("mma.sync.aligned.m16n8k16.row.col.f32.bf16.bf16.f32 {%0,%1,%2,%3}, {%4,%5,%6,%7}, {%8,%9}, {%0,%1,%2,%3};"
        : "+f"(c[0]), "+f"(c[1]), "+f"(c[2]), "+f"(c[3]) : "r"(a0), "r"(a1), "r"(a2), "r"(a3), "r"(b0), "r"(b1));
}
__device__ __forceinline__ void mma16816v(float (&c)[4], uint32_t a0, uint32_t a1, uint32_t a2, uint32_t a3, uint32_t b0, uint32_t b1) {
    asm volatile("mma.sync.aligned.m16n8k16.row.col.f32.bf16.bf16.f32 {%0,%1,%2,%3}, {%4,%5,%6,%7}, {%8,%9}, {%0,%1,%2,%3};"
        : "+f"(c[0]), "+f"(c[1]), "+f"(c[2]), "+f"(c[3]) : "r"(a0), "r"(a1), "r"(a2), "r"(a3), "r"(b0), "r"(b1));
}
__device__ __forceinline__ int xpos(int w) {
    const int seg = w / 40, r = w - 40 * seg;
    return 40 * seg + (r < 32 ? (r & 16) + 4 * (r & 3) + ((r >> 2) & 3) : 32 + 2 * (r & 3) + ((r >> 2) & 1));
}
#define NA 0
#define NA_LD ""
#define NA_ST ""
__device__ __forceinline__ void st_pkt(uint4* p, uint32_t a, uint32_t b, uint32_t c, uint32_t d) {
    asm volatile("{\n.reg .b128 t;\n.reg .b64 lo, hi;\nmov.b64 lo, {%1,%2};\nmov.b64 hi, {%3,%4};\nmov.b128 t, {lo,hi};\nst.relaxed.gpu.global" NA_ST ".b128 [%0], t;\n}"
                 ::"l"(p), "r"(a), "r"(b), "r"(c), "r"(d) : "memory");
}
__device__ __forceinline__ void st_pktf(uint4* p, float a, float b, float c, float d, uint32_t bit) {
    st_pkt(p, __float_as_uint(a), __float_as_uint(b), __float_as_uint(c), (__float_as_uint(d) & ~1u) | bit);
}
__device__ __forceinline__ void red_pkt(uint4* p, float a, float b, float c) {
    asm volatile("red.relaxed.gpu.global.add.v4.f32 [%0], {%1,%2,%3,%4};" ::"l"(p), "f"(a), "f"(b), "f"(c), "f"(1.0f) : "memory");
}
__device__ __forceinline__ uint4 ld_pkt(const uint4* p) {
    uint4 v;
    asm volatile("{\n.reg .b128 t;\n.reg .b64 lo, hi;\nld.relaxed.gpu.global" NA_LD ".b128 t, [%4];\nmov.b128 {lo,hi}, t;\nmov.b64 {%0,%1}, lo;\nmov.b64 {%2,%3}, hi;\n}"
                 : "=r"(v.x), "=r"(v.y), "=r"(v.z), "=r"(v.w) : "l"(p) : "memory");
    return v;
}
__device__ __forceinline__ uint2 ld_pkt2(const uint2* p) {
    unsigned long long v;
    asm volatile("ld.relaxed.gpu.global" NA_LD ".b64 %0, [%1];" : "=l"(v) : "l"(p) : "memory");
    return make_uint2((uint32_t)v, (uint32_t)(v >> 32));
}
__device__ __forceinline__ void st_pkt2(uint2* p, uint32_t a, uint32_t b) {
    asm volatile("st.relaxed.gpu.global" NA_ST ".b64 [%0], %1;" ::"l"(p), "l"((unsigned long long)a | ((unsigned long long)b << 32)) : "memory");
}
__device__ __forceinline__ float ex2(float x) { float y; asm("ex2.approx.ftz.f32 %0, %1;" : "=f"(y) : "f"(x)); return y; }
__device__ __forceinline__ float rcp(float x) { float y; asm("rcp.approx.ftz.f32 %0, %1;" : "=f"(y) : "f"(x)); return y; }
__device__ __forceinline__ uint32_t pack2(float lo, float hi) {
    uint32_t r; asm("cvt.rn.bf16x2.f32 %0, %1, %2;" : "=r"(r) : "f"(hi), "f"(lo)); return r;
}
__device__ __forceinline__ float bf_lo(uint32_t w) { return __uint_as_float(w << 16); }
__device__ __forceinline__ float bf_hi(uint32_t w) { return __uint_as_float(w & 0xffff0000u); }
__device__ __forceinline__ float bfr(float x) { return bf_lo(pack2(x, 0.f)); }
__device__ __forceinline__ float f_(uint32_t u) { return __uint_as_float(u); }

__device__ __forceinline__ uint32_t add2(uint32_t a, uint32_t b) { uint32_t r; asm("add.rn.bf16x2 %0, %1, %2;" : "=r"(r) : "r"(a), "r"(b)); return r; }
__device__ __forceinline__ uint32_t mul2(uint32_t a, uint32_t b) { uint32_t r; asm("mul.rn.bf16x2 %0, %1, %2;" : "=r"(r) : "r"(a), "r"(b)); return r; }
__device__ __forceinline__ uint32_t f2key(float f) { const uint32_t u = __float_as_uint(f); return u ^ ((uint32_t)((int)u >> 31) | 0x80000000u); }
__device__ __forceinline__ float key2f(uint32_t k) { return __uint_as_float(k ^ ((uint32_t)((int)~k >> 31) | 0x80000000u)); }
__device__ __forceinline__ float4 lds128f(uint32_t a) {
    float4 v; asm volatile("ld.shared.v4.f32 {%0,%1,%2,%3}, [%4];" : "=f"(v.x), "=f"(v.y), "=f"(v.z), "=f"(v.w) : "r"(a) : "memory"); return v;
}
__device__ __forceinline__ float2 lds64f(uint32_t a) { float2 v; asm volatile("ld.shared.v2.f32 {%0,%1}, [%2];" : "=f"(v.x), "=f"(v.y) : "r"(a) : "memory"); return v; }
__device__ __forceinline__ uint32_t lds32(uint32_t a) { uint32_t v; asm volatile("ld.shared.u32 %0, [%1];" : "=r"(v) : "r"(a) : "memory"); return v; }
__device__ __forceinline__ uint32_t lds16(uint32_t a) { uint32_t v; asm volatile("ld.shared.u16 %0, [%1];" : "=r"(v) : "r"(a) : "memory"); return v; }
__device__ __forceinline__ void sts16(uint32_t a, uint32_t v) { asm volatile("st.shared.u16 [%0], %1;" ::"r"(a), "r"(v) : "memory"); }
__device__ __forceinline__ void sts32(uint32_t a, uint32_t v) { asm volatile("st.shared.u32 [%0], %1;" ::"r"(a), "r"(v) : "memory"); }
__device__ __forceinline__ void sts32(uint32_t a, float v) { asm volatile("st.shared.f32 [%0], %1;" ::"r"(a), "f"(v) : "memory"); }
__device__ __forceinline__ void sts128(uint32_t a, float x, float y, float z, float w) {
    asm volatile("st.shared.v4.f32 [%0], {%1,%2,%3,%4};" ::"r"(a), "f"(x), "f"(y), "f"(z), "f"(w) : "memory");
}
template <int N> struct IC { static constexpr int value = N; };
__device__ __forceinline__ int opq(int x) { asm volatile("" : "+r"(x)); return x; }
__device__ __forceinline__ uint32_t opq(uint32_t x) { asm volatile("" : "+r"(x)); return x; }
__device__ __forceinline__ uint32_t pin(uint32_t x) { x = opq(x); sts32(SM_MISC + 12, x); return x; }
__device__ __forceinline__ float pin(float x) { sts32(SM_MISC + 12, x); return x; }
template <typename T> __device__ __forceinline__ T* pin(T* p) {
    asm volatile("{\n.reg .b32 lo, hi;\nmov.b64 {lo, hi}, %0;\nst.shared.v2.b32 [%1], {lo, hi};\n}" : "+l"(p) : "r"(SM_MISC + 16) : "memory");
    return p;
}
template <typename T> __device__ __forceinline__ T* opq(T* p) { asm volatile("" : "+l"(p)); return p; }

__device__ __forceinline__ void ln_stats(float& mean, float& inv) {
    const float4 a = lds128f(SM_ST), b = lds128f(SM_ST + 16), c = lds128f(SM_ST + 32), d = lds128f(SM_ST + 48);
    const float s2 = ((a.x + a.z) + (b.x + b.z)) + ((c.x + c.z) + (d.x + d.z));
    const float md = (((a.y + a.w) + (b.y + b.w)) + ((c.y + c.w) + (d.y + d.w))) * (1.0f / DM);
    const float var = fmaxf(s2 * (1.0f / DM) - md * md, 0.f);
    mean = bfr(md);
    asm("rsqrt.approx.ftz.f32 %0, %1;" : "=f"(inv) : "f"(var + 1e-5f));
}
template <int SK, bool GRAM, typename AddrF>
__device__ __forceinline__ void gemv15(float (&cc)[3][4], float (&gr)[4], uint32_t (&pre)[9][4], AddrF ad, uint32_t px, uint32_t px2) {
    uint32_t x0[4], x1[4];
    lds128(px, x0[0], x0[1], x0[2], x0[3]);
    lds128(px + 64, x1[0], x1[1], x1[2], x1[3]);
    gr[0] = gr[1] = gr[2] = gr[3] = 0.f;
#pragma unroll
    for (int i = 0; i < 3; i++) {
        cc[i][0] = cc[i][1] = cc[i][2] = cc[i][3] = 0.f;
        mma16816v(cc[i], pre[i][0], pre[i][1], pre[i][2], pre[i][3], x0[0], x0[1]);
    }
#pragma unroll
    for (int i = 0; i < 3; i++) ldsm4t(ad(i) + 3 * SK, pre[i]);
    if (GRAM) mma16816v(gr, x0[0], 0u, x0[1], 0u, x0[0], x0[1]);
#pragma unroll
    for (int i = 0; i < 3; i++) mma16816v(cc[i], pre[3 + i][0], pre[3 + i][1], pre[3 + i][2], pre[3 + i][3], x0[2], x0[3]);
#pragma unroll
    for (int i = 0; i < 3; i++) ldsm4t(ad(i) + 4 * SK, pre[3 + i]);
    lds64(px2, x0[0], x0[1]);
    if (GRAM) mma16816v(gr, x0[2], 0u, x0[3], 0u, x0[2], x0[3]);
#pragma unroll
    for (int i = 0; i < 3; i++) mma16816v(cc[i], pre[6 + i][0], pre[6 + i][1], pre[6 + i][2], pre[6 + i][3], x1[0], x1[1]);
    if (GRAM) mma16816v(gr, x1[0], 0u, x1[1], 0u, x1[0], x1[1]);
#pragma unroll
    for (int i = 0; i < 3; i++) mma16816v(cc[i], pre[i][0], pre[i][1], pre[i][2], pre[i][3], x1[2], x1[3]);
    if (GRAM) mma16816v(gr, x1[2], 0u, x1[3], 0u, x1[2], x1[3]);
    if (GRAM) mma16816v(gr, x0[0], 0u, x0[1], 0u, x0[0], x0[1]);
#pragma unroll
    for (int i = 0; i < 3; i++) mma16816v(cc[i], pre[3 + i][0], pre[3 + i][1], pre[3 + i][2], pre[3 + i][3], x0[0], x0[1]);
}
template <int SK, typename AddrF, typename AddrG>
__device__ __forceinline__ void gemv15p4(float (&cc)[3][4], uint32_t (&pre)[12][4], AddrF ad, uint32_t px, AddrG px2) {
    uint32_t x0[4], x1[4];
    lds128(px, x0[0], x0[1], x0[2], x0[3]);
#pragma unroll
    for (int i = 0; i < 3; i++) {
        cc[i][0] = cc[i][1] = cc[i][2] = cc[i][3] = 0.f;
        mma16816v(cc[i], pre[i][0], pre[i][1], pre[i][2], pre[i][3], x0[0], x0[1]);
    }
    lds128(px + 64, x1[0], x1[1], x1[2], x1[3]);
#pragma unroll
    for (int i = 0; i < 3; i++) mma16816v(cc[i], pre[3 + i][0], pre[3 + i][1], pre[3 + i][2], pre[3 + i][3], x0[2], x0[3]);
#pragma unroll
    for (int i = 0; i < 3; i++) ldsm4t(ad(i) + 4 * SK, pre[i]);
    lds64(px2(), x0[0], x0[1]);
#pragma unroll
    for (int i = 0; i < 3; i++) mma16816v(cc[i], pre[6 + i][0], pre[6 + i][1], pre[6 + i][2], pre[6 + i][3], x1[0], x1[1]);
#pragma unroll
    for (int i = 0; i < 3; i++) mma16816v(cc[i], pre[9 + i][0], pre[9 + i][1], pre[9 + i][2], pre[9 + i][3], x1[2], x1[3]);
#pragma unroll
    for (int i = 0; i < 3; i++) mma16816v(cc[i], pre[i][0], pre[i][1], pre[i][2], pre[i][3], x0[0], x0[1]);
}
__device__ __forceinline__ void gemv15r(float (&cc)[3][4], float (&gr)[4], const uint32_t (&pre)[9][4], const uint32_t (&ext)[45][4], uint32_t px, uint32_t px2) {
    uint32_t x0[4], x1[4], x2[2];
    lds128(px, x0[0], x0[1], x0[2], x0[3]);
    lds128(px + 64, x1[0], x1[1], x1[2], x1[3]);
    lds64(px2, x2[0], x2[1]);
    gr[0] = gr[1] = gr[2] = gr[3] = 0.f;
#pragma unroll
    for (int ks = 0; ks < 5; ks++) {
        const uint32_t b0 = ks < 2 ? x0[2 * (ks & 1)] : ks < 4 ? x1[2 * (ks & 1)] : x2[0], b1 = ks < 2 ? x0[2 * (ks & 1) + 1] : ks < 4 ? x1[2 * (ks & 1) + 1] : x2[1];
        mma16816v(gr, b0, 0u, b1, 0u, b0, b1);
#pragma unroll
        for (int i = 0; i < 3; i++) {
            if (ks == 0) cc[i][0] = cc[i][1] = cc[i][2] = cc[i][3] = 0.f;
            const uint32_t (&f)[4] = ks < 3 ? pre[ks < 3 ? 3 * ks + i : 0] : ext[ks < 3 ? 0 : 3 * (ks - 3) + i];
            mma16816v(cc[i], f[0], f[1], f[2], f[3], b0, b1);
        }
    }
}

struct Maps { CUtensorMap k, v, wq, wo, w1, w3, w2, ks, vs; const void *kp, *vp;
};
#define RT67 0
#define RT_SEL (((wu & 1) ? RT_MASK2 : RT_MASK) ^ (wu >= 6 ? RT67 : 0))
#define K4D_G 0
#define K4D_R 1500
#define PWA -1
#define PWS 0
#define PWP 0
#define K4LATE 0

__device__ __forceinline__ void load_ffn(const Maps& maps, int b, uint32_t dst, uint32_t bar) {
    const bool gu = b < NG;
    mbar_expect_tx(bar, gu ? 61440 : 49152);
    tma3d(dst, gu ? (b < NG / 2 ? &maps.w1 : &maps.w3) : &maps.w2, gu ? 48 * (b & (NG / 2 - 1)) : 16 * (b - DN0), 0, 0, bar, FFN_POL);
}

__device__ __forceinline__ void load_wo(const Maps& maps, uint32_t dst, int h, int c, uint32_t bar, int nbox) {
#pragma unroll 1
    for (int i = 0; i < nbox; i++) {
        mbar_expect_tx(bar + 8 * i, 12288);
        tma3d(dst + i * 12288, &maps.wo, 0, h * DH, 5 * c + i, bar + 8 * i, POL_EF);
    }
}

__global__ void __launch_bounds__(NT, 1)
decode_kernel(const __grid_constant__ Maps maps, const __nv_bfloat16* __restrict__ x_in, __nv_bfloat16* __restrict__ out) {
    extern __shared__ __align__(1024) unsigned char smem[];
    const int tid = threadIdx.x;
    const int wu = __shfl_sync(0xffffffffu, tid >> 5, 0);
    const int b = blockIdx.x, h = b >> 2, c = b & 3;
    if (smem_u32(smem) != SB) return;

    PROF_T(0);
    {
        const int warp = tid >> 5, lane = tid & 31;
        const uint32_t rbar = SM_BAR + warp * 16;
        if (lane == 0) {
            mbar_init(rbar, 1); mbar_init(rbar + 8, 1); mbar_init(SM_XBAR + warp * 8, 1);
            if (warp == 0) {
                mbar_init(QBAR, 1); mbar_init(FBAR, 1); mbar_init(QRDY, 2);
#pragma unroll
                for (int i = 0; i < 5; i++) mbar_init(WBAR + 8 * i, 1);
                asm volatile("fence.mbarrier_init.release.cluster;" ::: "memory");
                mbar_expect_tx(QBAR, 61440);
                tma5d(SM_Q, &maps.wq, 3 * h, 2 * c, QBAR, POL_EF);
            }
            asm volatile("fence.mbarrier_init.release.cluster;" ::: "memory");
            if (warp >= 1 && warp < 7) {
                const CUtensorMap* mp = warp == 1 ? &maps.k : warp == 2 ? &maps.v : warp == 3 ? &maps.wo : warp == 4 ? &maps.w1 : warp == 5 ? &maps.w3 : &maps.w2;
                asm volatile("prefetch.tensormap [%0];" ::"l"(mp) : "memory");
            }
        }
        if (tid == 96) sts32(SM_MISC + 8, 0u);
        if (lane < 2) sts32(SM_KX + warp * 96 + 4 * lane, 0u);
        if (tid >= 128 && tid < 148) {
            const float v = f_(tid < 138 ? ONES : 0u);
            sts128(SM_ONE + 16 * (tid - 128), v, v, v, v);
        }
        if (b == 0 && tid == 255) asm volatile("st.relaxed.gpu.global.u32 [%0], %1;" ::"l"(g_scr.ticket), "r"(0) : "memory");
        if (tid < 52) st_pkt(tid < 48 ? &g_scr.qx[b * 48 + tid] : reinterpret_cast<uint4*>(&g_scr.mx[h * 32 + c * 8]) + (tid - 48), 0, 0, 0, 0);
        if (tid >= 64 && tid < 66 && b < 108) st_pkt(&g_scr.acc[1][(2 * b + tid - 64) * ACC_STR], 0, 0, 0, 0);
        __syncthreads();
        PROF_D(14);
        if (lane == 0) {
            const int row = ROW0(warp);
            mbar_expect_tx(rbar, TILE);
            tma2d(SM_RING + warp * 2 * TILE, &maps.k, 0, row, rbar, POL_EF);
            mbar_expect_tx(rbar + 8, TILE);
            tma2d(SM_RING + (warp * 2 + 1) * TILE, &maps.k, 0, row + TS, rbar + 8, POL_EF);
        }
    }

    uint32_t kr[45][4];
#define KR(n) kr[(n) >> 2][(n) & 3]
    const float SC = 0.07216878364870322f * 1.4426950408889634f;
    int role = 0;

#pragma unroll 1
    for (int layer = 0; layer < 2; layer++) {
        const uint32_t tag = layer + 1, tbit = layer ^ 1;
        PROF_D(1 + layer * 16);
        uint2 xv = make_uint2(0u, 0u);
        uint32_t qo;
        {
            const int tl = opq(tid), warp = tl >> 5, lane = tl & 31, g = lane >> 2, t = lane & 3, mat = lane >> 3, r8 = lane & 7;
            const int kh = warp >> 2, mg = warp & 3;
            const uint32_t aq = SM_Q + kh * TILE + ((mat >> 1) * 8 + r8) * 128 + (((2 * mg + (mat & 1)) ^ r8) << 4);
            if (layer == 0 && tl < 160) xv = reinterpret_cast<const uint2*>(x_in)[tl];
            mbar_wait(QBAR, 0);
            uint32_t pre[PRE4 ? 12 : 9][4];
#pragma unroll
            for (int n = 0; n < (PRE4 ? 12 : 9); n++) ldsm4t(aq + (n % 3) * 2048 + (n / 3) * 2 * TILE, pre[n]);
            if (layer == 1) {
                __syncthreads();
                if (K4D_G | K4D_R) {
                    const uint32_t d = role < NG ? K4D_G : role >= DN0 + NDN ? K4D_R : 0;
                    uint32_t t0, t1; asm volatile("mov.u32 %0, %%clock;" : "=r"(t0));
                    do asm volatile("mov.u32 %0, %%clock;" : "=r"(t1)); while (t1 - t0 < d);
                }
                const uint32_t pc = role < NG ? PCG : role >= DN0 + NDN ? PCR : PCD;
                if (!(PCG | PCR | PCD) || !pc) {
                    if (wu < NEARLY) tile_load(SM_Q + XCH(wu) * TILE, &maps.k, ROW0(wu) + 5 * TS, SM_XBAR + wu * 8);
                } else if (wu == 7) {
                    uint32_t t0, t1; asm volatile("mov.u32 %0, %%clock;" : "=r"(t0));
#pragma unroll 1
                    for (int w = 0; w < NEARLY; w++) {
                        do asm volatile("mov.u32 %0, %%clock;" : "=r"(t1)); while (t1 - t0 < w * pc);
                        tile_load(SM_Q + XCH(w) * TILE, &maps.k, ROW0(w) + 5 * TS, SM_XBAR + w * 8);
                    }
                }
            }
            const uint32_t pm = opq(g == 1 ? SM_ONE : SM_XS + 160 * (2 * c + kh) + 16 * t);
            const uint32_t pm2 = opq(pm + 128 - (g == 1 ? 0 : 8 * t));
            const uint32_t dq = opq(SM_R + 768 * kh + 4 * (16 * mg + g));
            qo = HOIST & 1 ? pin(16u * (b * 48 + (tl & 63) + (tl >= 64 ? NCTA * 48 : 0))) : 0;
            if (tl < 160) {
                const uint32_t xa0 = opq(SM_XS + 4 * xpos(2 * tl));
                const bool xl = tl % 20 < 16;
                if (layer == 1) {
                    const uint4* px = opq(&g_scr.ay[tl]);
                    uint4 v;
                    int it = 0;
                    bool more;
                    if (PD_G | PD_R) {
                        const uint32_t d = role < NG ? PD_G : role >= DN0 + NDN ? PD_R : 0;
                        uint32_t t0, t1; asm volatile("mov.u32 %0, %%clock;" : "=r"(t0));
                        do asm volatile("mov.u32 %0, %%clock;" : "=r"(t1)); while (t1 - t0 < d);
                    }
                    do { v = ld_pkt(px); more = ++it < SPIN_CAP; } while (!__all_sync(0xffffffffu, (v.y & v.w) == 1) && more);
                    DBG(it, 1);
                    xv = make_uint2(v.x, v.z);
                }
                sts32(xa0, xv.x);
                if (xl) sts32(xa0 + 16, xv.y); else sts32(xa0 + 8, xv.y);
            }
            if (layer) PC(24);
            __syncthreads();
            if (layer) PC(25);
            PROF_T(13 + layer * 16);
            float cc[3][4], gr[4];
            gemv15<2 * TILE, false>(cc, gr, pre, [&](int i) { return aq + i * 2048; }, pm, pm2);
            if (t == 0) {
#pragma unroll
                for (int i = 0; i < 3; i++) { sts32(dq + 256 * i, cc[i][0]); sts32(dq + 256 * i + 32, cc[i][2]); }
                if (layer == 0) {
#pragma unroll
                    for (int i = 0; i < 3; i++) { sts32(dq + 256 * i + 1536, cc[i][1]); sts32(dq + 256 * i + 1568, cc[i][3]); }
                }
            }
        }
        {
            const int tl = opq(tid), j = tl & 63;
            const bool snd = j < 48 && (tl < 64 || (tl < 128 && layer == 0));
            const uint32_t fa = opq(SM_R + 16 * tl + (tl >= 64 ? 512 : 0));
            if (!(HOIST & 1)) qo = 16u * (b * 48 + (tl & 63) + (tl >= 64 ? NCTA * 48 : 0));
            uint4* pq = reinterpret_cast<uint4*>(reinterpret_cast<char*>(g_scr.qx) + qo);
            if (layer) PC(26);
            __syncthreads();
            if (layer) PC(27);
            PROF_D(33 + layer * 16);
            if (snd) {
                const float4 u = lds128f(fa), v = lds128f(fa + 768);
                st_pktf(pq, u.x + v.x, u.y + v.y, u.z + v.z, u.w + v.w, tbit);
            }
            if (layer) PC(28);
            if (layer == 1 && wu >= NEARLY) tile_load(SM_Q + XCH(wu) * TILE, &maps.k, ROW0(wu) + 5 * TS, SM_XBAR + wu * 8);
            if (EARLY4 == 1 && layer == 1 && wu == 5 && role < NG && elect_one()) {
                mbar_expect_tx(WBAR + 32, 12288);
                tma3d(SM_Q + 4 * 12288, &maps.wo, 0, h * DH, 5 * c + 4, WBAR + 32, POL_EF);
            }
            if (layer == 1 && tl >= 192 && tl < 194 && b < 108) st_pkt(&g_scr.acc[0][(2 * b + tl - 192) * ACC_STR], 0, 0, 0, 0);
            lds64(tl < 160 ? SM_XS + 8 * tl : SM_ZERO, xv.x, xv.y);
            const float e0 = bf_lo(xv.x), e1 = bf_hi(xv.x), e2 = bf_lo(xv.y), e3 = bf_hi(xv.y);
            const float s1 = (e0 + e1) + (e2 + e3), s2 = (e0 * e0 + e1 * e1) + (e2 * e2 + e3 * e3);
            const bool lo = !(tl & 16);
            float sv = (lo ? s1 : s2) + __shfl_xor_sync(0xffffffffu, lo ? s2 : s1, 16);
#pragma unroll
            for (int o = 8; o > 0; o >>= 1) sv += __shfl_xor_sync(0xffffffffu, sv, o);
            if ((tl & 15) == 0) sts32(SM_ST + 8 * (tl >> 5) + (lo ? 4 : 0), sv);
            __syncthreads();
        }

        float sc0 = -INFINITY, sc1 = -INFINITY, sc2 = 0.f, sc3 = 0.f, mw;
        uint32_t pk0, pk1;
        float acc[3][4];
        {
            const uint32_t ring = SM_RING + wu * 2 * TILE, rb = SM_BAR + wu * 16;
            const uint32_t xtile = SM_Q + XCH(wu) * TILE, xb = SM_XBAR + wu * 8;
            const int row0 = ROW0(wu);
            auto issue1 = [&](int n, bool vph = false) {
                const CUtensorMap* mp = n < 8 ? &maps.k : &maps.v;
                const int row = row0 + ((n + (n >= 8 ? 2 : 0)) & 7) * TS;
                if (vph && wu < L1R && n == 12 - (wu & 1)) {
                    tile_load_l1(ring + (n & 1) * TILE, maps.vp, row, rb + (n & 1) * 8, opq(tid) & 31);
                    return;
                }
                tile_load(ring + (n & 1) * TILE, mp, row, rb + (n & 1) * 8);
                if ((RT_SEL >> n) & 1) tile_keep(n < 8 ? &maps.ks : &maps.vs, row);
            };
            auto refill1 = [&](int s, bool vph = false) { issue1(s + 2, vph); };
#define K_OFF(i) ((uint32_t)((3 * ((g >> 1) + 4 * (g & 1)) + ((i) >> 1)) * 128 + ((t ^ ((3 * ((g >> 1) + 4 * (g & 1)) + ((i) >> 1)) & 7) ^ (((i) & 1) << 2)) << 4)))
#define V_OFF(i) ((uint32_t)((6 * t + (i)) * 128 + ((g ^ ((6 * t + (i)) & 7)) << 4)))
#define LANE_IDS const int tl = opq(tid), lane = tl & 31, g = lane >> 2, t = lane & 3; (void)tl; (void)lane; (void)g; (void)t;
            const uint32_t kx = SM_KX + wu * 96;
#pragma unroll 1
            for (int s = layer ? 5 : 0; s < 5 + layer; s++) {
                if (s < 5) {
                    LANE_IDS
                    mbar_wait(rb + (s & 1) * 8, (s >> 1) & 1);
                    if (s == 0) PROF_D(52);
                    if (s == 3) PROF_D(53);
                    const uint32_t tile = ring + (s & 1) * TILE;
                    uint32_t mx = 0u, mn = 0xffffffffu;
#pragma unroll
                    for (int q = 0; q < 12; q++) {
                        uint32_t a0, a1, a2, a3;
                        lds128(tile + K_OFF(q % 6) + (q / 6) * 3072, a0, a1, a2, a3);
                        a0 &= 0x7fff7fffu; a1 &= 0x7fff7fffu; a2 &= 0x7fff7fffu; a3 &= 0x7fff7fffu;
                        mx = __vimax3_u16x2(__vimax3_u16x2(mx, a0, a1), a2, a3);
                        mn = __viaddmin_u16x2(a0, 0xffffffffu, __viaddmin_u16x2(a1, 0xffffffffu, __viaddmin_u16x2(a2, 0xffffffffu, __viaddmin_u16x2(a3, 0xffffffffu, mn))));
                    }
                    const uint32_t emax = __reduce_max_sync(0xffffffffu, max(mx & 0xffffu, mx >> 16)) >> 7;
                    const uint32_t base = (max(emax, 16u) - 15u) << 7, lim = base + 0x7fu;
                    bool raw = emax < 80u || emax > 190u;
                    if (!raw && __reduce_min_sync(0xffffffffu, min(mn & 0xffffu, mn >> 16)) < lim) {
                        const uint32_t n0 = lds32(kx);
                        __syncwarp();
#pragma unroll 1
                        for (int q = 0; q < 12; q++) {
                            const int i = q >= 6 ? q - 6 : q;
                            const uint32_t a = tile + K_OFF(i) + (q >= 6 ? 3072 : 0);
                            uint32_t a0, a1, a2, a3;
                            lds128(a, a0, a1, a2, a3);
                            const uint32_t m = __viaddmin_u16x2(a0 & 0x7fff7fffu, 0xffffffffu, __viaddmin_u16x2(a1 & 0x7fff7fffu, 0xffffffffu,
                                               __viaddmin_u16x2(a2 & 0x7fff7fffu, 0xffffffffu, __viaddmin_u16x2(a3 & 0x7fff7fffu, 0xffffffffu, 0xffffffffu))));
                            if (min(m & 0xffffu, m >> 16) < lim) {
#pragma unroll 1
                                for (int e = 0; e < 8; e++) {
                                    const uint32_t x = lds16(a + 2 * e);
                                    if ((x & 0x7fffu) - 1u < lim) {
                                        uint32_t n;
                                        asm volatile("atom.shared.add.u32 %0, [%1], 1;" : "=r"(n) : "r"(kx) : "memory");
                                        if (n < NEXC) sts32(kx + 32 + 4 * n, x | (2 * ((2 * t + ((e >> 1) & 1)) * 12 + 2 * i + (e >> 2)) + (e & 1)) << 16 | (16 * s + (q >= 6 ? 8 : 0) + g) << 24);
                                        sts16(a + 2 * e, 0u);
                                    }
                                }
                            }
                        }
                        __syncwarp();
                        raw = lds32(kx) > NEXC;
                        __syncwarp();
                        if (raw && lane == 0) sts32(kx, n0);
                        asm volatile("fence.proxy.async.shared::cta;" ::: "memory");
                    }
                    if (lane == 0) {
                        sts32(kx + 8 + 4 * s, (base + (31u << 7)) << 16);
                        if (raw) sts32(kx + 4, lds32(kx + 4) | 1u << s);
                    }
                    const uint32_t b2 = (0x10000u - base) * 0x10001u;
                    auto pack = [&](auto S) {
                        constexpr int n0 = 36 * decltype(S)::value;
#pragma unroll
                        for (int q = 0; q < 12; q++) {
                            uint32_t a0, a1, a2, a3;
                            lds128(tile + K_OFF(q % 6) + (q / 6) * 3072, a0, a1, a2, a3);
                            a0 = __viaddmax_s16x2(a0 & 0x7fff7fffu, b2, 0u) | (a0 & 0x80008000u); a1 = __viaddmax_s16x2(a1 & 0x7fff7fffu, b2, 0u) | (a1 & 0x80008000u);
                            a2 = __viaddmax_s16x2(a2 & 0x7fff7fffu, b2, 0u) | (a2 & 0x80008000u); a3 = __viaddmax_s16x2(a3 & 0x7fff7fffu, b2, 0u) | (a3 & 0x80008000u);
                            KR(n0 + 3 * q) = __byte_perm(a0, a1, 0x6420);
                            KR(n0 + 3 * q + 1) = __byte_perm(a2, a3, 0x6420);
                            const uint32_t ho = __byte_perm(a2, a3, 0x7531);
                            KR(n0 + 3 * q + 2) = __byte_perm(a0, a1, 0x7531) | __funnelshift_r(ho, ho, 4);
                        }
                    };
                    switch (s) {
                        case 0: pack(IC<0>()); break;
                        case 1: pack(IC<1>()); break;
                        case 2: pack(IC<2>()); break;
                        case 3: pack(IC<3>()); break;
                        default: pack(IC<4>()); break;
                    }
                    __syncwarp();
                    refill1(s);
                }
                if (wu < 2 && (s == QAT || layer)) {
                    const int tc = min(opq(tid), 47);
                    const uint4* pq = opq(&g_scr.qx[h * 4 * 48 + tc]);
                    uint4 v[4];
                    int it = 0;
                    bool more = true;
#pragma unroll
                    for (int k = 0; k < 4; k++) v[k] = ld_pkt(pq + 48 * k);
                    if (layer == 0) {
                        uint4 u[4];
                        do {
#pragma unroll
                            for (int k = 0; k < 4; k++) u[k] = ld_pkt(pq + NCTA * 48 + 48 * k);
                            more = ++it < SPIN_CAP;
                        } while (!__all_sync(0xffffffffu, u[0].w & u[1].w & u[2].w & u[3].w & 1) && more);
                        DBG(it, 2);
                        sts128(SM_CS + 16 * tc, (f_(u[0].x) + f_(u[1].x)) + (f_(u[2].x) + f_(u[3].x)), (f_(u[0].y) + f_(u[1].y)) + (f_(u[2].y) + f_(u[3].y)),
                               (f_(u[0].z) + f_(u[1].z)) + (f_(u[2].z) + f_(u[3].z)), (f_(u[0].w) + f_(u[1].w)) + (f_(u[2].w) + f_(u[3].w)));
                    }
                    float mean, inv;
                    ln_stats(mean, inv);
                    const float4 cs = lds128f(SM_CS + 16 * tc);
                    mean *= -inv;
                    const float m0 = pin(mean * cs.x), m1 = pin(mean * cs.y), m2 = pin(mean * cs.z), m3 = pin(mean * cs.w);
                    const int w = 2 * tc;
                    const uint32_t qd = pin(SM_QS + 4 * (((w >> 2) & 3) * 24 + 2 * (w >> 4) + ((w >> 1) & 1)));
                    while (__any_sync(0xffffffffu, ((v[0].w ^ tbit) | (v[1].w ^ tbit) | (v[2].w ^ tbit) | (v[3].w ^ tbit)) & 1) && more) {
#pragma unroll
                        for (int k = 0; k < 4; k++) v[k] = ld_pkt(pq + 48 * k);
                        more = ++it < SPIN_CAP;
                    }
                    DBG(it, 3 + 100 * layer);
                    const float q0 = fmaf(inv, (f_(v[0].x) + f_(v[1].x)) + (f_(v[2].x) + f_(v[3].x)), m0), q1 = fmaf(inv, (f_(v[0].y) + f_(v[1].y)) + (f_(v[2].y) + f_(v[3].y)), m1);
                    const float q2 = fmaf(inv, (f_(v[0].z) + f_(v[1].z)) + (f_(v[2].z) + f_(v[3].z)), m2), q3 = fmaf(inv, (f_(v[0].w) + f_(v[1].w)) + (f_(v[2].w) + f_(v[3].w)), m3);
                    sts32(qd, pack2(q0, q1));
                    sts32(qd + 48, pack2(q2, q3));
                    sts32(SM_MISC + 24 + 4 * wu, __ballot_sync(0xffffffffu, !((fabsf(q0) + fabsf(q1)) + (fabsf(q2) + fabsf(q3)) < 0x1p30f)));
                    __syncwarp();
                    if (elect_one()) asm volatile("mbarrier.arrive.shared::cta.b64 _, [%0];" ::"r"(QRDY) : "memory");
                }
            }
            uint32_t qa, ka[6];
            {
                LANE_IDS
                qa = opq(SM_QS + (2 * t + (g & 1)) * 48);
#pragma unroll
                for (int i = 0; i < 6; i++) ka[i] = opq(xtile + K_OFF(i));
            }
            if (layer) PC(29);
            mbar_wait(QRDY, layer);
            if (layer) PC(30);
            PROF_T(2 + layer * 16);
            {
                uint32_t qf[12];
#pragma unroll
                for (int i = 0; i < 3; i++) lds128(qa + 16 * i, qf[4 * i], qf[4 * i + 1], qf[4 * i + 2], qf[4 * i + 3]);
                const int t = opq(tid) & 3;
                uint32_t qs[12];
#pragma unroll
                for (int i = 0; i < 12; i++) qs[i] = mul2(qf[i], 0x6f806f80u);
                auto kr_scores = [&](auto TAU, float& sa, float& sb) {
                    constexpr int tau = decltype(TAU)::value;
                    float cc[2][4] = {{0.f, 0.f, 0.f, 0.f}, {0.f, 0.f, 0.f, 0.f}};
#pragma unroll
                    for (int n = 0; n < 12; n++) {
                        const int q = (n & 1) * 6 + (n >> 1), i = n >> 1;
                        const uint32_t l0 = KR(36 * tau + 3 * q), l1 = KR(36 * tau + 3 * q + 1), hh = KR(36 * tau + 3 * q + 2);
                        const uint32_t h0 = hh & 0x87878787u, h1 = __funnelshift_l(hh, hh, 4) & 0x87878787u;
                        mma16816(cc[n & 1], __byte_perm(l0, h0, 0x5140), __byte_perm(l0, h0, 0x7362), __byte_perm(l1, h1, 0x5140), __byte_perm(l1, h1, 0x7362), qs[2 * i], qs[2 * i + 1]);
                    }
                    if (t == (tau & 3)) { sa = cc[0][0] + cc[0][3]; sb = cc[1][0] + cc[1][3]; }
                };
                auto stage_v = [&](auto S) {
                    constexpr int s = decltype(S)::value;
                    const int lane = opq(tid) & 31, g = lane >> 2, t = lane & 3;
#pragma unroll
                    for (int i = 0; i < 6; i++) {
                        const uint32_t a = ring + s * TILE + V_OFF(i);
                        lds128(a, kr[12 * s + i][0], kr[12 * s + i][1], kr[12 * s + i][2], kr[12 * s + i][3]);
                        lds128(a + 3072, kr[12 * s + 6 + i][0], kr[12 * s + 6 + i][1], kr[12 * s + 6 + i][2], kr[12 * s + 6 + i][3]);
                    }
                    __syncwarp();
                    tile_load(ring + s * TILE, s ? &maps.v : &maps.k, row0 + (s ? 2 : 7) * TS, rb + s * 8);
                };
                if (layer == 1) {
                    mbar_wait(xb, 0);
                    PROF_D(34);
                    float cA[4] = {0.f, 0.f, 0.f, 0.f}, cB[4] = {0.f, 0.f, 0.f, 0.f};
                    uint32_t f[6][4];
#pragma unroll
                    for (int i = 0; i < 3; i++) {
                        lds128(ka[i], f[2 * i][0], f[2 * i][1], f[2 * i][2], f[2 * i][3]);
                        lds128(ka[i] + 3072, f[2 * i + 1][0], f[2 * i + 1][1], f[2 * i + 1][2], f[2 * i + 1][3]);
                    }
#pragma unroll
                    for (int i = 0; i < 3; i++) {
                        mma16816v(cA, f[2 * i][0], f[2 * i][1], f[2 * i][2], f[2 * i][3], qf[2 * i], qf[2 * i + 1]);
                        lds128(ka[3 + i], f[2 * i][0], f[2 * i][1], f[2 * i][2], f[2 * i][3]);
                        mma16816v(cB, f[2 * i + 1][0], f[2 * i + 1][1], f[2 * i + 1][2], f[2 * i + 1][3], qf[2 * i], qf[2 * i + 1]);
                        lds128(ka[3 + i] + 3072, f[2 * i + 1][0], f[2 * i + 1][1], f[2 * i + 1][2], f[2 * i + 1][3]);
                    }
                    __syncwarp();
                    tile_load(xtile, &maps.k, row0 + 6 * TS, xb);
#pragma unroll
                    for (int i = 0; i < 3; i++) {
                        mma16816v(cA, f[2 * i][0], f[2 * i][1], f[2 * i][2], f[2 * i][3], qf[6 + 2 * i], qf[7 + 2 * i]);
                        mma16816v(cB, f[2 * i + 1][0], f[2 * i + 1][1], f[2 * i + 1][2], f[2 * i + 1][3], qf[6 + 2 * i], qf[7 + 2 * i]);
                    }
                    sc2 = cA[0] + cA[3]; sc3 = cB[0] + cB[3];
                }
                kr_scores(IC<0>(), sc0, sc1);
                kr_scores(IC<1>(), sc0, sc1);
                if (layer == 1) stage_v(IC<0>());
                kr_scores(IC<2>(), sc0, sc1);
                if (layer == 1) stage_v(IC<1>());
                kr_scores(IC<3>(), sc0, sc1);
                kr_scores(IC<4>(), sc2, sc3);
                {
                    LANE_IDS
                    const float sa = f_(lds32(kx + 8 + 4 * t)), sb = t == 0 ? f_(lds32(kx + 24)) : 1.0f;
                    const int nx = (int)lds32(kx);
                    uint32_t rm = lds32(kx + 4), big0, big1;
                    lds64(SM_MISC + 24, big0, big1);
                    if (big0 | big1) rm = 31;
                    sc0 *= sa; sc1 *= sa; sc2 *= sb; sc3 *= sb;
#pragma unroll 1
                    for (int n = 0; n < nx; n++) {
                        const uint32_t w = lds32(kx + 32 + 4 * n);
                        const int tau = w >> 28;
                        const float d = bf_lo(lds16(SM_QS + ((w >> 15) & 0x1fe))) * bf_lo(w);
                        if (((w >> 24) & 7) == g && (tau & 3) == t) {
                            const int k = ((w >> 27) & 1) + (tau >> 2) * 2;
                            if (k == 0) sc0 += d; else if (k == 1) sc1 += d; else if (k == 2) sc2 += d; else sc3 += d;
                        }
                    }
#pragma unroll 1
                    for (; rm; rm &= rm - 1) {
                        const int tau = __ffs(rm) - 1;
#pragma unroll 1
                        for (int hf = 0; hf < 2; hf++) {
                            const char* gp = static_cast<const char*>(maps.kp) + (size_t)(row0 + tau * TS) * 128 + (8 * hf + (g >> 1) + 4 * (g & 1)) * 384 + 16 * t;
                            float cA[4] = {0.f, 0.f, 0.f, 0.f};
#pragma unroll
                            for (int i = 0; i < 6; i++) {
                                const uint4 a = __ldcg(reinterpret_cast<const uint4*>(gp + 64 * i));
                                mma16816(cA, a.x, a.y, a.z, a.w, qf[2 * i], qf[2 * i + 1]);
                            }
                            if ((tau & 3) == t) {
                                const int k = hf + (tau >> 2) * 2;
                                const float d = cA[0] + cA[3];
                                if (k == 0) sc0 = d; else if (k == 1) sc1 = d; else if (k == 2) sc2 = d; else sc3 = d;
                            }
                        }
                    }
                }
                if (layer == 0) {
                    LANE_IDS
#pragma unroll 1
                    for (int s = 5; s < 8; s++) {
                        mbar_wait(rb + (s & 1) * 8, (s >> 1) & 1);
                        const uint32_t tile = ring + (s & 1) * TILE;
                        float cA[4] = {0.f, 0.f, 0.f, 0.f}, cB[4] = {0.f, 0.f, 0.f, 0.f};
#pragma unroll
                        for (int i = 0; i < 6; i++) {
                            uint32_t a0, a1, a2, a3;
                            lds128(tile + K_OFF(i), a0, a1, a2, a3);
                            mma16816(cA, a0, a1, a2, a3, qf[2 * i], qf[2 * i + 1]);
                            lds128(tile + K_OFF(i) + 3072, a0, a1, a2, a3);
                            mma16816(cB, a0, a1, a2, a3, qf[2 * i], qf[2 * i + 1]);
                        }
                        if (t == (s & 3)) { sc2 = cA[0] + cA[3]; sc3 = cB[0] + cB[3]; }
                        __syncwarp();
                        refill1(s);
                    }
                } else {
                    LANE_IDS
#pragma unroll 1
                    for (int i = 2; i < 4; i++) {
                        const uint32_t tile = i == 3 ? ring : xtile, tb = i == 3 ? rb : xb;
                        mbar_wait(tb, i == 2);
                        PROF_D(34 + i);
#pragma unroll
                        for (int k = 0; k < 6; k++) {
                            const uint32_t a = tile + K_OFF(k);
                            lds128(a, kr[24 + k][0], kr[24 + k][1], kr[24 + k][2], kr[24 + k][3]);
                            lds128(a + 3072, kr[24 + 6 + k][0], kr[24 + 6 + k][1], kr[24 + 6 + k][2], kr[24 + 6 + k][3]);
                        }
                        float cA[4] = {0.f, 0.f, 0.f, 0.f}, cB[4] = {0.f, 0.f, 0.f, 0.f}, cC[4] = {0.f, 0.f, 0.f, 0.f}, cD[4] = {0.f, 0.f, 0.f, 0.f};
#pragma unroll
                        for (int k = 0; k < 3; k++) {
                            mma16816(cA, kr[24 + k][0], kr[24 + k][1], kr[24 + k][2], kr[24 + k][3], qf[2 * k], qf[2 * k + 1]);
                            mma16816(cB, kr[24 + 6 + k][0], kr[24 + 6 + k][1], kr[24 + 6 + k][2], kr[24 + 6 + k][3], qf[2 * k], qf[2 * k + 1]);
                            mma16816(cC, kr[24 + 3 + k][0], kr[24 + 3 + k][1], kr[24 + 3 + k][2], kr[24 + 3 + k][3], qf[6 + 2 * k], qf[7 + 2 * k]);
                            mma16816(cD, kr[24 + 9 + k][0], kr[24 + 9 + k][1], kr[24 + 9 + k][2], kr[24 + 9 + k][3], qf[6 + 2 * k], qf[7 + 2 * k]);
                        }
                        __syncwarp();
                        tile_load(tile, &maps.v, row0 + (i + 1) * TS, tb);
                        if (t == i) { sc2 = (cA[0] + cC[0]) + (cA[3] + cC[3]); sc3 = (cB[0] + cD[0]) + (cB[3] + cD[3]); }
                    }
                }
            }
            {
                const uint32_t mk = __reduce_max_sync(0xffffffffu, f2key(fmaxf(fmaxf(sc0, sc1), fmaxf(sc2, sc3))));
                if ((opq(tid) & 31) == 0) st_pkt2(&g_scr.mx[h * 32 + c * 8 + wu], mk, tag);
                mw = key2f(mk);
            }
            pk0 = pack2(ex2((sc0 - mw) * SC), ex2((sc1 - mw) * SC));
            pk1 = pack2(ex2((sc2 - mw) * SC), ex2((sc3 - mw) * SC));
            sc2 = (bf_lo(pk0) + bf_hi(pk0)) + (bf_lo(pk1) + bf_hi(pk1));
#pragma unroll
            for (int o = 16; o > 0; o >>= 1) sc2 += __shfl_xor_sync(0xffffffffu, sc2, o);
#pragma unroll
            for (int s = 0; s < 3; s++) { acc[s][0] = acc[s][1] = acc[s][2] = acc[s][3] = 0.f; }
            auto head_ld = [&](int lane) { const uint2 mv = ld_pkt2(&g_scr.mx[h * 32 + lane]); sc0 = f_(mv.x); sc1 = f_(mv.y); };
            auto head_factor = [&](int lane) {
                int it = 0;
                while (!__all_sync(0xffffffffu, __float_as_uint(sc1) == tag) && ++it < SPIN_CAP) head_ld(lane);
                DBG(it, 4 + 100 * layer);
                sc3 = ex2((mw - key2f(__reduce_max_sync(0xffffffffu, __float_as_uint(sc0)))) * SC);
            };
#define P_CONSTS \
                const uint32_t sel0 = g == 0 ? 0x4410u : (g == 1 ? 0x1044u : 0x4444u); \
                const uint32_t sel1 = g == 2 ? 0x4410u : (g == 3 ? 0x1044u : 0x4444u); \
                const int src00 = 4 * (t < 2 ? 4 * t : 4 * (t - 2) + 1);
#define P_FRAGS(tau) \
                const uint32_t pk = ((tau) & 4) ? pk1 : pk0; \
                const uint32_t w0 = __shfl_sync(0xffffffffu, pk, src00 + ((tau) & 3)); \
                const uint32_t w1 = __shfl_sync(0xffffffffu, pk, src00 + ((tau) & 3) + 8); \
                uint32_t pb[4][2]; \
                _Pragma("unroll") for (int j = 0; j < 4; j++) { \
                    const uint32_t src = ((j & 1) ? w1 : w0) >> ((j >> 1) * 16); \
                    pb[j][0] = __byte_perm(src, 0, sel0); pb[j][1] = __byte_perm(src, 0, sel1); \
                }
            if (layer == 0) {
#pragma unroll 1
                for (int s = 8; s < 16; s++) {
                    LANE_IDS
                    P_CONSTS
                    if (RESET_AT == s) {
                        uint4* p = nullptr;
                        if (tl < 48) p = &g_scr.qx[b * 48 + tl];
                        else if (tl < 98) p = &g_scr.cx[b * 56 + tl - 48];
                        else if (tl < 145) {}
                        else if (tl >= 160) { if (tl < 208) p = &g_scr.qc[b * 48 + tl - 160]; }
                        else if (b < NG) { if (tl < 153) p = &g_scr.ah[b * 8 + tl - 145]; }
                        else if (b < DN0 + NDN && tl < 149) p = &g_scr.ay[(b - DN0) * (AYS ? 8 : 4) + tl - 145];
                        if (p) st_pkt(p, 0, 0, 0, tl < 48);
                    }
                    if (s == 13) head_ld(lane);
                    P_FRAGS((s + 2) & 7)
                    mbar_wait(rb + (s & 1) * 8, (s >> 1) & 1);
                    const uint32_t tile = ring + (s & 1) * TILE;
#pragma unroll
                    for (int j = 0; j < 4; j++) {
#pragma unroll
                        for (int u = 0; u < 3; u++) {
                            uint32_t a0, a1, a2, a3;
                            lds128(tile + (j >> 1) * 3072 + V_OFF(3 * (j & 1) + u), a0, a1, a2, a3);
                            mma16816(acc[u], a0, a1, a2, a3, pb[j][0], pb[j][1]);
                        }
                    }
                    __syncwarp();
                    if (s < 14) refill1(s, true);
                    if (s == 13) head_factor(lane);
                    if (wu == 7 && s == WO_AT && elect_one()) {
                        PROF_X(47);
                        load_wo(maps, SM_B, h, c, WBAR, 5);
                    }
                }
            } else {
                LANE_IDS
                P_CONSTS
#pragma unroll
                for (int s = 0; s < 2; s++) {
                    P_FRAGS(s)
#pragma unroll
                    for (int j = 0; j < 4; j++) {
#pragma unroll
                        for (int u = 0; u < 3; u++) {
                            const int k = 6 * (j >> 1) + 3 * (j & 1) + u;
                            mma16816(acc[u], kr[12 * s + k][0], kr[12 * s + k][1], kr[12 * s + k][2], kr[12 * s + k][3], pb[j][0], pb[j][1]);
                        }
                    }
                }
#pragma unroll 1
                for (int i = 4; i < 10; i++) {
                    const int sl = i == 5 ? 0 : (i == 6 || i == 8 ? 1 : 2);
                    const uint32_t tile = sl ? ring + (sl - 1) * TILE : xtile, tb = sl ? rb + (sl - 1) * 8 : xb;
                    if (i == 8) head_ld(lane);
                    if (i == 9) head_factor(lane);
                    P_FRAGS(i - 2)
                    mbar_wait(tb, (0xC0 >> i) & 1);
                    PROF_D(34 + i);
#pragma unroll
                    for (int k = 0; k < 6; k++) {
                        const uint32_t a = tile + V_OFF(k);
                        lds128(a, kr[24 + k][0], kr[24 + k][1], kr[24 + k][2], kr[24 + k][3]);
                        lds128(a + 3072, kr[24 + 6 + k][0], kr[24 + 6 + k][1], kr[24 + 6 + k][2], kr[24 + 6 + k][3]);
                    }
#pragma unroll
                    for (int j = 0; j < 4; j++) {
#pragma unroll
                        for (int u = 0; u < 3; u++) {
                            const int k = 6 * (j >> 1) + 3 * (j & 1) + u;
                            mma16816(acc[u], kr[24 + k][0], kr[24 + k][1], kr[24 + k][2], kr[24 + k][3], pb[j][0], pb[j][1]);
                        }
                    }
                    __syncwarp();
                    if (wu < L1R && i == 6 - 2 * (wu & 1)) tile_load_l1(tile, maps.vp, row0 + (6 - (wu & 1)) * TS, tb, lane);
                    else if (i == 4 || i == 6 || i == 7) tile_load(tile, &maps.v, row0 + (i == 4 ? 5 : i) * TS, tb);
                    if (EARLY4 >= 4 && i == EARLY4 && wu == 5 && role < NG && elect_one()) {
                        mbar_expect_tx(WBAR + 32, 12288);
                        tma3d(SM_Q + 4 * 12288, &maps.wo, 0, h * DH, 5 * c + 4, WBAR + 32, POL_EF);
                    }
                    if (i == WO_AT1 && HAS_FFN && elect_one()) {
                        uint32_t n;
                        asm volatile("atom.shared.add.u32 %0, [%1], 1;" : "=r"(n) : "r"(SM_MISC + 8) : "memory");
                        if (n == 7u) {
                            PROF_X(63);
                            load_wo(maps, SM_Q, h, c, WBAR, EARLY4 || (KEEP4 && role >= DN0) ? 4 : 5);
                        }
                    }
                }
            }
#undef P_FRAGS
#undef P_CONSTS
#undef LANE_IDS
#undef K_OFF
#undef V_OFF
        }
        PROF_D(3 + layer * 16);
        PC(layer * 32 + 1);

        uint32_t ticket = 0;
        uint4* pr;
        {
            const int tl = opq(tid), warp = tl >> 5, lane = tl & 31, g = lane >> 2, t = lane & 3, mat = lane >> 3, r8 = lane & 7;
            {
                const uint32_t d = SM_R + 4 * (warp * 196 + 8 * g + 4 * t);
                if (t < 2) {
#pragma unroll
                    for (int u = 0; u < 3; u++) sts128(d + 256 * u, acc[u][0] * sc3, acc[u][1] * sc3, acc[u][2] * sc3, acc[u][3] * sc3);
                }
                if (lane == 0) sts128(d + 768, sc2 * sc3, 0.f, 0.f, 0.f);
            }
            const int tc = min(tl, 48);
            uint4* pc = opq(&g_scr.cx[h * 4 * 56 + tc]);
            uint4* po = opq(pc + c * 56);
            const uint32_t fa = opq(SM_R + 16 * tc);
            __syncthreads();
            PROF_T(4 + layer * 16);
            PC(layer * 32 + 2);
            const int kg = warp >> 1, mg = warp & 1;
            const bool wo2 = layer && HAS_FFN;
            const bool wo4 = wo2 && !(KEEP4 && role >= DN0);
            uint32_t aw, oa, ob0, dw;
            uint32_t* tk;
            auto addrs = [&]() {
                aw = pin((wo2 ? SM_Q : SM_B) + (48 * kg + (mat >> 1) * 8 + r8) * 64 + (((2 * mg + (mat & 1)) ^ ((r8 >> 1) & 3)) << 4));
                oa = pin(SM_OS + 96 * kg + 8 * t);
                ob0 = pin(oa + 8 * t);
                dw = pin(SM_R + 4 * (4 * (16 * mg + g) + kg));
                tk = opq(g_scr.ticket + 0);
                if (HOIST & 2) pr = pin(&g_scr.acc[layer][(54 * c + min(tl, 53)) * ACC_STR]);
            };
            uint32_t a[NWPRE][3][4];
            auto preload = [&]() {
#pragma unroll
                for (int i = 0; i < NWPRE; i++) {
                    mbar_wait(WBAR + 8 * i, wo2);
#pragma unroll
                    for (int ks = 0; ks < 3; ks++) ldsm4t(aw + i * 12288 + ks * 1024, a[i][ks]);
                }
            };
            if (wu < 2) {
                if (tl < 49) {
                    float4 v[8];
#pragma unroll
                    for (int w = 0; w < 8; w++) v[w] = lds128f(fa + w * 784);
                    st_pktf(po, ((v[0].x + v[1].x) + (v[2].x + v[3].x)) + ((v[4].x + v[5].x) + (v[6].x + v[7].x)),
                            ((v[0].y + v[1].y) + (v[2].y + v[3].y)) + ((v[4].y + v[5].y) + (v[6].y + v[7].y)),
                            ((v[0].z + v[1].z) + (v[2].z + v[3].z)) + ((v[4].z + v[5].z) + (v[6].z + v[7].z)),
                            ((v[0].w + v[1].w) + (v[2].w + v[3].w)) + ((v[4].w + v[5].w) + (v[6].w + v[7].w)), tbit);
                }
                __syncwarp();
                uint4 v[4];
#pragma unroll
                for (int k = 0; k < 4; k++) v[k] = ld_pkt(pc + k * 56);
                asm volatile("bar.arrive 1, 256;" ::: "memory");
                addrs();
                const int w = 2 * tc, k3 = w / 24, r = w - 24 * k3;
                const uint32_t d0 = pin(tl < 48 ? SM_OS + 4 * (24 * k3 + (r < 16 ? 4 * (r & 3) + (r >> 2) : 16 + 2 * (r & 3) + ((r >> 2) & 1))) : SM_MISC);
                const uint32_t d1 = pin(tl < 48 ? d0 + (r < 16 ? 16 : 8) : SM_MISC + 12);
                int it = 0;
                bool more = true;
                while (__any_sync(0xffffffffu, ((v[0].w ^ tbit) | (v[1].w ^ tbit) | (v[2].w ^ tbit) | (v[3].w ^ tbit)) & 1) && more) {
#pragma unroll
                    for (int k = 0; k < 4; k++) v[k] = ld_pkt(pc + k * 56);
                    more = ++it < SPIN_CAP;
                }
                DBG(it, 5 + 100 * layer);
                const float o0 = (f_(v[0].x) + f_(v[1].x)) + (f_(v[2].x) + f_(v[3].x));
                const uint32_t w0 = pack2(o0, (f_(v[0].y) + f_(v[1].y)) + (f_(v[2].y) + f_(v[3].y)));
                sts32(d1, pack2((f_(v[0].z) + f_(v[1].z)) + (f_(v[2].z) + f_(v[3].z)), (f_(v[0].w) + f_(v[1].w)) + (f_(v[2].w) + f_(v[3].w))));
                sts32(d0, tl < 48 ? w0 : __float_as_uint(o0));
                asm volatile("bar.arrive 2, 256;" ::: "memory");
                PC(layer * 32 + 3);
                preload();
                asm volatile("bar.sync 3, 64;" ::: "memory");
            } else {
                addrs();
                asm volatile("bar.sync 1, 256;" ::: "memory");
                preload();
                PC(layer * 32 + 3);
                asm volatile("bar.sync 2, 256;" ::: "memory");
            }
            PROF_T(5 + layer * 16);
            PC(layer * 32 + 5);
            uint32_t ob[6];
            lds128(ob0, ob[0], ob[1], ob[2], ob[3]);
            lds64(oa + 64, ob[4], ob[5]);
            if (tl == 224 && layer == 0)
                asm volatile("atom.relaxed.gpu.global.inc.u32 %0, [%1], 0x7fffffff;" : "=r"(ticket) : "l"(tk) : "memory");
            auto put = [&](int i, const float (&cc)[4]) { if (t == 0) { sts32(dw + 512 * i, cc[0]); sts32(dw + 512 * i + 128, cc[2]); } };
            {
                float c0[4] = {0.f, 0.f, 0.f, 0.f}, c1[4] = {0.f, 0.f, 0.f, 0.f}, c2[4] = {0.f, 0.f, 0.f, 0.f}, c3[4] = {0.f, 0.f, 0.f, 0.f};
                mbar_wait(WBAR + 16, wo2);
#pragma unroll
                for (int ks = 0; ks < 3; ks++) {
                    mma16816v(c0, a[0][ks][0], a[0][ks][1], a[0][ks][2], a[0][ks][3], ob[2 * ks], ob[2 * ks + 1]);
                    mma16816v(c1, a[1][ks][0], a[1][ks][1], a[1][ks][2], a[1][ks][3], ob[2 * ks], ob[2 * ks + 1]);
                    if (ks == 0) mbar_wait(WBAR + 24, wo2);
                    if (ks == 1) mbar_wait(WBAR + 32, wo4);
#pragma unroll
                    for (int i = 0; i < 2; i++) ldsm4t(aw + (2 + i) * 12288 + ks * 1024, a[i][ks]);
                }
                const uint32_t aw4 = aw + (wo2 && !wo4 ? SM_B - SM_Q : 0) + 4 * 12288;
#pragma unroll
                for (int ks = 0; ks < 3; ks++) {
                    mma16816v(c2, a[0][ks][0], a[0][ks][1], a[0][ks][2], a[0][ks][3], ob[2 * ks], ob[2 * ks + 1]);
                    mma16816v(c3, a[1][ks][0], a[1][ks][1], a[1][ks][2], a[1][ks][3], ob[2 * ks], ob[2 * ks + 1]);
                    if (ks == 0) { ldsm4t(aw4, a[0][0]); ldsm4t(aw4 + 1024, a[1][0]); put(0, c0); put(1, c1); }
                    if (ks == 1) ldsm4t(aw4 + 2048, a[0][1]);
                }
                float c4[4] = {0.f, 0.f, 0.f, 0.f}, c5[4] = {0.f, 0.f, 0.f, 0.f};
                mma16816v(c4, a[0][0][0], a[0][0][1], a[0][0][2], a[0][0][3], ob[0], ob[1]);
                mma16816v(c5, a[1][0][0], a[1][0][1], a[1][0][2], a[1][0][3], ob[2], ob[3]);
                mma16816v(c4, a[0][1][0], a[0][1][1], a[0][1][2], a[0][1][3], ob[4], ob[5]);
                put(2, c2); put(3, c3);
                c4[0] += c5[0]; c4[2] += c5[2];
                put(4, c4);
            }
        }
        {
            const int tl = opq(tid);
            if (!(HOIST & 2)) pr = opq(&g_scr.acc[layer][(54 * c + min(tl, 53)) * ACC_STR]);
            const uint32_t fa = opq(SM_R + 48 * tl);
            const float il = rcp(f_(lds32(SM_MISC)));
            PC(layer * 32 + 6);
            __syncthreads();
            PROF_D(6 + layer * 16);
            PC(layer * 32 + 7);
            if (tl < 54) {
                const float4 v0 = lds128f(fa), v1 = lds128f(fa + 16), v2 = lds128f(fa + 32);
                const float y0 = il * ((v0.x + v0.y) + (v0.z + v0.w)), y1 = il * ((v1.x + v1.y) + (v1.z + v1.w)), y2 = il * ((v2.x + v2.y) + (v2.z + v2.w));
                red_pkt(pr, y0, tl == 53 ? 0.f : y1, tl == 53 ? 0.f : y2);
            }
            if (tl == 224 && layer == 0) {
                sts32(SM_MISC + 4, ticket);
                if (ticket < DN0 + NDN && (ticket < NG || !DNTH)) load_ffn(maps, ticket, SM_B, FBAR);
            }
        }
        PROF_T(7 + layer * 16);
        PC(layer * 32 + 8);
        __syncthreads();
        if (layer == 0) role = __shfl_sync(0xffffffffu, (int)lds32(SM_MISC + 4), 0);
        PC(layer * 32 + 9);
        const uint32_t DONE32 = 0x42000000u;
        if (role < NG) {
            const int tl = opq(tid), warp = tl >> 5, lane = tl & 31, g = lane >> 2, t = lane & 3, mat = lane >> 3, r8 = lane & 7;
            const uint32_t ag = SM_B + (80 * warp + (mat >> 1) * 8 + r8) * 96 + (((mat & 1) ^ (r8 >> 2)) << 4);
            constexpr int GI = 32, GK = 16 * 96;
            const bool on = (g & 1) == (t >> 1), isx = (on && g < 2) || g == 4;
            const uint32_t pm = opq(isx ? SM_XS + 160 * warp + 16 * t : (on || g == 5 ? SM_ONE : SM_ZERO)), pm2 = opq(pm + 128 - (isx ? 8 * t : 0));
            const uint32_t dg = opq(SM_R + 4 * (2 * (warp * 48 + g) + t));
            uint32_t ho = HOIST & 4 ? pin(16u * (role * 8 + 4 * warp + ((lane * 11) >> 5))) : 0;
            uint32_t fa = HOIST & 8 ? pin(SM_R + 8 * (24 * warp + 2 * min(lane, 11))) : 0;
            uint32_t pre[9][4];
            {
                bool hx = wu == 7;
                int it = 0;
                const uint4* px = opq(&g_scr.acc[layer][min(tl, 215) * ACC_STR]);
                const int cq = tl / 54, r = tl - 54 * cq, k0 = min(160 * cq + 3 * r, DM - 1);
                const uint32_t w0 = SM_XS + 4 * xpos(k0 >> 1), w1 = SM_XS + 4 * xpos(min((k0 >> 1) + 1, DM / 2 - 1));
                const bool two = tl < 216 && r != 53;
                const uint32_t e0 = opq(tl < 216 ? w0 + 2 * (k0 & 1) : SM_MISC + 12);
                const uint32_t e1 = opq(two ? ((k0 & 1) ? w1 : w0 + 2) : SM_MISC + 12), e2 = opq(two ? w1 + 2 * (k0 & 1) : SM_MISC + 12);
                const uint32_t x01 = opq(lds16(e0) | (lds16(e1) << 16)), x2 = lds16(e2);
                auto take_x = [&](const uint4 v) {
                    if (__all_sync(0xffffffffu, v.w == DONE32)) {
                        hx = true;
                        const uint32_t y01 = add2(x01, pack2(f_(v.x), f_(v.y))), y2 = add2(x2, pack2(f_(v.z), 0.f));
                        sts16(e0, y01); sts16(e1, y01 >> 16); sts16(e2, y2);
                    }
                };
                while (!mbar_test(FBAR, 0) && ++it < SPIN_CAP) { if (!hx) take_x(ld_pkt(px)); }
                uint4 v = make_uint4(0u, 0u, 0u, 0u);
                if (!hx) v = ld_pkt(px);
#pragma unroll
                for (int n = 0; n < 9; n++) ldsm4t(ag + (n % 3) * GI + (n / 3) * GK, pre[n]);
                if (layer) {
#pragma unroll
                    for (int n = 9; n < 15; n++) ldsm4t(ag + (n % 3) * GI + (n / 3) * GK, kr[n - 9]);
                }
                PC(layer * 32 + 10);
                if (!hx) {
                    bool more = true;
                    while (!__all_sync(0xffffffffu, v.w == DONE32) && more) { v = ld_pkt(px); more = ++it < SPIN_CAP; }
                    const uint32_t y01 = add2(x01, pack2(f_(v.x), f_(v.y))), y2 = add2(x2, pack2(f_(v.z), 0.f));
                    sts16(e0, y01); sts16(e1, y01 >> 16); sts16(e2, y2);
                }
                DBG(it, 6 + 100 * layer);
                PC(layer * 32 + 11);
            }
            __syncthreads();
            PC(layer * 32 + 12);
            PROF_T(9 + layer * 16);
            {
                float cc[3][4], gr[4];
                if (layer) gemv15r(cc, gr, pre, kr, pm, pm2);
                else gemv15<GK, true>(cc, gr, pre, [&](int i) { return ag + i * GI; }, pm, pm2);
                if (t < 2) {
#pragma unroll
                    for (int i = 0; i < 3; i++) { sts32(dg + 128 * i, cc[i][0] + cc[i][3]); sts32(dg + 128 * i + 64, cc[i][1] + cc[i][2]); }
                }
                if ((lane | 4) == 22) sts32(SM_ST + 8 * warp + (g & 1) * 4, gr[0]);
            }
            if (!(HOIST & 8)) fa = opq(G1W ? SM_R + 16 * min(lane, 23) : SM_R + 8 * (24 * warp + 2 * min(lane, 11)));
            if (!(HOIST & 4)) ho = 16u * (role * 8 + 4 * warp + ((lane * 11) >> 5));
            uint4* ph = reinterpret_cast<uint4*>(reinterpret_cast<char*>(g_scr.ah) + ho);
            const bool snd = ((G1W ? 0x249249 : 0x249) >> lane) & 1;
            PC(layer * 32 + 13);
            __syncthreads();
            PC(layer * 32 + 14);
            PROF_D(43 + layer * 16);
            if (wu < (G1W ? 1 : 2)) {
                float mean, inv;
                float4 v[8];
#pragma unroll
                for (int w = 0; w < 8; w++) v[w] = lds128f(fa + w * 384);
                ln_stats(mean, inv);
                const float ga = inv * ((((v[0].x + v[1].x) + (v[2].x + v[3].x)) + ((v[4].x + v[5].x) + (v[6].x + v[7].x))) -
                                        mean * (((v[0].y + v[1].y) + (v[2].y + v[3].y)) + ((v[4].y + v[5].y) + (v[6].y + v[7].y))));
                const float gb = inv * ((((v[0].z + v[1].z) + (v[2].z + v[3].z)) + ((v[4].z + v[5].z) + (v[6].z + v[7].z))) -
                                        mean * (((v[0].w + v[1].w) + (v[2].w + v[3].w)) + ((v[4].w + v[5].w) + (v[6].w + v[7].w))));
                uint32_t wd = pack2(ga, gb);
                if (role < NG / 2) {
                    const float g0 = bf_lo(wd), g1 = bf_hi(wd);
                    wd = pack2(g0 * rcp(1.0f + ex2(-1.4426950408889634f * g0)), g1 * rcp(1.0f + ex2(-1.4426950408889634f * g1)));
                }
                const uint32_t wa = __shfl_down_sync(0xffffffffu, wd, 1), wb = __shfl_down_sync(0xffffffffu, wd, 2);
                if (snd) st_pkt(ph, wd, wa, wb, tag);
            }
            if (HOLD & 2) __syncthreads();
            PROF_T(10 + layer * 16);
            PC(layer * 32 + 15);
        } else if (role < DN0 + NDN) {
            const int j = role - DN0;
            const int tl = opq(tid), warp = tl >> 5, lane = tl & 31, g = lane >> 2, t = lane & 3, mat = lane >> 3, r8 = lane & 7;
            float xr0 = 0.f, xr1 = 0.f;
            if (wu == 0) {
                const int col = 16 * j + (lane & 15), cc = col / 160, r = col - 160 * cc, e = r % 3;
                const uint4* px = &g_scr.acc[layer][(54 * cc + r / 3) * ACC_STR];
                const float x0 = bf_lo(lds16(SM_XS + 4 * xpos(col >> 1) + 2 * (col & 1)));
                uint4 v;
                int it = 0;
                bool ld = DNTH && layer == 0;
                do {
                    v = ld_pkt(px);
                    if (ld && f_(__shfl_sync(0xffffffffu, v.w, 0)) >= (float)DNTH) { ld = false; if (lane == 0) load_ffn(maps, role, SM_B, FBAR); }
                } while (!__all_sync(0xffffffffu, v.w == DONE32) && ++it < SPIN_CAP);
                DBG(it, 7 + 100 * layer);
                if (ld && lane == 0) load_ffn(maps, role, SM_B, FBAR);
                const float xres = bfr(x0 + bfr(f_(e == 0 ? v.x : (e == 1 ? v.y : v.z))));
                xr0 = __shfl_sync(0xffffffffu, xres, 2 * (lane & 7));
                xr1 = __shfl_sync(0xffffffffu, xres, 2 * (lane & 7) + 1);
            }
            PC(layer * 32 + 17);
            PROF_T(9 + layer * 16);
            const uint32_t ad = SM_B + (192 * warp + (mat >> 1) * 8 + r8) * 32 + (((mat & 1) ^ (r8 >> 2)) << 4);
            const uint32_t hs = SM_R + 384 * warp, hb = opq(hs + 16 * t), dd = opq(SM_R + 3072 + 4 * (warp * 16 + g));
            uint32_t pre[NPRE][4];
            uint32_t pos[3];
#pragma unroll
            for (int i = 0; i < 3; i++) { const int w = 3 * lane + i; pos[i] = opq(hs + 4 * ((w & ~15) + 4 * (w & 3) + ((w >> 2) & 1) + ((w >> 2) & 2))); }
            const uint4* ph = opq(&g_scr.ah[tl]);
            const uint32_t fa = opq(SM_R + 3072 + 8 * (lane & 7));
            uint2* py = opq(reinterpret_cast<uint2*>(g_scr.ay) + (AYS ? 16 : 8) * j + (lane & 7));
            uint32_t* po = opq(reinterpret_cast<uint32_t*>(out) + 8 * j + (lane & 7));
            mbar_wait(FBAR, 0);
#pragma unroll
            for (int n = 0; n < NPRE; n++) ldsm4t(ad + n * 512, pre[n]);
            PC(layer * 32 + 18);
            {
                uint4 v, u;
                int it = 0;
                bool more;
                if (PD_D) {
                    uint32_t t0, t1; asm volatile("mov.u32 %0, %%clock;" : "=r"(t0));
                    do asm volatile("mov.u32 %0, %%clock;" : "=r"(t1)); while (t1 - t0 < (layer ? PD_D : PD_D0));
                }
                do { v = ld_pkt(ph); u = ld_pkt(ph + 256); more = ++it < SPIN_CAP; }
                while (!__all_sync(0xffffffffu, v.w == tag && u.w == tag) && more);
                DBG(it, 8 + 100 * layer);
                PC(layer * 32 + 19);
                sts32(pos[0], mul2(v.x, u.x)); sts32(pos[1], mul2(v.y, u.y)); sts32(pos[2], mul2(v.z, u.z));
            }
            __syncwarp();
            PROF_T(11 + layer * 16);
            PC(layer * 32 + 20);
            {
                float cc[4][4];
                uint32_t hv[3][4];
#pragma unroll
                for (int jj = 0; jj < 3; jj++) lds128(hb + 64 * jj, hv[jj][0], hv[jj][1], hv[jj][2], hv[jj][3]);
#pragma unroll
                for (int n = 0; n < 12; n++) {
                    const int s = n < NPRE ? n : n - NPRE;
                    if (n < 4) cc[n][0] = cc[n][1] = cc[n][2] = cc[n][3] = 0.f;
                    mma16816v(cc[n & 3], pre[s][0], pre[s][1], pre[s][2], pre[s][3], hv[(n >> 1) % 3][2 * (n & 1)], hv[(n >> 1) % 3][2 * (n & 1) + 1]);
                    if (n + NPRE < 12) ldsm4t(ad + (n + NPRE) * 512, pre[n]);
                    if ((n & 1) && n < 6) lds128(hb + 64 * ((n >> 1) + 3), hv[n >> 1][0], hv[n >> 1][1], hv[n >> 1][2], hv[n >> 1][3]);
                }
                if (t == 0) { sts32(dd, (cc[0][0] + cc[1][0]) + (cc[2][0] + cc[3][0])); sts32(dd + 32, (cc[0][2] + cc[1][2]) + (cc[2][2] + cc[3][2])); }
            }
            PC(layer * 32 + 21);
            __syncthreads();
            PC(layer * 32 + 22);
            if (tl < 8) {
                float2 v[8];
#pragma unroll
                for (int w = 0; w < 8; w++) v[w] = lds64f(fa + 64 * w);
                const uint32_t y = pack2(((v[0].x + v[1].x) + (v[2].x + v[3].x)) + ((v[4].x + v[5].x) + (v[6].x + v[7].x)),
                                         ((v[0].y + v[1].y) + (v[2].y + v[3].y)) + ((v[4].y + v[5].y) + (v[6].y + v[7].y)));
                const uint32_t wd = pack2(xr0 + bf_lo(y), xr1 + bf_hi(y));
                if (layer) asm volatile("st.global.u32 [%0], %1;" ::"l"(po), "r"(wd) : "memory");
                st_pkt2(py, wd, tag);
            }
            if (HOLD & 1) __syncthreads();
            PROF_T(12 + layer * 16);
            PC(layer * 32 + 23);
        }
    }
}

typedef CUresult (*EncodeFn)(CUtensorMap*, CUtensorMapDataType, cuuint32_t, void*, const cuuint64_t*, const cuuint64_t*, const cuuint32_t*,
                             const cuuint32_t*, CUtensorMapInterleave, CUtensorMapSwizzle, CUtensorMapL2promotion, CUtensorMapFloatOOBfill);

void make_map(EncodeFn enc, CUtensorMap* m, const void* base, int rank, uint64_t d0, uint64_t d1, uint64_t d2, uint64_t s1, uint64_t s2,
              uint32_t b0, uint32_t b1, uint32_t b2, CUtensorMapSwizzle sw, CUtensorMapL2promotion pr = CU_TENSOR_MAP_L2_PROMOTION_NONE) {
    cuuint64_t dims[3] = {d0, d1, d2};
    cuuint64_t strides[2] = {s1, s2};
    cuuint32_t box[3] = {b0, b1, b2};
    cuuint32_t es[3] = {1, 1, 1};
    enc(m, CU_TENSOR_MAP_DATA_TYPE_BFLOAT16, rank, const_cast<void*>(base), dims, strides, box, es, CU_TENSOR_MAP_INTERLEAVE_NONE, sw,
        pr, CU_TENSOR_MAP_FLOAT_OOB_FILL_NONE);
}

}

extern "C" void kernel_launch(void* const* d_in, const int* in_sizes, int n_in, void* d_out, int out_size) {
    (void)in_sizes; (void)n_in; (void)out_size;
    static EncodeFn enc = nullptr;
    if (!enc) {
        void* fn = nullptr;
        cudaDriverEntryPointQueryResult qr;
        cudaGetDriverEntryPoint("cuTensorMapEncodeTiled", &fn, cudaEnableDefault, &qr);
        enc = reinterpret_cast<EncodeFn>(fn);
        cudaFuncSetAttribute(decode_kernel, cudaFuncAttributeMaxDynamicSharedMemorySize, SM_TOTAL);
    }
    Maps maps;
    make_map(enc, &maps.k, d_in[1], 2, 64, (uint64_t)NH * SK * 3, 1, 128, 0, 64, 48, 1, CU_TENSOR_MAP_SWIZZLE_128B);
    make_map(enc, &maps.v, d_in[2], 2, 64, (uint64_t)NH * SK * 3, 1, 128, 0, 64, 48, 1, CU_TENSOR_MAP_SWIZZLE_128B);
    {
        cuuint64_t dims[5] = {64, 16, NH * DH / 64, DM / 80, 5};
        cuuint64_t strides[4] = {NH * DH * 2, 128, 80 * NH * DH * 2, 16 * NH * DH * 2};
        cuuint32_t box[5] = {64, 16, 3, 2, 5};
        cuuint32_t es[5] = {1, 1, 1, 1, 1};
        enc(&maps.wq, CU_TENSOR_MAP_DATA_TYPE_BFLOAT16, 5, d_in[3], dims, strides, box, es, CU_TENSOR_MAP_INTERLEAVE_NONE, CU_TENSOR_MAP_SWIZZLE_128B,
            CU_TENSOR_MAP_L2_PROMOTION_NONE, CU_TENSOR_MAP_FLOAT_OOB_FILL_NONE);
    }
    make_map(enc, &maps.wo, d_in[4], 3, 32, NH * DH, DM / 32, DM * 2, 64, 32, 192, 1, CU_TENSOR_MAP_SWIZZLE_64B);
    constexpr int GW = 48;
    make_map(enc, &maps.w1, d_in[6], 3, FF, 160, 4, FF * 2, 160 * FF * 2, GW, 160, 4, CU_TENSOR_MAP_SWIZZLE_NONE, FFN_PROMO);
    make_map(enc, &maps.w3, d_in[7], 3, FF, 160, 4, FF * 2, 160 * FF * 2, GW, 160, 4, CU_TENSOR_MAP_SWIZZLE_NONE, FFN_PROMO);
    make_map(enc, &maps.w2, d_in[8], 3, DM, 256, 6, DM * 2, 256 * DM * 2, 16, 256, 6, CU_TENSOR_MAP_SWIZZLE_32B, FFN_PROMO);
    maps.kp = d_in[1];
    maps.vp = d_in[2];
#define KWD 16
    const int KW = KWD;
    make_map(enc, &maps.ks, d_in[1], 2, 64, (uint64_t)NH * SK * 3, 1, 128, 0, KW, 48, 1, CU_TENSOR_MAP_SWIZZLE_NONE);
    make_map(enc, &maps.vs, d_in[2], 2, 64, (uint64_t)NH * SK * 3, 1, 128, 0, KW, 48, 1, CU_TENSOR_MAP_SWIZZLE_NONE);
    decode_kernel<<<NCTA, NT, SM_TOTAL, cudaStreamPerThread>>>(maps, (const __nv_bfloat16*)d_in[0], (__nv_bfloat16*)d_out);
}
```

```cpp
#include <cuda_runtime.h>
#include <cuda_bf16.h>
#include <cuda.h>
#include <stdint.h>
#include <math.h>
#include <stdlib.h>
#include <stdio.h>

namespace {

constexpr int DM = 640;
constexpr int NH = 32;
constexpr int DH = 192;
constexpr int SK = 32768;
constexpr int WIN = 4096;
constexpr int FF = 1536;
constexpr int NCTA = 128;
constexpr int NT = 256;
constexpr int TILE = 6144;
constexpr int NG = 64;
constexpr int DN0 = 64;
constexpr int NDN = 40;

constexpr uint32_t SB = 1024;
constexpr uint32_t SM_RING = SB;
constexpr uint32_t SM_B = SM_RING + 8 * 2 * TILE;
constexpr uint32_t SM_Q = SM_B + 61440;
constexpr uint32_t SM_XS = SM_Q + 61440;
constexpr uint32_t SM_R = SM_XS + 1280;
constexpr uint32_t SM_ST = SM_R + 4096;
constexpr uint32_t SM_QS = SM_R + 6272;
constexpr uint32_t SM_OS = SM_QS + 384;
constexpr uint32_t SM_CS = SM_OS + 384;
constexpr uint32_t SM_BAR = SM_CS + 768;
constexpr uint32_t SM_XBAR = SM_BAR + 24 * 8;
constexpr uint32_t SM_MISC = SM_XBAR + 8 * 8;
constexpr uint32_t SM_ONE = SM_MISC + 32;
constexpr uint32_t SM_ZERO = SM_ONE + 160;
constexpr uint32_t SM_KX = SM_ZERO + 160;
constexpr uint32_t SM_TOTAL = SM_KX + 8 * 96 - SB;
constexpr int NEXC = 16;
static_assert(SM_TOTAL <= 232448, "shared memory");
constexpr uint32_t QBAR = SM_BAR + 16 * 8, FBAR = QBAR + 8, WBAR = QBAR + 16, QRDY = QBAR + 56;

constexpr unsigned long long POL_EF = 0x12F0000000000000ull;
constexpr unsigned long long POL_EN = 0x1000000000000000ull;

#define RT_MASK 0x2EE0u
#define RT_MASK2 0x35E0u
#define RESET_AT 14
#define WO_AT 15
#define WO_AT1 7
#define FFN_PROMO CU_TENSOR_MAP_L2_PROMOTION_NONE
#define FFN_POL POL_EF
#define HAS_FFN (role < DN0 + NDN)
#define ACC_STR 1
#define NPRE 6

#define HOIST 15
#define PD_G 0
#define PD_R 0
#define PD_D 0
#define PD_D0 0
#define AYS 0
#define G1W 0
#define EARLYQ 3
#define PADN 0
#define PCG 1
#define PCR 1
#define PCD 0
#define L1T 0
#define QAT 3
#define WPF 0
#define WPM 0
#define WPP 0
#define WOL 1
#define WOD 0
#define PKD 0
#define TWOCH 1
#define E7 0
#define QW 0
#define NWPRE 2
#define L1R 3
#define PRE1 5
#define HOLD 3
#define DNTH 23
#define KEEP4 1
#define PRE4 0
#define NEARLY (PRE4 ? 8 : 6)
#define EARLY4 1
#define XCH(w) (w)
#define LAYOUT 1
#define ROW0(w) ((h * SK + (SK - WIN) + c * 1024 + (w) * 128) * 3)
constexpr int TS = 48;
#define CAPL 19
constexpr int SPIN_CAP = 1 << CAPL;
constexpr uint32_t ONES = 0x3F803F80u;

struct Scratch {
    uint4 qx[NCTA * 48];
    uint4 qc[NCTA * 48];
    uint4 cx[NCTA * 56];
    uint4 pad0[160];
    uint4 acc[2][216 * 8];
    uint4 ay[320];
    uint4 ah[NG * 8];
    uint2 mx[NH * 32];
    uint32_t ticket[32];
    uint32_t pad1[32];
};
__device__ Scratch g_scr;
#define DBG(it, site)
#define PROF_T(i)
#define PROF_D(i)
#define PROF_X(i)
#define PC(i)

__device__ __forceinline__ uint32_t smem_u32(const void* p) { return (uint32_t)__cvta_generic_to_shared(p); }
__device__ __forceinline__ void mbar_init(uint32_t bar, uint32_t cnt) {
    asm volatile("mbarrier.init.shared::cta.b64 [%0], %1;" ::"r"(bar), "r"(cnt) : "memory");
}
__device__ __forceinline__ void mbar_expect_tx(uint32_t bar, uint32_t bytes) {
    asm volatile("mbarrier.arrive.expect_tx.shared::cta.b64 _, [%0], %1;" ::"r"(bar), "r"(bytes) : "memory");
}
__device__ __forceinline__ bool mbar_test(uint32_t bar, uint32_t parity) {
    uint32_t done;
    asm volatile("{\n.reg .pred p;\nmbarrier.try_wait.parity.shared::cta.b64 p, [%1], %2;\nselp.u32 %0, 1, 0, p;\n}"
                 : "=r"(done) : "r"(bar), "r"(parity) : "memory");
    return done;
}
__device__ __forceinline__ void mbar_wait(uint32_t bar, uint32_t parity) {
    asm volatile("{\n.reg .pred p;\n.reg .u32 n;\nmov.u32 n, 0;\n"
                 "W: mbarrier.try_wait.parity.shared::cta.b64 p, [%0], %1;\n@p bra D;\n"
                 "add.u32 n, n, 1;\nsetp.lt.u32 p, n, %2;\n@p bra W;\nD:\n}" ::"r"(bar), "r"(parity), "n"(SPIN_CAP) : "memory");
}
__device__ __forceinline__ void tma2d(uint32_t dst, const CUtensorMap* map, int c0, int c1, uint32_t bar, unsigned long long pol) {
    asm volatile("cp.async.bulk.tensor.2d.shared::cluster.global.mbarrier::complete_tx::bytes.L2::cache_hint [%0], [%1, {%3, %4}], [%2], %5;"
                 ::"r"(dst), "l"(map), "r"(bar), "r"(c0), "r"(c1), "l"(pol) : "memory");
}
__device__ __forceinline__ void tma3d(uint32_t dst, const CUtensorMap* map, int c0, int c1, int c2, uint32_t bar, unsigned long long pol) {
    asm volatile("cp.async.bulk.tensor.3d.shared::cluster.global.mbarrier::complete_tx::bytes.L2::cache_hint [%0], [%1, {%3, %4, %5}], [%2], %6;"
                 ::"r"(dst), "l"(map), "r"(bar), "r"(c0), "r"(c1), "r"(c2), "l"(pol) : "memory");
}
__device__ __forceinline__ void tma5d(uint32_t dst, const CUtensorMap* map, int c2, int c3, uint32_t bar, unsigned long long pol) {
    asm volatile("cp.async.bulk.tensor.5d.shared::cluster.global.mbarrier::complete_tx::bytes.L2::cache_hint [%0], [%1, {0, 0, %3, %4, 0}], [%2], %5;"
                 ::"r"(dst), "l"(map), "r"(bar), "r"(c2), "r"(c3), "l"(pol) : "memory");
}
__device__ __forceinline__ void tma2d_pf(const CUtensorMap* map, int c0, int c1, unsigned long long pol) {
    asm volatile("cp.async.bulk.prefetch.tensor.2d.L2.global.L2::cache_hint [%0, {%1, %2}], %3;" ::"l"(map), "r"(c0), "r"(c1), "l"(pol) : "memory");
}
__device__ __forceinline__ void tile_load(uint32_t dst, const CUtensorMap* map, int row, uint32_t bar) {
    asm volatile("{\n.reg .pred p;\nelect.sync _|p, 0xffffffff;\n"
                 "@p mbarrier.arrive.expect_tx.shared::cta.b64 _, [%2], 6144;\n"
                 "@p cp.async.bulk.tensor.2d.shared::cluster.global.mbarrier::complete_tx::bytes.L2::cache_hint [%0], [%1, {0, %3}], [%2], %4;\n}"
                 ::"r"(dst), "l"(map), "r"(bar), "r"(row), "l"(POL_EF) : "memory");
}
__device__ __forceinline__ void tile_keep(const CUtensorMap* map, int row) {
    asm volatile("{\n.reg .pred p;\nelect.sync _|p, 0xffffffff;\n"
                 "@p cp.async.bulk.prefetch.tensor.2d.L2.global.L2::cache_hint [%0, {0, %1}], %2;\n}"
                 ::"l"(map), "r"(row), "l"(POL_EN) : "memory");
}
__device__ __forceinline__ void tile_load_l1(uint32_t dst, const void* base, int row, uint32_t bar, int lane) {
    const char* g = static_cast<const char*>(base) + (size_t)row * 128 + lane * 16;
    const uint32_t s0 = dst + (lane >> 3) * 128 + (((lane & 7) ^ (lane >> 3)) << 4), s1 = s0 ^ 64;
#pragma unroll
    for (int k = 0; k < 12; k++)
        asm volatile("cp.async.ca.shared.global.L2::cache_hint [%0], [%1], 16, %2;" ::"r"(((k & 1) ? s1 : s0) + k * 512), "l"(g + k * 512), "l"(POL_EF) : "memory");
    asm volatile("cp.async.mbarrier.arrive.shared::cta.b64 [%0];" ::"r"(bar) : "memory");
    __syncwarp();
    if (lane == 0) asm volatile("mbarrier.arrive.shared::cta.b64 _, [%0];" ::"r"(bar) : "memory");
}
__device__ __forceinline__ bool elect_one() {
    uint32_t p;
    asm volatile("{\n.reg .pred p;\nelect.sync _|p, 0xffffffff;\nselp.u32 %0, 1, 0, p;\n}" : "=r"(p));
    return p;
}
__device__ __forceinline__ void lds128(uint32_t addr, uint32_t& a, uint32_t& b, uint32_t& c, uint32_t& d) {
    asm volatile("ld.shared.v4.u32 {%0,%1,%2,%3}, [%4];" : "=r"(a), "=r"(b), "=r"(c), "=r"(d) : "r"(addr) : "memory");
}
__device__ __forceinline__ void lds64(uint32_t addr, uint32_t& a, uint32_t& b) {
    asm volatile("ld.shared.v2.u32 {%0,%1}, [%2];" : "=r"(a), "=r"(b) : "r"(addr) : "memory");
}
__device__ __forceinline__ void ldsm4t(uint32_t addr, uint32_t (&a)[4]) {
    asm volatile("ldmatrix.sync.aligned.m8n8.x4.trans.shared.b16 {%0,%1,%2,%3}, [%4];" : "=r"(a[0]), "=r"(a[1]), "=r"(a[2]), "=r"(a[3]) : "r"(addr) : "memory");
}
__device__ __forceinline__ void mma16816(float (&c)[4], uint32_t a0, uint32_t a1, uint32_t a2, uint32_t a3, uint32_t b0, uint32_t b1) {
    asm("mma.sync.aligned.m16n8k16.row.col.f32.bf16.bf16.f32 {%0,%1,%2,%3}, {%4,%5,%6,%7}, {%8,%9}, {%0,%1,%2,%3};"
        : "+f"(c[0]), "+f"(c[1]), "+f"(c[2]), "+f"(c[3]) : "r"(a0), "r"(a1), "r"(a2), "r"(a3), "r"(b0), "r"(b1));
}
__device__ __forceinline__ void mma16816v(float (&c)[4], uint32_t a0, uint32_t a1, uint32_t a2, uint32_t a3, uint32_t b0, uint32_t b1) {
    asm volatile("mma.sync.aligned.m16n8k16.row.col.f32.bf16.bf16.f32 {%0,%1,%2,%3}, {%4,%5,%6,%7}, {%8,%9}, {%0,%1,%2,%3};"
        : "+f"(c[0]), "+f"(c[1]), "+f"(c[2]), "+f"(c[3]) : "r"(a0), "r"(a1), "r"(a2), "r"(a3), "r"(b0), "r"(b1));
}
__device__ __forceinline__ int xpos(int w) {
    const int seg = w / 40, r = w - 40 * seg;
    return 40 * seg + (r < 32 ? (r & 16) + 4 * (r & 3) + ((r >> 2) & 3) : 32 + 2 * (r & 3) + ((r >> 2) & 1));
}
#define NA 0
#define NA_LD ""
#define NA_ST ""
__device__ __forceinline__ void st_pkt(uint4* p, uint32_t a, uint32_t b, uint32_t c, uint32_t d) {
    asm volatile("{\n.reg .b128 t;\n.reg .b64 lo, hi;\nmov.b64 lo, {%1,%2};\nmov.b64 hi, {%3,%4};\nmov.b128 t, {lo,hi};\nst.relaxed.gpu.global" NA_ST ".b128 [%0], t;\n}"
                 ::"l"(p), "r"(a), "r"(b), "r"(c), "r"(d) : "memory");
}
__device__ __forceinline__ void st_pktf(uint4* p, float a, float b, float c, float d, uint32_t bit) {
    st_pkt(p, __float_as_uint(a), __float_as_uint(b), __float_as_uint(c), (__float_as_uint(d) & ~1u) | bit);
}
__device__ __forceinline__ void red_pkt(uint4* p, float a, float b, float c) {
    asm volatile("red.relaxed.gpu.global.add.v4.f32 [%0], {%1,%2,%3,%4};" ::"l"(p), "f"(a), "f"(b), "f"(c), "f"(1.0f) : "memory");
}
__device__ __forceinline__ uint4 ld_pkt(const uint4* p) {
    uint4 v;
    asm volatile("{\n.reg .b128 t;\n.reg .b64 lo, hi;\nld.relaxed.gpu.global" NA_LD ".b128 t, [%4];\nmov.b128 {lo,hi}, t;\nmov.b64 {%0,%1}, lo;\nmov.b64 {%2,%3}, hi;\n}"
                 : "=r"(v.x), "=r"(v.y), "=r"(v.z), "=r"(v.w) : "l"(p) : "memory");
    return v;
}
__device__ __forceinline__ uint2 ld_pkt2(const uint2* p) {
    unsigned long long v;
    asm volatile("ld.relaxed.gpu.global" NA_LD ".b64 %0, [%1];" : "=l"(v) : "l"(p) : "memory");
    return make_uint2((uint32_t)v, (uint32_t)(v >> 32));
}
__device__ __forceinline__ void st_pkt2(uint2* p, uint32_t a, uint32_t b) {
    asm volatile("st.relaxed.gpu.global" NA_ST ".b64 [%0], %1;" ::"l"(p), "l"((unsigned long long)a | ((unsigned long long)b << 32)) : "memory");
}
__device__ __forceinline__ float ex2(float x) { float y; asm("ex2.approx.ftz.f32 %0, %1;" : "=f"(y) : "f"(x)); return y; }
__device__ __forceinline__ float rcp(float x) { float y; asm("rcp.approx.ftz.f32 %0, %1;" : "=f"(y) : "f"(x)); return y; }
__device__ __forceinline__ uint32_t pack2(float lo, float hi) {
    uint32_t r; asm("cvt.rn.bf16x2.f32 %0, %1, %2;" : "=r"(r) : "f"(hi), "f"(lo)); return r;
}
__device__ __forceinline__ float bf_lo(uint32_t w) { return __uint_as_float(w << 16); }
__device__ __forceinline__ float bf_hi(uint32_t w) { return __uint_as_float(w & 0xffff0000u); }
__device__ __forceinline__ float bfr(float x) { return bf_lo(pack2(x, 0.f)); }
__device__ __forceinline__ float f_(uint32_t u) { return __uint_as_float(u); }

__device__ __forceinline__ uint32_t add2(uint32_t a, uint32_t b) { uint32_t r; asm("add.rn.bf16x2 %0, %1, %2;" : "=r"(r) : "r"(a), "r"(b)); return r; }
__device__ __forceinline__ uint32_t mul2(uint32_t a, uint32_t b) { uint32_t r; asm("mul.rn.bf16x2 %0, %1, %2;" : "=r"(r) : "r"(a), "r"(b)); return r; }
__device__ __forceinline__ uint32_t f2key(float f) { const uint32_t u = __float_as_uint(f); return u ^ ((uint32_t)((int)u >> 31) | 0x80000000u); }
__device__ __forceinline__ float key2f(uint32_t k) { return __uint_as_float(k ^ ((uint32_t)((int)~k >> 31) | 0x80000000u)); }
__device__ __forceinline__ float4 lds128f(uint32_t a) {
    float4 v; asm volatile("ld.shared.v4.f32 {%0,%1,%2,%3}, [%4];" : "=f"(v.x), "=f"(v.y), "=f"(v.z), "=f"(v.w) : "r"(a) : "memory"); return v;
}
__device__ __forceinline__ float2 lds64f(uint32_t a) { float2 v; asm volatile("ld.shared.v2.f32 {%0,%1}, [%2];" : "=f"(v.x), "=f"(v.y) : "r"(a) : "memory"); return v; }
__device__ __forceinline__ uint32_t lds32(uint32_t a) { uint32_t v; asm volatile("ld.shared.u32 %0, [%1];" : "=r"(v) : "r"(a) : "memory"); return v; }
__device__ __forceinline__ uint32_t lds16(uint32_t a) { uint32_t v; asm volatile("ld.shared.u16 %0, [%1];" : "=r"(v) : "r"(a) : "memory"); return v; }
__device__ __forceinline__ void sts16(uint32_t a, uint32_t v) { asm volatile("st.shared.u16 [%0], %1;" ::"r"(a), "r"(v) : "memory"); }
__device__ __forceinline__ void sts32(uint32_t a, uint32_t v) { asm volatile("st.shared.u32 [%0], %1;" ::"r"(a), "r"(v) : "memory"); }
__device__ __forceinline__ void sts32(uint32_t a, float v) { asm volatile("st.shared.f32 [%0], %1;" ::"r"(a), "f"(v) : "memory"); }
__device__ __forceinline__ void sts128(uint32_t a, float x, float y, float z, float w) {
    asm volatile("st.shared.v4.f32 [%0], {%1,%2,%3,%4};" ::"r"(a), "f"(x), "f"(y), "f"(z), "f"(w) : "memory");
}
template <int N> struct IC { static constexpr int value = N; };
__device__ __forceinline__ int opq(int x) { asm volatile("" : "+r"(x)); return x; }
__device__ __forceinline__ uint32_t opq(uint32_t x) { asm volatile("" : "+r"(x)); return x; }
__device__ __forceinline__ uint32_t pin(uint32_t x) { x = opq(x); sts32(SM_MISC + 12, x); return x; }
__device__ __forceinline__ float pin(float x) { sts32(SM_MISC + 12, x); return x; }
template <typename T> __device__ __forceinline__ T* pin(T* p) {
    asm volatile("{\n.reg .b32 lo, hi;\nmov.b64 {lo, hi}, %0;\nst.shared.v2.b32 [%1], {lo, hi};\n}" : "+l"(p) : "r"(SM_MISC + 16) : "memory");
    return p;
}
template <typename T> __device__ __forceinline__ T* opq(T* p) { asm volatile("" : "+l"(p)); return p; }

__device__ __forceinline__ void ln_stats(float& mean, float& inv) {
    const float4 a = lds128f(SM_ST), b = lds128f(SM_ST + 16), c = lds128f(SM_ST + 32), d = lds128f(SM_ST + 48);
    const float s2 = ((a.x + a.z) + (b.x + b.z)) + ((c.x + c.z) + (d.x + d.z));
    const float md = (((a.y + a.w) + (b.y + b.w)) + ((c.y + c.w) + (d.y + d.w))) * (1.0f / DM);
    const float var = fmaxf(s2 * (1.0f / DM) - md * md, 0.f);
    mean = bfr(md);
    asm("rsqrt.approx.ftz.f32 %0, %1;" : "=f"(inv) : "f"(var + 1e-5f));
}
template <int SK, bool GRAM, typename AddrF>
__device__ __forceinline__ void gemv15(float (&cc)[3][4], float (&gr)[4], uint32_t (&pre)[9][4], AddrF ad, uint32_t px, uint32_t px2) {
    uint32_t x0[4], x1[4];
    lds128(px, x0[0], x0[1], x0[2], x0[3]);
    lds128(px + 64, x1[0], x1[1], x1[2], x1[3]);
    gr[0] = gr[1] = gr[2] = gr[3] = 0.f;
#pragma unroll
    for (int i = 0; i < 3; i++) {
        cc[i][0] = cc[i][1] = cc[i][2] = cc[i][3] = 0.f;
        mma16816v(cc[i], pre[i][0], pre[i][1], pre[i][2], pre[i][3], x0[0], x0[1]);
    }
#pragma unroll
    for (int i = 0; i < 3; i++) ldsm4t(ad(i) + 3 * SK, pre[i]);
    if (GRAM) mma16816v(gr, x0[0], 0u, x0[1], 0u, x0[0], x0[1]);
#pragma unroll
    for (int i = 0; i < 3; i++) mma16816v(cc[i], pre[3 + i][0], pre[3 + i][1], pre[3 + i][2], pre[3 + i][3], x0[2], x0[3]);
#pragma unroll
    for (int i = 0; i < 3; i++) ldsm4t(ad(i) + 4 * SK, pre[3 + i]);
    lds64(px2, x0[0], x0[1]);
    if (GRAM) mma16816v(gr, x0[2], 0u, x0[3], 0u, x0[2], x0[3]);
#pragma unroll
    for (int i = 0; i < 3; i++) mma16816v(cc[i], pre[6 + i][0], pre[6 + i][1], pre[6 + i][2], pre[6 + i][3], x1[0], x1[1]);
    if (GRAM) mma16816v(gr, x1[0], 0u, x1[1], 0u, x1[0], x1[1]);
#pragma unroll
    for (int i = 0; i < 3; i++) mma16816v(cc[i], pre[i][0], pre[i][1], pre[i][2], pre[i][3], x1[2], x1[3]);
    if (GRAM) mma16816v(gr, x1[2], 0u, x1[3], 0u, x1[2], x1[3]);
    if (GRAM) mma16816v(gr, x0[0], 0u, x0[1], 0u, x0[0], x0[1]);
#pragma unroll
    for (int i = 0; i < 3; i++) mma16816v(cc[i], pre[3 + i][0], pre[3 + i][1], pre[3 + i][2], pre[3 + i][3], x0[0], x0[1]);
}
template <int SK, typename AddrF, typename AddrG>
__device__ __forceinline__ void gemv15p4(float (&cc)[3][4], uint32_t (&pre)[12][4], AddrF ad, uint32_t px, AddrG px2) {
    uint32_t x0[4], x1[4];
    lds128(px, x0[0], x0[1], x0[2], x0[3]);
#pragma unroll
    for (int i = 0; i < 3; i++) {
        cc[i][0] = cc[i][1] = cc[i][2] = cc[i][3] = 0.f;
        mma16816v(cc[i], pre[i][0], pre[i][1], pre[i][2], pre[i][3], x0[0], x0[1]);
    }
    lds128(px + 64, x1[0], x1[1], x1[2], x1[3]);
#pragma unroll
    for (int i = 0; i < 3; i++) mma16816v(cc[i], pre[3 + i][0], pre[3 + i][1], pre[3 + i][2], pre[3 + i][3], x0[2], x0[3]);
#pragma unroll
    for (int i = 0; i < 3; i++) ldsm4t(ad(i) + 4 * SK, pre[i]);
    lds64(px2(), x0[0], x0[1]);
#pragma unroll
    for (int i = 0; i < 3; i++) mma16816v(cc[i], pre[6 + i][0], pre[6 + i][1], pre[6 + i][2], pre[6 + i][3], x1[0], x1[1]);
#pragma unroll
    for (int i = 0; i < 3; i++) mma16816v(cc[i], pre[9 + i][0], pre[9 + i][1], pre[9 + i][2], pre[9 + i][3], x1[2], x1[3]);
#pragma unroll
    for (int i = 0; i < 3; i++) mma16816v(cc[i], pre[i][0], pre[i][1], pre[i][2], pre[i][3], x0[0], x0[1]);
}
__device__ __forceinline__ void gemv15r(float (&cc)[3][4], float (&gr)[4], const uint32_t (&pre)[9][4], const uint32_t (&ext)[45][4], uint32_t px, uint32_t px2) {
    uint32_t x0[4], x1[4], x2[2];
    lds128(px, x0[0], x0[1], x0[2], x0[3]);
    lds128(px + 64, x1[0], x1[1], x1[2], x1[3]);
    lds64(px2, x2[0], x2[1]);
    gr[0] = gr[1] = gr[2] = gr[3] = 0.f;
#pragma unroll
    for (int ks = 0; ks < 5; ks++) {
        const uint32_t b0 = ks < 2 ? x0[2 * (ks & 1)] : ks < 4 ? x1[2 * (ks & 1)] : x2[0], b1 = ks < 2 ? x0[2 * (ks & 1) + 1] : ks < 4 ? x1[2 * (ks & 1) + 1] : x2[1];
        mma16816v(gr, b0, 0u, b1, 0u, b0, b1);
#pragma unroll
        for (int i = 0; i < 3; i++) {
            if (ks == 0) cc[i][0] = cc[i][1] = cc[i][2] = cc[i][3] = 0.f;
            const uint32_t (&f)[4] = ks < 3 ? pre[ks < 3 ? 3 * ks + i : 0] : ext[ks < 3 ? 0 : 3 * (ks - 3) + i];
            mma16816v(cc[i], f[0], f[1], f[2], f[3], b0, b1);
        }
    }
}

struct Maps { CUtensorMap k, v, wq, wo, w1, w3, w2, ks, vs; const void *kp, *vp, *wop;
};
#define RT67 0
#define RT_SEL (((wu & 1) ? RT_MASK2 : RT_MASK) ^ (wu >= 6 ? RT67 : 0))
#define K4D_G 0
#define K4D_R 1500
#define PWA -1
#define PWS 0
#define PWP 0
#define K4LATE 0

__device__ __forceinline__ void load_ffn(const Maps& maps, int b, uint32_t dst, uint32_t bar) {
    const bool gu = b < NG;
    mbar_expect_tx(bar, gu ? 61440 : 49152);
    tma3d(dst, gu ? (b < NG / 2 ? &maps.w1 : &maps.w3) : &maps.w2, gu ? 48 * (b & (NG / 2 - 1)) : 16 * (b - DN0), 0, 0, bar, FFN_POL);
}

__device__ __forceinline__ void load_wo(const Maps& maps, uint32_t dst, int h, int c, uint32_t bar, int nbox) {
#pragma unroll 1
    for (int i = 0; i < nbox; i++) {
        mbar_expect_tx(bar + 8 * i, 12288);
        tma3d(dst + i * 12288, &maps.wo, 0, h * DH, 5 * c + i, bar + 8 * i, POL_EF);
    }
}

__global__ void __launch_bounds__(NT, 1)
decode_kernel(const __grid_constant__ Maps maps, const __nv_bfloat16* __restrict__ x_in, __nv_bfloat16* __restrict__ out) {
    extern __shared__ __align__(1024) unsigned char smem[];
    const int tid = threadIdx.x;
    const int wu = __shfl_sync(0xffffffffu, tid >> 5, 0);
    const int b = blockIdx.x, h = b >> 2, c = b & 3;
    if (smem_u32(smem) != SB) return;

    PROF_T(0);
    {
        const int warp = tid >> 5, lane = tid & 31;
        const uint32_t rbar = SM_BAR + warp * 16;
        if (lane == 0) {
            mbar_init(rbar, 1); mbar_init(rbar + 8, 1); mbar_init(SM_XBAR + warp * 8, 1);
            if (warp == 0) {
                mbar_init(QBAR, 1); mbar_init(FBAR, 1); mbar_init(QRDY, 2);
#pragma unroll
                for (int i = 0; i < 5; i++) mbar_init(WBAR + 8 * i, 1);
                asm volatile("fence.mbarrier_init.release.cluster;" ::: "memory");
                mbar_expect_tx(QBAR, 61440);
                tma5d(SM_Q, &maps.wq, 3 * h, 2 * c, QBAR, POL_EF);
            }
            asm volatile("fence.mbarrier_init.release.cluster;" ::: "memory");
            if (warp >= 1 && warp < 7) {
                const CUtensorMap* mp = warp == 1 ? &maps.k : warp == 2 ? &maps.v : warp == 3 ? &maps.wo : warp == 4 ? &maps.w1 : warp == 5 ? &maps.w3 : &maps.w2;
                asm volatile("prefetch.tensormap [%0];" ::"l"(mp) : "memory");
            }
        }
        if (tid == 96) sts32(SM_MISC + 8, 0u);
        if (lane < 2) sts32(SM_KX + warp * 96 + 4 * lane, 0u);
        if (tid >= 128 && tid < 148) {
            const float v = f_(tid < 138 ? ONES : 0u);
            sts128(SM_ONE + 16 * (tid - 128), v, v, v, v);
        }
        if (b == 0 && tid == 255) asm volatile("st.relaxed.gpu.global.u32 [%0], %1;" ::"l"(g_scr.ticket), "r"(0) : "memory");
        if (tid < 52) st_pkt(tid < 48 ? &g_scr.qx[b * 48 + tid] : reinterpret_cast<uint4*>(&g_scr.mx[h * 32 + c * 8]) + (tid - 48), 0, 0, 0, 0);
        if (tid >= 64 && tid < 66 && b < 108) st_pkt(&g_scr.acc[1][(2 * b + tid - 64) * ACC_STR], 0, 0, 0, 0);
        __syncthreads();
        PROF_D(14);
        if (lane == 0) {
            const int row = ROW0(warp);
            mbar_expect_tx(rbar, TILE);
            tma2d(SM_RING + warp * 2 * TILE, &maps.k, 0, row, rbar, POL_EF);
            mbar_expect_tx(rbar + 8, TILE);
            tma2d(SM_RING + (warp * 2 + 1) * TILE, &maps.k, 0, row + TS, rbar + 8, POL_EF);
        }
    }

    uint32_t kr[45][4];
#define KR(n) kr[(n) >> 2][(n) & 3]
    const float SC = 0.07216878364870322f * 1.4426950408889634f;
    int role = 0;

#pragma unroll 1
    for (int layer = 0; layer < 2; layer++) {
        const uint32_t tag = layer + 1, tbit = layer ^ 1;
        PROF_D(1 + layer * 16);
        uint2 xv = make_uint2(0u, 0u);
        uint32_t qo;
        {
            const int tl = opq(tid), warp = tl >> 5, lane = tl & 31, g = lane >> 2, t = lane & 3, mat = lane >> 3, r8 = lane & 7;
            const int kh = warp >> 2, mg = warp & 3;
            const uint32_t aq = SM_Q + kh * TILE + ((mat >> 1) * 8 + r8) * 128 + (((2 * mg + (mat & 1)) ^ r8) << 4);
            if (layer == 0 && tl < 160) xv = reinterpret_cast<const uint2*>(x_in)[tl];
            mbar_wait(QBAR, 0);
            uint32_t pre[PRE4 ? 12 : 9][4];
#pragma unroll
            for (int n = 0; n < (PRE4 ? 12 : 9); n++) ldsm4t(aq + (n % 3) * 2048 + (n / 3) * 2 * TILE, pre[n]);
            if (layer == 1) {
                __syncthreads();
                if (K4D_G | K4D_R) {
                    const uint32_t d = role < NG ? K4D_G : role >= DN0 + NDN ? K4D_R : 0;
                    uint32_t t0, t1; asm volatile("mov.u32 %0, %%clock;" : "=r"(t0));
                    do asm volatile("mov.u32 %0, %%clock;" : "=r"(t1)); while (t1 - t0 < d);
                }
                const uint32_t pc = role < NG ? PCG : role >= DN0 + NDN ? PCR : PCD;
                if (!(PCG | PCR | PCD) || !pc) {
                    if (wu < NEARLY) tile_load(SM_Q + XCH(wu) * TILE, &maps.k, ROW0(wu) + 5 * TS, SM_XBAR + wu * 8);
                } else if (wu == 7) {
                    uint32_t t0, t1; asm volatile("mov.u32 %0, %%clock;" : "=r"(t0));
#pragma unroll 1
                    for (int w = 0; w < NEARLY; w++) {
                        do asm volatile("mov.u32 %0, %%clock;" : "=r"(t1)); while (t1 - t0 < w * pc);
                        tile_load(SM_Q + XCH(w) * TILE, &maps.k, ROW0(w) + 5 * TS, SM_XBAR + w * 8);
                    }
                }
            }
            const uint32_t pm = opq(g == 1 ? SM_ONE : SM_XS + 160 * (2 * c + kh) + 16 * t);
            const uint32_t pm2 = opq(pm + 128 - (g == 1 ? 0 : 8 * t));
            const uint32_t dq = opq(SM_R + 768 * kh + 4 * (16 * mg + g));
            qo = HOIST & 1 ? pin(16u * (b * 48 + (tl & 63) + (tl >= 64 ? NCTA * 48 : 0))) : 0;
            if (tl < 160) {
                const uint32_t xa0 = opq(SM_XS + 4 * xpos(2 * tl));
                const bool xl = tl % 20 < 16;
                if (layer == 1) {
                    const uint4* px = opq(&g_scr.ay[tl]);
                    uint4 v;
                    int it = 0;
                    bool more;
                    if (PD_G | PD_R) {
                        const uint32_t d = role < NG ? PD_G : role >= DN0 + NDN ? PD_R : 0;
                        uint32_t t0, t1; asm volatile("mov.u32 %0, %%clock;" : "=r"(t0));
                        do asm volatile("mov.u32 %0, %%clock;" : "=r"(t1)); while (t1 - t0 < d);
                    }
                    do { v = ld_pkt(px); more = ++it < SPIN_CAP; } while (!__all_sync(0xffffffffu, (v.y & v.w) == 1) && more);
                    DBG(it, 1);
                    xv = make_uint2(v.x, v.z);
                }
                sts32(xa0, xv.x);
                if (xl) sts32(xa0 + 16, xv.y); else sts32(xa0 + 8, xv.y);
            }
            if (layer) PC(24);
            __syncthreads();
            if (layer) PC(25);
            PROF_T(13 + layer * 16);
            float cc[3][4], gr[4];
            gemv15<2 * TILE, false>(cc, gr, pre, [&](int i) { return aq + i * 2048; }, pm, pm2);
            if (t == 0) {
#pragma unroll
                for (int i = 0; i < 3; i++) { sts32(dq + 256 * i, cc[i][0]); sts32(dq + 256 * i + 32, cc[i][2]); }
                if (layer == 0) {
#pragma unroll
                    for (int i = 0; i < 3; i++) { sts32(dq + 256 * i + 1536, cc[i][1]); sts32(dq + 256 * i + 1568, cc[i][3]); }
                }
            }
        }
        {
            const int tl = opq(tid), j = tl & 63;
            const bool snd = j < 48 && (tl < 64 || (tl < 128 && layer == 0));
            const uint32_t fa = opq(SM_R + 16 * tl + (tl >= 64 ? 512 : 0));
            if (!(HOIST & 1)) qo = 16u * (b * 48 + (tl & 63) + (tl >= 64 ? NCTA * 48 : 0));
            uint4* pq = reinterpret_cast<uint4*>(reinterpret_cast<char*>(g_scr.qx) + qo);
            if (layer) PC(26);
            __syncthreads();
            if (layer) PC(27);
            PROF_D(33 + layer * 16);
            if (snd) {
                const float4 u = lds128f(fa), v = lds128f(fa + 768);
                st_pktf(pq, u.x + v.x, u.y + v.y, u.z + v.z, u.w + v.w, tbit);
            }
            if (layer) PC(28);
            if (layer == 1 && wu >= NEARLY) tile_load(SM_Q + XCH(wu) * TILE, &maps.k, ROW0(wu) + 5 * TS, SM_XBAR + wu * 8);
            if (EARLY4 == 1 && layer == 1 && wu == 5 && role < NG && elect_one()) {
                mbar_expect_tx(WBAR + 32, 12288);
                tma3d(SM_Q + 4 * 12288, &maps.wo, 0, h * DH, 5 * c + 4, WBAR + 32, POL_EF);
            }
            if (layer == 1 && tl >= 192 && tl < 194 && b < 108) st_pkt(&g_scr.acc[0][(2 * b + tl - 192) * ACC_STR], 0, 0, 0, 0);
            lds64(tl < 160 ? SM_XS + 8 * tl : SM_ZERO, xv.x, xv.y);
            const float e0 = bf_lo(xv.x), e1 = bf_hi(xv.x), e2 = bf_lo(xv.y), e3 = bf_hi(xv.y);
            const float s1 = (e0 + e1) + (e2 + e3), s2 = (e0 * e0 + e1 * e1) + (e2 * e2 + e3 * e3);
            const bool lo = !(tl & 16);
            float sv = (lo ? s1 : s2) + __shfl_xor_sync(0xffffffffu, lo ? s2 : s1, 16);
#pragma unroll
            for (int o = 8; o > 0; o >>= 1) sv += __shfl_xor_sync(0xffffffffu, sv, o);
            if ((tl & 15) == 0) sts32(SM_ST + 8 * (tl >> 5) + (lo ? 4 : 0), sv);
            __syncthreads();
        }

        float sc0 = -INFINITY, sc1 = -INFINITY, sc2 = 0.f, sc3 = 0.f, mw;
        uint32_t pk0, pk1;
        float acc[3][4];
        {
            const uint32_t ring = SM_RING + wu * 2 * TILE, rb = SM_BAR + wu * 16;
            const uint32_t xtile = SM_Q + XCH(wu) * TILE, xb = SM_XBAR + wu * 8;
            const int row0 = ROW0(wu);
            const uint32_t bt = SM_B + wu * TILE;
            auto issue1 = [&](int n, bool vph = false) {
                const CUtensorMap* mp = n < 8 ? &maps.k : &maps.v;
                const int row = row0 + ((n + (n >= 8 ? 2 : 0)) & 7) * TS;
                if (vph && wu < L1R && n == 12 - (wu & 1)) {
                    tile_load_l1(ring + (n & 1) * TILE, maps.vp, row, rb + (n & 1) * 8, opq(tid) & 31);
                    return;
                }
                const int k = vph || n >= 6 ? n & 1 : n >= 3 ? n - 3 : n;
                tile_load(k == 2 ? bt : ring + k * TILE, mp, row, k == 2 ? xb : rb + k * 8);
                if ((RT_SEL >> n) & 1) tile_keep(n < 8 ? &maps.ks : &maps.vs, row);
            };
            auto refill1 = [&](int s, bool vph = false) { issue1(s + 2, vph); };
#define K_OFF(i) ((uint32_t)((3 * ((g >> 1) + 4 * (g & 1)) + ((i) >> 1)) * 128 + ((t ^ ((3 * ((g >> 1) + 4 * (g & 1)) + ((i) >> 1)) & 7) ^ (((i) & 1) << 2)) << 4)))
#define V_OFF(i) ((uint32_t)((6 * t + (i)) * 128 + ((g ^ ((6 * t + (i)) & 7)) << 4)))
#define LANE_IDS const int tl = opq(tid), lane = tl & 31, g = lane >> 2, t = lane & 3; (void)tl; (void)lane; (void)g; (void)t;
            const uint32_t kx = SM_KX + wu * 96;
#pragma unroll 1
            for (int s = layer ? 5 : 0; s < 5 + layer; s++) {
                if (s < 5) {
                    LANE_IDS
                    const int k = s >= 3 ? s - 3 : s;
                    mbar_wait(k == 2 ? xb : rb + k * 8, s >= 3);
                    refill1(s);
                    if (s == 0) PROF_D(52);
                    if (s == 3) PROF_D(53);
                    const uint32_t tile = k == 2 ? bt : ring + k * TILE;
                    uint32_t mx = 0u, mn = 0xffffffffu, mn2 = 0xffffffffu;
#pragma unroll
                    for (int q = 0; q < 12; q++) {
                        uint32_t a0, a1, a2, a3;
                        lds128(tile + K_OFF(q % 6) + (q / 6) * 3072, a0, a1, a2, a3);
                        a0 &= 0x7fff7fffu; a1 &= 0x7fff7fffu; a2 &= 0x7fff7fffu; a3 &= 0x7fff7fffu;
                        mx = __vimax3_u16x2(__vimax3_u16x2(mx, a0, a1), a2, a3);
                        if (TWOCH) {
                            mn = __viaddmin_u16x2(a0, 0xffffffffu, __viaddmin_u16x2(a1, 0xffffffffu, mn));
                            mn2 = __viaddmin_u16x2(a2, 0xffffffffu, __viaddmin_u16x2(a3, 0xffffffffu, mn2));
                        } else mn = __viaddmin_u16x2(a0, 0xffffffffu, __viaddmin_u16x2(a1, 0xffffffffu, __viaddmin_u16x2(a2, 0xffffffffu, __viaddmin_u16x2(a3, 0xffffffffu, mn))));
                    }
                    mn = __vminu2(mn, mn2);
                    const uint32_t emax = __reduce_max_sync(0xffffffffu, max(mx & 0xffffu, mx >> 16)) >> 7;
                    const uint32_t base = (max(emax, 16u) - 15u) << 7, lim = base + 0x7fu;
                    bool raw = emax < 80u || emax > 190u;
                    uint32_t fl = __ballot_sync(0xffffffffu, min(mn & 0xffffu, mn >> 16) < lim);
                    if (!raw && fl) {
                        const uint32_t n0 = lds32(kx);
                        __syncwarp();
#pragma unroll 1
                        for (; fl; fl &= fl - 1) {
                            const int g = (__ffs(fl) - 1) >> 2, t = (__ffs(fl) - 1) & 3, q = min(lane, 23) >> 1, i = q >= 6 ? q - 6 : q;
                            const uint32_t a = tile + K_OFF(i) + (q >= 6 ? 3072 : 0) + 8 * (lane & 1);
                            uint32_t w0, w1;
                            lds64(a, w0, w1);
#pragma unroll 1
                            for (int e = 0; e < 4; e++) {
                                const uint32_t x = __funnelshift_r(w0, w1, 16 * e) & 0xffffu;
                                if (e == 1) w0 = w1;
                                if ((x & 0x7fffu) - 1u < lim && lane < 24) {
                                    uint32_t n;
                                    asm volatile("atom.shared.add.u32 %0, [%1], 1;" : "=r"(n) : "r"(kx) : "memory");
                                    if (n < NEXC) sts32(kx + 32 + 4 * n, x | (2 * ((2 * t + (e >> 1)) * 12 + 2 * i + (lane & 1)) + (e & 1)) << 16 | (16 * s + (q >= 6 ? 8 : 0) + g) << 24);
                                    sts16(a + 2 * e, 0u);
                                }
                            }
                        }
                        __syncwarp();
                        raw = lds32(kx) > NEXC;
                        __syncwarp();
                        if (raw && lane == 0) sts32(kx, n0);
                    }
                    if (lane == 0) {
                        sts32(kx + 8 + 4 * s, (base + (31u << 7)) << 16);
                        if (raw) sts32(kx + 4, lds32(kx + 4) | 1u << s);
                    }
                    const uint32_t b2 = (0x10000u - base) * 0x10001u;
                    auto pack = [&](auto S) {
                        constexpr int n0 = 36 * decltype(S)::value;
#pragma unroll
                        for (int q = 0; q < 12; q++) {
                            uint32_t a0, a1, a2, a3;
                            lds128(tile + K_OFF(q % 6) + (q / 6) * 3072, a0, a1, a2, a3);
                            a0 = __viaddmax_s16x2(a0 & 0x7fff7fffu, b2, 0u) | (a0 & 0x80008000u); a1 = __viaddmax_s16x2(a1 & 0x7fff7fffu, b2, 0u) | (a1 & 0x80008000u);
                            a2 = __viaddmax_s16x2(a2 & 0x7fff7fffu, b2, 0u) | (a2 & 0x80008000u); a3 = __viaddmax_s16x2(a3 & 0x7fff7fffu, b2, 0u) | (a3 & 0x80008000u);
                            KR(n0 + 3 * q) = __byte_perm(a0, a1, 0x6420);
                            KR(n0 + 3 * q + 1) = __byte_perm(a2, a3, 0x6420);
                            const uint32_t ho = __byte_perm(a2, a3, 0x7531);
                            KR(n0 + 3 * q + 2) = __byte_perm(a0, a1, 0x7531) | __funnelshift_r(ho, ho, 4);
                        }
                    };
                    switch (s) {
                        case 0: pack(IC<0>()); break;
                        case 1: pack(IC<1>()); break;
                        case 2: pack(IC<2>()); break;
                        case 3: pack(IC<3>()); break;
                        default: pack(IC<4>()); break;
                    }
                    if (PKD) { uint32_t t0, t1; asm volatile("mov.u32 %0, %%clock;" : "=r"(t0)); do asm volatile("mov.u32 %0, %%clock;" : "=r"(t1)); while (t1 - t0 < PKD); }
                    __syncwarp();
                    if (E7 && s == 4) refill1(5);
                }
                if (wu < 2 && (s == QAT || layer)) {
                    const int tc = min(opq(tid), 47);
                    const uint4* pq = opq(&g_scr.qx[h * 4 * 48 + tc]);
                    uint4 v[4];
                    int it = 0;
                    bool more = true;
#pragma unroll
                    for (int k = 0; k < 4; k++) v[k] = ld_pkt(pq + 48 * k);
                    if (layer == 0) {
                        uint4 u[4];
                        do {
#pragma unroll
                            for (int k = 0; k < 4; k++) u[k] = ld_pkt(pq + NCTA * 48 + 48 * k);
                            more = ++it < SPIN_CAP;
                        } while (!__all_sync(0xffffffffu, u[0].w & u[1].w & u[2].w & u[3].w & 1) && more);
                        DBG(it, 2);
                        sts128(SM_CS + 16 * tc, (f_(u[0].x) + f_(u[1].x)) + (f_(u[2].x) + f_(u[3].x)), (f_(u[0].y) + f_(u[1].y)) + (f_(u[2].y) + f_(u[3].y)),
                               (f_(u[0].z) + f_(u[1].z)) + (f_(u[2].z) + f_(u[3].z)), (f_(u[0].w) + f_(u[1].w)) + (f_(u[2].w) + f_(u[3].w)));
                    }
                    float mean, inv;
                    ln_stats(mean, inv);
                    const float4 cs = lds128f(SM_CS + 16 * tc);
                    mean *= -inv;
                    const float m0 = pin(mean * cs.x), m1 = pin(mean * cs.y), m2 = pin(mean * cs.z), m3 = pin(mean * cs.w);
                    const int w = 2 * tc;
                    const uint32_t qd = pin(SM_QS + 4 * (((w >> 2) & 3) * 24 + 2 * (w >> 4) + ((w >> 1) & 1)));
                    while (__any_sync(0xffffffffu, ((v[0].w ^ tbit) | (v[1].w ^ tbit) | (v[2].w ^ tbit) | (v[3].w ^ tbit)) & 1) && more) {
#pragma unroll
                        for (int k = 0; k < 4; k++) v[k] = ld_pkt(pq + 48 * k);
                        more = ++it < SPIN_CAP;
                    }
                    DBG(it, 3 + 100 * layer);
                    const float q0 = fmaf(inv, (f_(v[0].x) + f_(v[1].x)) + (f_(v[2].x) + f_(v[3].x)), m0), q1 = fmaf(inv, (f_(v[0].y) + f_(v[1].y)) + (f_(v[2].y) + f_(v[3].y)), m1);
                    const float q2 = fmaf(inv, (f_(v[0].z) + f_(v[1].z)) + (f_(v[2].z) + f_(v[3].z)), m2), q3 = fmaf(inv, (f_(v[0].w) + f_(v[1].w)) + (f_(v[2].w) + f_(v[3].w)), m3);
                    sts32(qd, pack2(q0, q1));
                    sts32(qd + 48, pack2(q2, q3));
                    sts32(SM_MISC + 24 + 4 * wu, __ballot_sync(0xffffffffu, !((fabsf(q0) + fabsf(q1)) + (fabsf(q2) + fabsf(q3)) < 0x1p30f)));
                    __syncwarp();
                    if (elect_one()) asm volatile("mbarrier.arrive.shared::cta.b64 _, [%0];" ::"r"(QRDY) : "memory");
                }
            }
            uint32_t qa, ka[6];
            {
                LANE_IDS
                qa = opq(SM_QS + (2 * t + (g & 1)) * 48);
#pragma unroll
                for (int i = 0; i < 6; i++) ka[i] = opq(xtile + K_OFF(i));
            }
            if (layer) PC(29);
            mbar_wait(QRDY, layer);
            if (layer) PC(30);
            PROF_T(2 + layer * 16);
            {
                uint32_t qf[12];
#pragma unroll
                for (int i = 0; i < 3; i++) lds128(qa + 16 * i, qf[4 * i], qf[4 * i + 1], qf[4 * i + 2], qf[4 * i + 3]);
                const int t = opq(tid) & 3;
                uint32_t qs[12];
#pragma unroll
                for (int i = 0; i < 12; i++) qs[i] = mul2(qf[i], 0x6f806f80u);
                auto kr_scores = [&](auto TAU, float& sa, float& sb) {
                    constexpr int tau = decltype(TAU)::value;
                    float cc[2][4] = {{0.f, 0.f, 0.f, 0.f}, {0.f, 0.f, 0.f, 0.f}};
#pragma unroll
                    for (int n = 0; n < 12; n++) {
                        const int q = (n & 1) * 6 + (n >> 1), i = n >> 1;
                        const uint32_t l0 = KR(36 * tau + 3 * q), l1 = KR(36 * tau + 3 * q + 1), hh = KR(36 * tau + 3 * q + 2);
                        const uint32_t h0 = hh & 0x87878787u, h1 = __funnelshift_l(hh, hh, 4) & 0x87878787u;
                        mma16816(cc[n & 1], __byte_perm(l0, h0, 0x5140), __byte_perm(l0, h0, 0x7362), __byte_perm(l1, h1, 0x5140), __byte_perm(l1, h1, 0x7362), qs[2 * i], qs[2 * i + 1]);
                    }
                    if (t == (tau & 3)) { sa = cc[0][0] + cc[0][3]; sb = cc[1][0] + cc[1][3]; }
                };
                auto stage_v = [&](auto S) {
                    constexpr int s = decltype(S)::value;
                    const int lane = opq(tid) & 31, g = lane >> 2, t = lane & 3;
#pragma unroll
                    for (int i = 0; i < 6; i++) {
                        const uint32_t a = ring + s * TILE + V_OFF(i);
                        lds128(a, kr[12 * s + i][0], kr[12 * s + i][1], kr[12 * s + i][2], kr[12 * s + i][3]);
                        lds128(a + 3072, kr[12 * s + 6 + i][0], kr[12 * s + 6 + i][1], kr[12 * s + 6 + i][2], kr[12 * s + 6 + i][3]);
                    }
                    __syncwarp();
                    tile_load(ring + s * TILE, s ? &maps.v : &maps.k, row0 + (s ? 2 : 7) * TS, rb + s * 8);
                };
                if (layer == 1) {
                    mbar_wait(xb, 0);
                    PROF_D(34);
                    float cA[4] = {0.f, 0.f, 0.f, 0.f}, cB[4] = {0.f, 0.f, 0.f, 0.f};
                    uint32_t f[6][4];
#pragma unroll
                    for (int i = 0; i < 3; i++) {
                        lds128(ka[i], f[2 * i][0], f[2 * i][1], f[2 * i][2], f[2 * i][3]);
                        lds128(ka[i] + 3072, f[2 * i + 1][0], f[2 * i + 1][1], f[2 * i + 1][2], f[2 * i + 1][3]);
                    }
#pragma unroll
                    for (int i = 0; i < 3; i++) {
                        mma16816v(cA, f[2 * i][0], f[2 * i][1], f[2 * i][2], f[2 * i][3], qf[2 * i], qf[2 * i + 1]);
                        lds128(ka[3 + i], f[2 * i][0], f[2 * i][1], f[2 * i][2], f[2 * i][3]);
                        mma16816v(cB, f[2 * i + 1][0], f[2 * i + 1][1], f[2 * i + 1][2], f[2 * i + 1][3], qf[2 * i], qf[2 * i + 1]);
                        lds128(ka[3 + i] + 3072, f[2 * i + 1][0], f[2 * i + 1][1], f[2 * i + 1][2], f[2 * i + 1][3]);
                    }
                    __syncwarp();
                    tile_load(xtile, &maps.k, row0 + 6 * TS, xb);
#pragma unroll
                    for (int i = 0; i < 3; i++) {
                        mma16816v(cA, f[2 * i][0], f[2 * i][1], f[2 * i][2], f[2 * i][3], qf[6 + 2 * i], qf[7 + 2 * i]);
                        mma16816v(cB, f[2 * i + 1][0], f[2 * i + 1][1], f[2 * i + 1][2], f[2 * i + 1][3], qf[6 + 2 * i], qf[7 + 2 * i]);
                    }
                    sc2 = cA[0] + cA[3]; sc3 = cB[0] + cB[3];
                }
                kr_scores(IC<0>(), sc0, sc1);
                kr_scores(IC<1>(), sc0, sc1);
                if (layer == 1) stage_v(IC<0>());
                kr_scores(IC<2>(), sc0, sc1);
                if (layer == 1) stage_v(IC<1>());
                kr_scores(IC<3>(), sc0, sc1);
                kr_scores(IC<4>(), sc2, sc3);
                {
                    LANE_IDS
                    const float sa = f_(lds32(kx + 8 + 4 * t)), sb = t == 0 ? f_(lds32(kx + 24)) : 1.0f;
                    const int nx = (int)lds32(kx);
                    uint32_t rm = lds32(kx + 4), big0, big1;
                    lds64(SM_MISC + 24, big0, big1);
                    if (big0 | big1) rm = 31;
                    sc0 *= sa; sc1 *= sa; sc2 *= sb; sc3 *= sb;
#pragma unroll 1
                    for (int n = 0; n < nx; n++) {
                        const uint32_t w = lds32(kx + 32 + 4 * n);
                        const int tau = w >> 28;
                        const float d = bf_lo(lds16(SM_QS + ((w >> 15) & 0x1fe))) * bf_lo(w);
                        if (((w >> 24) & 7) == g && (tau & 3) == t) {
                            const int k = ((w >> 27) & 1) + (tau >> 2) * 2;
                            if (k == 0) sc0 += d; else if (k == 1) sc1 += d; else if (k == 2) sc2 += d; else sc3 += d;
                        }
                    }
#pragma unroll 1
                    for (; rm; rm &= rm - 1) {
                        const int tau = __ffs(rm) - 1;
#pragma unroll 1
                        for (int hf = 0; hf < 2; hf++) {
                            const char* gp = static_cast<const char*>(maps.kp) + (size_t)(row0 + tau * TS) * 128 + (8 * hf + (g >> 1) + 4 * (g & 1)) * 384 + 16 * t;
                            float cA[4] = {0.f, 0.f, 0.f, 0.f};
#pragma unroll
                            for (int i = 0; i < 6; i++) {
                                const uint4 a = __ldcg(reinterpret_cast<const uint4*>(gp + 64 * i));
                                mma16816(cA, a.x, a.y, a.z, a.w, qf[2 * i], qf[2 * i + 1]);
                            }
                            if ((tau & 3) == t) {
                                const int k = hf + (tau >> 2) * 2;
                                const float d = cA[0] + cA[3];
                                if (k == 0) sc0 = d; else if (k == 1) sc1 = d; else if (k == 2) sc2 = d; else sc3 = d;
                            }
                        }
                    }
                }
                if (layer == 0) {
                    LANE_IDS
#pragma unroll 1
                    for (int s = 5; s < 8; s++) {
                        mbar_wait(s == 5 ? xb : rb + (s & 1) * 8, s == 5);
                        const uint32_t tile = s == 5 ? bt : ring + (s & 1) * TILE;
                        float cA[4] = {0.f, 0.f, 0.f, 0.f}, cB[4] = {0.f, 0.f, 0.f, 0.f};
#pragma unroll
                        for (int i = 0; i < 6; i++) {
                            uint32_t a0, a1, a2, a3;
                            lds128(tile + K_OFF(i), a0, a1, a2, a3);
                            mma16816(cA, a0, a1, a2, a3, qf[2 * i], qf[2 * i + 1]);
                            lds128(tile + K_OFF(i) + 3072, a0, a1, a2, a3);
                            mma16816(cB, a0, a1, a2, a3, qf[2 * i], qf[2 * i + 1]);
                        }
                        if (t == (s & 3)) { sc2 = cA[0] + cA[3]; sc3 = cB[0] + cB[3]; }
                        __syncwarp();
                        if (!E7 || s > 5) refill1(s);
                    }
                } else {
                    LANE_IDS
#pragma unroll 1
                    for (int i = 2; i < 4; i++) {
                        const uint32_t tile = i == 3 ? ring : xtile, tb = i == 3 ? rb : xb;
                        mbar_wait(tb, 1);
                        PROF_D(34 + i);
#pragma unroll
                        for (int k = 0; k < 6; k++) {
                            const uint32_t a = tile + K_OFF(k);
                            lds128(a, kr[24 + k][0], kr[24 + k][1], kr[24 + k][2], kr[24 + k][3]);
                            lds128(a + 3072, kr[24 + 6 + k][0], kr[24 + 6 + k][1], kr[24 + 6 + k][2], kr[24 + 6 + k][3]);
                        }
                        float cA[4] = {0.f, 0.f, 0.f, 0.f}, cB[4] = {0.f, 0.f, 0.f, 0.f}, cC[4] = {0.f, 0.f, 0.f, 0.f}, cD[4] = {0.f, 0.f, 0.f, 0.f};
#pragma unroll
                        for (int k = 0; k < 3; k++) {
                            mma16816(cA, kr[24 + k][0], kr[24 + k][1], kr[24 + k][2], kr[24 + k][3], qf[2 * k], qf[2 * k + 1]);
                            mma16816(cB, kr[24 + 6 + k][0], kr[24 + 6 + k][1], kr[24 + 6 + k][2], kr[24 + 6 + k][3], qf[2 * k], qf[2 * k + 1]);
                            mma16816(cC, kr[24 + 3 + k][0], kr[24 + 3 + k][1], kr[24 + 3 + k][2], kr[24 + 3 + k][3], qf[6 + 2 * k], qf[7 + 2 * k]);
                            mma16816(cD, kr[24 + 9 + k][0], kr[24 + 9 + k][1], kr[24 + 9 + k][2], kr[24 + 9 + k][3], qf[6 + 2 * k], qf[7 + 2 * k]);
                        }
                        __syncwarp();
                        tile_load(tile, &maps.v, row0 + (i + 1) * TS, tb);
                        if (t == i) { sc2 = (cA[0] + cC[0]) + (cA[3] + cC[3]); sc3 = (cB[0] + cD[0]) + (cB[3] + cD[3]); }
                    }
                }
            }
            {
                const uint32_t mk = __reduce_max_sync(0xffffffffu, f2key(fmaxf(fmaxf(sc0, sc1), fmaxf(sc2, sc3))));
                if ((opq(tid) & 31) == 0) st_pkt2(&g_scr.mx[h * 32 + c * 8 + wu], mk, tag);
                mw = key2f(mk);
            }
            pk0 = pack2(ex2((sc0 - mw) * SC), ex2((sc1 - mw) * SC));
            pk1 = pack2(ex2((sc2 - mw) * SC), ex2((sc3 - mw) * SC));
            sc2 = (bf_lo(pk0) + bf_hi(pk0)) + (bf_lo(pk1) + bf_hi(pk1));
#pragma unroll
            for (int o = 16; o > 0; o >>= 1) sc2 += __shfl_xor_sync(0xffffffffu, sc2, o);
#pragma unroll
            for (int s = 0; s < 3; s++) { acc[s][0] = acc[s][1] = acc[s][2] = acc[s][3] = 0.f; }
            auto head_ld = [&](int lane) { const uint2 mv = ld_pkt2(&g_scr.mx[h * 32 + lane]); sc0 = f_(mv.x); sc1 = f_(mv.y); };
            auto head_factor = [&](int lane) {
                int it = 0;
                while (!__all_sync(0xffffffffu, __float_as_uint(sc1) == tag) && ++it < SPIN_CAP) head_ld(lane);
                DBG(it, 4 + 100 * layer);
                sc3 = ex2((mw - key2f(__reduce_max_sync(0xffffffffu, __float_as_uint(sc0)))) * SC);
            };
#define P_CONSTS \
                const uint32_t sel0 = g == 0 ? 0x4410u : (g == 1 ? 0x1044u : 0x4444u); \
                const uint32_t sel1 = g == 2 ? 0x4410u : (g == 3 ? 0x1044u : 0x4444u); \
                const int src00 = 4 * (t < 2 ? 4 * t : 4 * (t - 2) + 1);
#define P_FRAGS(tau) \
                const uint32_t pk = ((tau) & 4) ? pk1 : pk0; \
                const uint32_t w0 = __shfl_sync(0xffffffffu, pk, src00 + ((tau) & 3)); \
                const uint32_t w1 = __shfl_sync(0xffffffffu, pk, src00 + ((tau) & 3) + 8); \
                uint32_t pb[4][2]; \
                _Pragma("unroll") for (int j = 0; j < 4; j++) { \
                    const uint32_t src = ((j & 1) ? w1 : w0) >> ((j >> 1) * 16); \
                    pb[j][0] = __byte_perm(src, 0, sel0); pb[j][1] = __byte_perm(src, 0, sel1); \
                }
            if (layer == 0) {
#pragma unroll 1
                for (int s = 8; s < 16; s++) {
                    LANE_IDS
                    P_CONSTS
                    if (RESET_AT == s) {
                        uint4* p = nullptr;
                        if (tl < 48) p = &g_scr.qx[b * 48 + tl];
                        else if (tl < 98) p = &g_scr.cx[b * 56 + tl - 48];
                        else if (tl < 145) {}
                        else if (tl >= 160) { if (tl < 208) p = &g_scr.qc[b * 48 + tl - 160]; }
                        else if (b < NG) { if (tl < 153) p = &g_scr.ah[b * 8 + tl - 145]; }
                        else if (b < DN0 + NDN && tl < 149) p = &g_scr.ay[(b - DN0) * (AYS ? 8 : 4) + tl - 145];
                        if (p) st_pkt(p, 0, 0, 0, tl < 48);
                    }
                    if (s == 13) head_ld(lane);
                    P_FRAGS((s + 2) & 7)
                    mbar_wait(rb + (s & 1) * 8, ((s >> 1) + 1) & 1);
                    const uint32_t tile = ring + (s & 1) * TILE;
#pragma unroll
                    for (int j = 0; j < 4; j++) {
#pragma unroll
                        for (int u = 0; u < 3; u++) {
                            uint32_t a0, a1, a2, a3;
                            lds128(tile + (j >> 1) * 3072 + V_OFF(3 * (j & 1) + u), a0, a1, a2, a3);
                            mma16816(acc[u], a0, a1, a2, a3, pb[j][0], pb[j][1]);
                        }
                    }
                    __syncwarp();
                    if (s < 14) refill1(s, true);
                    if (s == 13) head_factor(lane);
                    if (WPF && wu == 7 && s == WPF && elect_one()) {
#pragma unroll 1
                        for (int i = 0; i < 5; i++)
                            asm volatile("cp.async.bulk.prefetch.tensor.3d.L2.global.L2::cache_hint [%0, {0, %1, %2}], %3;" ::"l"(&maps.wo), "r"(h * DH), "r"(5 * c + i), "l"(WPP ? POL_EF : POL_EN) : "memory");
                    }
                    if ((WOL || wu == 7) && s == WO_AT && elect_one()) {
                        uint32_t n = 7;
                        if (WOL) {
                            if (WOL > 1) { uint32_t t0, t1; asm volatile("mov.u32 %0, %%clock;" : "=r"(t0)); do asm volatile("mov.u32 %0, %%clock;" : "=r"(t1)); while (t1 - t0 < WOL); }
                            asm volatile("atom.shared.add.u32 %0, [%1], 1;" : "=r"(n) : "r"(SM_MISC + 8) : "memory");
                        }
                        if (n == 7 && !WOD) {
                            PROF_X(47);
                            load_wo(maps, SM_B, h, c, WBAR, 5);
                        }
                    }
                }
            } else {
                LANE_IDS
                P_CONSTS
#pragma unroll
                for (int s = 0; s < 2; s++) {
                    P_FRAGS(s)
#pragma unroll
                    for (int j = 0; j < 4; j++) {
#pragma unroll
                        for (int u = 0; u < 3; u++) {
                            const int k = 6 * (j >> 1) + 3 * (j & 1) + u;
                            mma16816(acc[u], kr[12 * s + k][0], kr[12 * s + k][1], kr[12 * s + k][2], kr[12 * s + k][3], pb[j][0], pb[j][1]);
                        }
                    }
                }
#pragma unroll 1
                for (int i = 4; i < 10; i++) {
                    const int sl = i == 5 ? 0 : (i == 6 || i == 8 ? 1 : 2);
                    const uint32_t tile = sl ? ring + (sl - 1) * TILE : xtile, tb = sl ? rb + (sl - 1) * 8 : xb;
                    if (i == 8) head_ld(lane);
                    if (i == 9) head_factor(lane);
                    P_FRAGS(i - 2)
                    mbar_wait(tb, (0x310 >> i) & 1);
                    PROF_D(34 + i);
#pragma unroll
                    for (int k = 0; k < 6; k++) {
                        const uint32_t a = tile + V_OFF(k);
                        lds128(a, kr[24 + k][0], kr[24 + k][1], kr[24 + k][2], kr[24 + k][3]);
                        lds128(a + 3072, kr[24 + 6 + k][0], kr[24 + 6 + k][1], kr[24 + 6 + k][2], kr[24 + 6 + k][3]);
                    }
#pragma unroll
                    for (int j = 0; j < 4; j++) {
#pragma unroll
                        for (int u = 0; u < 3; u++) {
                            const int k = 6 * (j >> 1) + 3 * (j & 1) + u;
                            mma16816(acc[u], kr[24 + k][0], kr[24 + k][1], kr[24 + k][2], kr[24 + k][3], pb[j][0], pb[j][1]);
                        }
                    }
                    __syncwarp();
                    if (wu < L1R && i == 6 - 2 * (wu & 1)) tile_load_l1(tile, maps.vp, row0 + (6 - (wu & 1)) * TS, tb, lane);
                    else if (i == 4 || i == 6 || i == 7) tile_load(tile, &maps.v, row0 + (i == 4 ? 5 : i) * TS, tb);
                    if (EARLY4 >= 4 && i == EARLY4 && wu == 5 && role < NG && elect_one()) {
                        mbar_expect_tx(WBAR + 32, 12288);
                        tma3d(SM_Q + 4 * 12288, &maps.wo, 0, h * DH, 5 * c + 4, WBAR + 32, POL_EF);
                    }
                    if (i == WO_AT1 && HAS_FFN && elect_one()) {
                        uint32_t n;
                        asm volatile("atom.shared.add.u32 %0, [%1], 1;" : "=r"(n) : "r"(SM_MISC + 8) : "memory");
                        if (n == (WOL ? 15u : 7u)) {
                            PROF_X(63);
                            load_wo(maps, SM_Q, h, c, WBAR, EARLY4 || (KEEP4 && role >= DN0) ? 4 : 5);
                        }
                    }
                }
            }
#undef P_FRAGS
#undef P_CONSTS
#undef LANE_IDS
#undef K_OFF
#undef V_OFF
        }
        PROF_D(3 + layer * 16);
        PC(layer * 32 + 1);

        uint32_t ticket = 0;
        uint4* pr;
        {
            const int tl = opq(tid), warp = tl >> 5, lane = tl & 31, g = lane >> 2, t = lane & 3, mat = lane >> 3, r8 = lane & 7;
            {
                const uint32_t d = SM_R + 4 * (warp * 196 + 8 * g + 4 * t);
                if (t < 2) {
#pragma unroll
                    for (int u = 0; u < 3; u++) sts128(d + 256 * u, acc[u][0] * sc3, acc[u][1] * sc3, acc[u][2] * sc3, acc[u][3] * sc3);
                }
                if (lane == 0) sts128(d + 768, sc2 * sc3, 0.f, 0.f, 0.f);
            }
            const int tc = min(tl, 48);
            uint4* pc = opq(&g_scr.cx[h * 4 * 56 + tc]);
            uint4* po = opq(pc + c * 56);
            const uint32_t fa = opq(SM_R + 16 * tc);
            __syncthreads();
            PROF_T(4 + layer * 16);
            PC(layer * 32 + 2);
            const int kg = warp >> 1, mg = warp & 1;
            const bool wo2 = layer && HAS_FFN;
            const bool wo4 = wo2 && !(KEEP4 && role >= DN0);
            uint32_t aw, oa, ob0, dw;
            uint32_t* tk;
            auto addrs = [&]() {
                aw = pin((wo2 ? SM_Q : SM_B) + (48 * kg + (mat >> 1) * 8 + r8) * 64 + (((2 * mg + (mat & 1)) ^ ((r8 >> 1) & 3)) << 4));
                oa = pin(SM_OS + 96 * kg + 8 * t);
                ob0 = pin(oa + 8 * t);
                dw = pin(SM_R + 4 * (4 * (16 * mg + g) + kg));
                tk = opq(g_scr.ticket + 0);
                if (HOIST & 2) pr = pin(&g_scr.acc[layer][(54 * c + min(tl, 53)) * ACC_STR]);
            };
            uint32_t a[NWPRE][3][4];
            auto preload = [&]() {
#pragma unroll
                for (int i = 0; i < NWPRE; i++) {
                    mbar_wait(WBAR + 8 * i, wo2);
#pragma unroll
                    for (int ks = 0; ks < 3; ks++) ldsm4t(aw + i * 12288 + ks * 1024, a[i][ks]);
                }
            };
            if (wu < 2) {
                if (tl < 49) {
                    float4 v[8];
#pragma unroll
                    for (int w = 0; w < 8; w++) v[w] = lds128f(fa + w * 784);
                    st_pktf(po, ((v[0].x + v[1].x) + (v[2].x + v[3].x)) + ((v[4].x + v[5].x) + (v[6].x + v[7].x)),
                            ((v[0].y + v[1].y) + (v[2].y + v[3].y)) + ((v[4].y + v[5].y) + (v[6].y + v[7].y)),
                            ((v[0].z + v[1].z) + (v[2].z + v[3].z)) + ((v[4].z + v[5].z) + (v[6].z + v[7].z)),
                            ((v[0].w + v[1].w) + (v[2].w + v[3].w)) + ((v[4].w + v[5].w) + (v[6].w + v[7].w)), tbit);
                }
                __syncwarp();
                uint4 v[4];
#pragma unroll
                for (int k = 0; k < 4; k++) v[k] = ld_pkt(pc + k * 56);
                asm volatile("bar.arrive 1, 256;" ::: "memory");
                addrs();
                const int w = 2 * tc, k3 = w / 24, r = w - 24 * k3;
                const uint32_t d0 = pin(tl < 48 ? SM_OS + 4 * (24 * k3 + (r < 16 ? 4 * (r & 3) + (r >> 2) : 16 + 2 * (r & 3) + ((r >> 2) & 1))) : SM_MISC);
                const uint32_t d1 = pin(tl < 48 ? d0 + (r < 16 ? 16 : 8) : SM_MISC + 12);
                int it = 0;
                bool more = true;
                while (__any_sync(0xffffffffu, ((v[0].w ^ tbit) | (v[1].w ^ tbit) | (v[2].w ^ tbit) | (v[3].w ^ tbit)) & 1) && more) {
#pragma unroll
                    for (int k = 0; k < 4; k++) v[k] = ld_pkt(pc + k * 56);
                    more = ++it < SPIN_CAP;
                }
                DBG(it, 5 + 100 * layer);
                const float o0 = (f_(v[0].x) + f_(v[1].x)) + (f_(v[2].x) + f_(v[3].x));
                const uint32_t w0 = pack2(o0, (f_(v[0].y) + f_(v[1].y)) + (f_(v[2].y) + f_(v[3].y)));
                sts32(d1, pack2((f_(v[0].z) + f_(v[1].z)) + (f_(v[2].z) + f_(v[3].z)), (f_(v[0].w) + f_(v[1].w)) + (f_(v[2].w) + f_(v[3].w))));
                sts32(d0, tl < 48 ? w0 : __float_as_uint(o0));
                asm volatile("bar.arrive 2, 256;" ::: "memory");
                PC(layer * 32 + 3);
                preload();
                asm volatile("bar.sync 3, 64;" ::: "memory");
            } else {
                addrs();
                if (WOD && layer == 0 && wu == 7 && elect_one()) {
                    uint32_t t0, t1; asm volatile("mov.u32 %0, %%clock;" : "=r"(t0)); do asm volatile("mov.u32 %0, %%clock;" : "=r"(t1)); while (t1 - t0 < WOD);
                    load_wo(maps, SM_B, h, c, WBAR, 5);
                }
                __syncwarp();
                asm volatile("bar.sync 1, 256;" ::: "memory");
                preload();
                PC(layer * 32 + 3);
                asm volatile("bar.sync 2, 256;" ::: "memory");
            }
            PROF_T(5 + layer * 16);
            PC(layer * 32 + 5);
            uint32_t ob[6];
            lds128(ob0, ob[0], ob[1], ob[2], ob[3]);
            lds64(oa + 64, ob[4], ob[5]);
            if (tl == 224 && layer == 0)
                asm volatile("atom.relaxed.gpu.global.inc.u32 %0, [%1], 0x7fffffff;" : "=r"(ticket) : "l"(tk) : "memory");
            auto put = [&](int i, const float (&cc)[4]) { if (t == 0) { sts32(dw + 512 * i, cc[0]); sts32(dw + 512 * i + 128, cc[2]); } };
            {
                float c0[4] = {0.f, 0.f, 0.f, 0.f}, c1[4] = {0.f, 0.f, 0.f, 0.f}, c2[4] = {0.f, 0.f, 0.f, 0.f}, c3[4] = {0.f, 0.f, 0.f, 0.f};
                mbar_wait(WBAR + 16, wo2);
#pragma unroll
                for (int ks = 0; ks < 3; ks++) {
                    mma16816v(c0, a[0][ks][0], a[0][ks][1], a[0][ks][2], a[0][ks][3], ob[2 * ks], ob[2 * ks + 1]);
                    mma16816v(c1, a[1][ks][0], a[1][ks][1], a[1][ks][2], a[1][ks][3], ob[2 * ks], ob[2 * ks + 1]);
                    if (ks == 0) mbar_wait(WBAR + 24, wo2);
                    if (ks == 1) mbar_wait(WBAR + 32, wo4);
#pragma unroll
                    for (int i = 0; i < 2; i++) ldsm4t(aw + (2 + i) * 12288 + ks * 1024, a[i][ks]);
                }
                const uint32_t aw4 = aw + (wo2 && !wo4 ? SM_B - SM_Q : 0) + 4 * 12288;
#pragma unroll
                for (int ks = 0; ks < 3; ks++) {
                    mma16816v(c2, a[0][ks][0], a[0][ks][1], a[0][ks][2], a[0][ks][3], ob[2 * ks], ob[2 * ks + 1]);
                    mma16816v(c3, a[1][ks][0], a[1][ks][1], a[1][ks][2], a[1][ks][3], ob[2 * ks], ob[2 * ks + 1]);
                    if (ks == 0) { ldsm4t(aw4, a[0][0]); ldsm4t(aw4 + 1024, a[1][0]); put(0, c0); put(1, c1); }
                    if (ks == 1) ldsm4t(aw4 + 2048, a[0][1]);
                }
                float c4[4] = {0.f, 0.f, 0.f, 0.f}, c5[4] = {0.f, 0.f, 0.f, 0.f};
                mma16816v(c4, a[0][0][0], a[0][0][1], a[0][0][2], a[0][0][3], ob[0], ob[1]);
                mma16816v(c5, a[1][0][0], a[1][0][1], a[1][0][2], a[1][0][3], ob[2], ob[3]);
                mma16816v(c4, a[0][1][0], a[0][1][1], a[0][1][2], a[0][1][3], ob[4], ob[5]);
                put(2, c2); put(3, c3);
                c4[0] += c5[0]; c4[2] += c5[2];
                put(4, c4);
            }
        }
        {
            const int tl = opq(tid);
            if (!(HOIST & 2)) pr = opq(&g_scr.acc[layer][(54 * c + min(tl, 53)) * ACC_STR]);
            const uint32_t fa = opq(SM_R + 48 * tl);
            const float il = rcp(f_(lds32(SM_MISC)));
            PC(layer * 32 + 6);
            __syncthreads();
            PROF_D(6 + layer * 16);
            PC(layer * 32 + 7);
            if (tl < 54) {
                const float4 v0 = lds128f(fa), v1 = lds128f(fa + 16), v2 = lds128f(fa + 32);
                const float y0 = il * ((v0.x + v0.y) + (v0.z + v0.w)), y1 = il * ((v1.x + v1.y) + (v1.z + v1.w)), y2 = il * ((v2.x + v2.y) + (v2.z + v2.w));
                red_pkt(pr, y0, tl == 53 ? 0.f : y1, tl == 53 ? 0.f : y2);
            }
            if (tl == 224 && layer == 0) {
                sts32(SM_MISC + 4, ticket);
                if (ticket < DN0 + NDN && (ticket < NG || !DNTH)) load_ffn(maps, ticket, SM_B, FBAR);
            }
        }
        PROF_T(7 + layer * 16);
        PC(layer * 32 + 8);
        __syncthreads();
        if (layer == 0) role = __shfl_sync(0xffffffffu, (int)lds32(SM_MISC + 4), 0);
        PC(layer * 32 + 9);
        const uint32_t DONE32 = 0x42000000u;
        if (role < NG) {
            const int tl = opq(tid), warp = tl >> 5, lane = tl & 31, g = lane >> 2, t = lane & 3, mat = lane >> 3, r8 = lane & 7;
            const uint32_t ag = SM_B + (80 * warp + (mat >> 1) * 8 + r8) * 96 + (((mat & 1) ^ (r8 >> 2)) << 4);
            constexpr int GI = 32, GK = 16 * 96;
            const bool on = (g & 1) == (t >> 1), isx = (on && g < 2) || g == 4;
            const uint32_t pm = opq(isx ? SM_XS + 160 * warp + 16 * t : (on || g == 5 ? SM_ONE : SM_ZERO)), pm2 = opq(pm + 128 - (isx ? 8 * t : 0));
            const uint32_t dg = opq(SM_R + 4 * (2 * (warp * 48 + g) + t));
            uint32_t ho = HOIST & 4 ? pin(16u * (role * 8 + 4 * warp + ((lane * 11) >> 5))) : 0;
            uint32_t fa = HOIST & 8 ? pin(SM_R + 8 * (24 * warp + 2 * min(lane, 11))) : 0;
            uint32_t pre[9][4];
            {
                bool hx = wu == 7;
                int it = 0;
                const uint4* px = opq(&g_scr.acc[layer][min(tl, 215) * ACC_STR]);
                const int cq = tl / 54, r = tl - 54 * cq, k0 = min(160 * cq + 3 * r, DM - 1);
                const uint32_t w0 = SM_XS + 4 * xpos(k0 >> 1), w1 = SM_XS + 4 * xpos(min((k0 >> 1) + 1, DM / 2 - 1));
                const bool two = tl < 216 && r != 53;
                const uint32_t e0 = opq(tl < 216 ? w0 + 2 * (k0 & 1) : SM_MISC + 12);
                const uint32_t e1 = opq(two ? ((k0 & 1) ? w1 : w0 + 2) : SM_MISC + 12), e2 = opq(two ? w1 + 2 * (k0 & 1) : SM_MISC + 12);
                const uint32_t x01 = opq(lds16(e0) | (lds16(e1) << 16)), x2 = lds16(e2);
                auto take_x = [&](const uint4 v) {
                    if (__all_sync(0xffffffffu, v.w == DONE32)) {
                        hx = true;
                        const uint32_t y01 = add2(x01, pack2(f_(v.x), f_(v.y))), y2 = add2(x2, pack2(f_(v.z), 0.f));
                        sts16(e0, y01); sts16(e1, y01 >> 16); sts16(e2, y2);
                    }
                };
                while (!mbar_test(FBAR, 0) && ++it < SPIN_CAP) { if (!hx) take_x(ld_pkt(px)); }
                uint4 v = make_uint4(0u, 0u, 0u, 0u);
                if (!hx) v = ld_pkt(px);
#pragma unroll
                for (int n = 0; n < 9; n++) ldsm4t(ag + (n % 3) * GI + (n / 3) * GK, pre[n]);
                if (layer) {
#pragma unroll
                    for (int n = 9; n < 15; n++) ldsm4t(ag + (n % 3) * GI + (n / 3) * GK, kr[n - 9]);
                }
                PC(layer * 32 + 10);
                if (!hx) {
                    bool more = true;
                    while (!__all_sync(0xffffffffu, v.w == DONE32) && more) { v = ld_pkt(px); more = ++it < SPIN_CAP; }
                    const uint32_t y01 = add2(x01, pack2(f_(v.x), f_(v.y))), y2 = add2(x2, pack2(f_(v.z), 0.f));
                    sts16(e0, y01); sts16(e1, y01 >> 16); sts16(e2, y2);
                }
                DBG(it, 6 + 100 * layer);
                PC(layer * 32 + 11);
            }
            __syncthreads();
            PC(layer * 32 + 12);
            PROF_T(9 + layer * 16);
            {
                float cc[3][4], gr[4];
                if (layer) gemv15r(cc, gr, pre, kr, pm, pm2);
                else gemv15<GK, true>(cc, gr, pre, [&](int i) { return ag + i * GI; }, pm, pm2);
                if (t < 2) {
#pragma unroll
                    for (int i = 0; i < 3; i++) { sts32(dg + 128 * i, cc[i][0] + cc[i][3]); sts32(dg + 128 * i + 64, cc[i][1] + cc[i][2]); }
                }
                if ((lane | 4) == 22) sts32(SM_ST + 8 * warp + (g & 1) * 4, gr[0]);
            }
            if (!(HOIST & 8)) fa = opq(G1W ? SM_R + 16 * min(lane, 23) : SM_R + 8 * (24 * warp + 2 * min(lane, 11)));
            if (!(HOIST & 4)) ho = 16u * (role * 8 + 4 * warp + ((lane * 11) >> 5));
            uint4* ph = reinterpret_cast<uint4*>(reinterpret_cast<char*>(g_scr.ah) + ho);
            const bool snd = ((G1W ? 0x249249 : 0x249) >> lane) & 1;
            PC(layer * 32 + 13);
            __syncthreads();
            PC(layer * 32 + 14);
            PROF_D(43 + layer * 16);
            if (wu < (G1W ? 1 : 2)) {
                float mean, inv;
                float4 v[8];
#pragma unroll
                for (int w = 0; w < 8; w++) v[w] = lds128f(fa + w * 384);
                ln_stats(mean, inv);
                const float ga = inv * ((((v[0].x + v[1].x) + (v[2].x + v[3].x)) + ((v[4].x + v[5].x) + (v[6].x + v[7].x))) -
                                        mean * (((v[0].y + v[1].y) + (v[2].y + v[3].y)) + ((v[4].y + v[5].y) + (v[6].y + v[7].y))));
                const float gb = inv * ((((v[0].z + v[1].z) + (v[2].z + v[3].z)) + ((v[4].z + v[5].z) + (v[6].z + v[7].z))) -
                                        mean * (((v[0].w + v[1].w) + (v[2].w + v[3].w)) + ((v[4].w + v[5].w) + (v[6].w + v[7].w))));
                uint32_t wd = pack2(ga, gb);
                if (role < NG / 2) {
                    const float g0 = bf_lo(wd), g1 = bf_hi(wd);
                    wd = pack2(g0 * rcp(1.0f + ex2(-1.4426950408889634f * g0)), g1 * rcp(1.0f + ex2(-1.4426950408889634f * g1)));
                }
                const uint32_t wa = __shfl_down_sync(0xffffffffu, wd, 1), wb = __shfl_down_sync(0xffffffffu, wd, 2);
                if (snd) st_pkt(ph, wd, wa, wb, tag);
            }
            if (HOLD & 2) __syncthreads();
            PROF_T(10 + layer * 16);
            PC(layer * 32 + 15);
        } else if (role < DN0 + NDN) {
            const int j = role - DN0;
            const int tl = opq(tid), warp = tl >> 5, lane = tl & 31, g = lane >> 2, t = lane & 3, mat = lane >> 3, r8 = lane & 7;
            float xr0 = 0.f, xr1 = 0.f;
            if (wu == 0) {
                const int col = 16 * j + (lane & 15), cc = col / 160, r = col - 160 * cc, e = r % 3;
                const uint4* px = &g_scr.acc[layer][(54 * cc + r / 3) * ACC_STR];
                const float x0 = bf_lo(lds16(SM_XS + 4 * xpos(col >> 1) + 2 * (col & 1)));
                uint4 v;
                int it = 0;
                bool ld = DNTH && layer == 0;
                do {
                    v = ld_pkt(px);
                    if (ld && f_(__shfl_sync(0xffffffffu, v.w, 0)) >= (float)DNTH) { ld = false; if (lane == 0) load_ffn(maps, role, SM_B, FBAR); }
                } while (!__all_sync(0xffffffffu, v.w == DONE32) && ++it < SPIN_CAP);
                DBG(it, 7 + 100 * layer);
                if (ld && lane == 0) load_ffn(maps, role, SM_B, FBAR);
                const float xres = bfr(x0 + bfr(f_(e == 0 ? v.x : (e == 1 ? v.y : v.z))));
                xr0 = __shfl_sync(0xffffffffu, xres, 2 * (lane & 7));
                xr1 = __shfl_sync(0xffffffffu, xres, 2 * (lane & 7) + 1);
            }
            PC(layer * 32 + 17);
            PROF_T(9 + layer * 16);
            const uint32_t ad = SM_B + (192 * warp + (mat >> 1) * 8 + r8) * 32 + (((mat & 1) ^ (r8 >> 2)) << 4);
            const uint32_t hs = SM_R + 384 * warp, hb = opq(hs + 16 * t), dd = opq(SM_R + 3072 + 4 * (warp * 16 + g));
            uint32_t pre[NPRE][4];
            uint32_t pos[3];
#pragma unroll
            for (int i = 0; i < 3; i++) { const int w = 3 * lane + i; pos[i] = opq(hs + 4 * ((w & ~15) + 4 * (w & 3) + ((w >> 2) & 1) + ((w >> 2) & 2))); }
            const uint4* ph = opq(&g_scr.ah[tl]);
            const uint32_t fa = opq(SM_R + 3072 + 8 * (lane & 7));
            uint2* py = opq(reinterpret_cast<uint2*>(g_scr.ay) + (AYS ? 16 : 8) * j + (lane & 7));
            uint32_t* po = opq(reinterpret_cast<uint32_t*>(out) + 8 * j + (lane & 7));
            mbar_wait(FBAR, 0);
#pragma unroll
            for (int n = 0; n < NPRE; n++) ldsm4t(ad + n * 512, pre[n]);
            PC(layer * 32 + 18);
            {
                uint4 v, u;
                int it = 0;
                bool more;
                if (PD_D) {
                    uint32_t t0, t1; asm volatile("mov.u32 %0, %%clock;" : "=r"(t0));
                    do asm volatile("mov.u32 %0, %%clock;" : "=r"(t1)); while (t1 - t0 < (layer ? PD_D : PD_D0));
                }
                do { v = ld_pkt(ph); u = ld_pkt(ph + 256); more = ++it < SPIN_CAP; }
                while (!__all_sync(0xffffffffu, v.w == tag && u.w == tag) && more);
                DBG(it, 8 + 100 * layer);
                PC(layer * 32 + 19);
                sts32(pos[0], mul2(v.x, u.x)); sts32(pos[1], mul2(v.y, u.y)); sts32(pos[2], mul2(v.z, u.z));
            }
            __syncwarp();
            PROF_T(11 + layer * 16);
            PC(layer * 32 + 20);
            {
                float cc[4][4];
                uint32_t hv[3][4];
#pragma unroll
                for (int jj = 0; jj < 3; jj++) lds128(hb + 64 * jj, hv[jj][0], hv[jj][1], hv[jj][2], hv[jj][3]);
#pragma unroll
                for (int n = 0; n < 12; n++) {
                    const int s = n < NPRE ? n : n - NPRE;
                    if (n < 4) cc[n][0] = cc[n][1] = cc[n][2] = cc[n][3] = 0.f;
                    mma16816v(cc[n & 3], pre[s][0], pre[s][1], pre[s][2], pre[s][3], hv[(n >> 1) % 3][2 * (n & 1)], hv[(n >> 1) % 3][2 * (n & 1) + 1]);
                    if (n + NPRE < 12) ldsm4t(ad + (n + NPRE) * 512, pre[n]);
                    if ((n & 1) && n < 6) lds128(hb + 64 * ((n >> 1) + 3), hv[n >> 1][0], hv[n >> 1][1], hv[n >> 1][2], hv[n >> 1][3]);
                }
                if (t == 0) { sts32(dd, (cc[0][0] + cc[1][0]) + (cc[2][0] + cc[3][0])); sts32(dd + 32, (cc[0][2] + cc[1][2]) + (cc[2][2] + cc[3][2])); }
            }
            PC(layer * 32 + 21);
            __syncthreads();
            PC(layer * 32 + 22);
            if (tl < 8) {
                float2 v[8];
#pragma unroll
                for (int w = 0; w < 8; w++) v[w] = lds64f(fa + 64 * w);
                const uint32_t y = pack2(((v[0].x + v[1].x) + (v[2].x + v[3].x)) + ((v[4].x + v[5].x) + (v[6].x + v[7].x)),
                                         ((v[0].y + v[1].y) + (v[2].y + v[3].y)) + ((v[4].y + v[5].y) + (v[6].y + v[7].y)));
                const uint32_t wd = pack2(xr0 + bf_lo(y), xr1 + bf_hi(y));
                if (layer) asm volatile("st.global.u32 [%0], %1;" ::"l"(po), "r"(wd) : "memory");
                st_pkt2(py, wd, tag);
            }
            if (HOLD & 1) __syncthreads();
            PROF_T(12 + layer * 16);
            PC(layer * 32 + 23);
        }
    }
}

typedef CUresult (*EncodeFn)(CUtensorMap*, CUtensorMapDataType, cuuint32_t, void*, const cuuint64_t*, const cuuint64_t*, const cuuint32_t*,
                             const cuuint32_t*, CUtensorMapInterleave, CUtensorMapSwizzle, CUtensorMapL2promotion, CUtensorMapFloatOOBfill);

void make_map(EncodeFn enc, CUtensorMap* m, const void* base, int rank, uint64_t d0, uint64_t d1, uint64_t d2, uint64_t s1, uint64_t s2,
              uint32_t b0, uint32_t b1, uint32_t b2, CUtensorMapSwizzle sw, CUtensorMapL2promotion pr = CU_TENSOR_MAP_L2_PROMOTION_NONE) {
    cuuint64_t dims[3] = {d0, d1, d2};
    cuuint64_t strides[2] = {s1, s2};
    cuuint32_t box[3] = {b0, b1, b2};
    cuuint32_t es[3] = {1, 1, 1};
    enc(m, CU_TENSOR_MAP_DATA_TYPE_BFLOAT16, rank, const_cast<void*>(base), dims, strides, box, es, CU_TENSOR_MAP_INTERLEAVE_NONE, sw,
        pr, CU_TENSOR_MAP_FLOAT_OOB_FILL_NONE);
}

}

extern "C" void kernel_launch(void* const* d_in, const int* in_sizes, int n_in, void* d_out, int out_size) {
    (void)in_sizes; (void)n_in; (void)out_size;
    static EncodeFn enc = nullptr;
    if (!enc) {
        void* fn = nullptr;
        cudaDriverEntryPointQueryResult qr;
        cudaGetDriverEntryPoint("cuTensorMapEncodeTiled", &fn, cudaEnableDefault, &qr);
        enc = reinterpret_cast<EncodeFn>(fn);
        cudaFuncSetAttribute(decode_kernel, cudaFuncAttributeMaxDynamicSharedMemorySize, SM_TOTAL);
    }
    Maps maps;
    make_map(enc, &maps.k, d_in[1], 2, 64, (uint64_t)NH * SK * 3, 1, 128, 0, 64, 48, 1, CU_TENSOR_MAP_SWIZZLE_128B);
    make_map(enc, &maps.v, d_in[2], 2, 64, (uint64_t)NH * SK * 3, 1, 128, 0, 64, 48, 1, CU_TENSOR_MAP_SWIZZLE_128B);
    {
        cuuint64_t dims[5] = {64, 16, NH * DH / 64, DM / 80, 5};
        cuuint64_t strides[4] = {NH * DH * 2, 128, 80 * NH * DH * 2, 16 * NH * DH * 2};
        cuuint32_t box[5] = {64, 16, 3, 2, 5};
        cuuint32_t es[5] = {1, 1, 1, 1, 1};
        enc(&maps.wq, CU_TENSOR_MAP_DATA_TYPE_BFLOAT16, 5, d_in[3], dims, strides, box, es, CU_TENSOR_MAP_INTERLEAVE_NONE, CU_TENSOR_MAP_SWIZZLE_128B,
            CU_TENSOR_MAP_L2_PROMOTION_NONE, CU_TENSOR_MAP_FLOAT_OOB_FILL_NONE);
    }
    make_map(enc, &maps.wo, d_in[4], 3, 32, NH * DH, DM / 32, DM * 2, 64, 32, 192, 1, CU_TENSOR_MAP_SWIZZLE_64B);
    constexpr int GW = 48;
    make_map(enc, &maps.w1, d_in[6], 3, FF, 160, 4, FF * 2, 160 * FF * 2, GW, 160, 4, CU_TENSOR_MAP_SWIZZLE_NONE, FFN_PROMO);
    make_map(enc, &maps.w3, d_in[7], 3, FF, 160, 4, FF * 2, 160 * FF * 2, GW, 160, 4, CU_TENSOR_MAP_SWIZZLE_NONE, FFN_PROMO);
    make_map(enc, &maps.w2, d_in[8], 3, DM, 256, 6, DM * 2, 256 * DM * 2, 16, 256, 6, CU_TENSOR_MAP_SWIZZLE_32B, FFN_PROMO);
    maps.kp = d_in[1];
    maps.wop = d_in[4];
    maps.vp = d_in[2];
#define KWD 16
    const int KW = KWD;
    make_map(enc, &maps.ks, d_in[1], 2, 64, (uint64_t)NH * SK * 3, 1, 128, 0, KW, 48, 1, CU_TENSOR_MAP_SWIZZLE_NONE);
    make_map(enc, &maps.vs, d_in[2], 2, 64, (uint64_t)NH * SK * 3, 1, 128, 0, KW, 48, 1, CU_TENSOR_MAP_SWIZZLE_NONE);
    decode_kernel<<<NCTA, NT, SM_TOTAL, cudaStreamPerThread>>>(maps, (const __nv_bfloat16*)d_in[0], (__nv_bfloat16*)d_out);
}
```

```cpp
#include <cuda_runtime.h>
#include <cuda_bf16.h>
#include <cuda.h>
#include <stdint.h>
#include <math.h>

namespace {

constexpr int DM = 640;
constexpr int NH = 32;
constexpr int DH = 192;
constexpr int SK = 32768;
constexpr int WIN = 4096;
constexpr int FF = 1536;
constexpr int NCTA = 128;
constexpr int NT = 256;
constexpr int TILE = 6144;
constexpr int TS = 48;
constexpr int NG = 64;
constexpr int DN0 = 64;
constexpr int NDN = 40;

constexpr uint32_t SB = 1024;
constexpr uint32_t SM_RING = SB;
constexpr uint32_t SM_B = SM_RING + 8 * 2 * TILE;
constexpr uint32_t SM_Q = SM_B + 61440;
constexpr uint32_t SM_XS = SM_Q + 61440;
constexpr uint32_t SM_R = SM_XS + 1280;
constexpr uint32_t SM_ST = SM_R + 4096;
constexpr uint32_t SM_QS = SM_R + 6272;
constexpr uint32_t SM_OS = SM_QS + 384;
constexpr uint32_t SM_CS = SM_OS + 384;
constexpr uint32_t SM_BAR = SM_CS + 768;
constexpr uint32_t SM_XBAR = SM_BAR + 24 * 8;
constexpr uint32_t SM_MISC = SM_XBAR + 8 * 8;
constexpr uint32_t SM_ONE = SM_MISC + 32;
constexpr uint32_t SM_ZERO = SM_ONE + 160;
constexpr uint32_t SM_KX = SM_ZERO + 160;
constexpr uint32_t SM_TOTAL = SM_KX + 8 * 96 - SB;
constexpr int NEXC = 16;
static_assert(SM_TOTAL <= 232448, "shared memory");
constexpr uint32_t QBAR = SM_BAR + 16 * 8, FBAR = QBAR + 8, WBAR = QBAR + 16, QRDY = QBAR + 56;

constexpr unsigned long long POL_EF = 0x12F0000000000000ull;
constexpr unsigned long long POL_EN = 0x1000000000000000ull;

constexpr uint32_t RT_EVEN = 0x2EE0u, RT_ODD = 0x35E0u;
constexpr int L1R = 3;
constexpr int DNTH = 23;
constexpr int NPRE = 6;
constexpr int SPIN_CAP = 1 << 19;
constexpr uint32_t ONES = 0x3F803F80u;
#define ROW0(w) ((h * SK + (SK - WIN) + c * 1024 + (w) * 128) * 3)

struct Scratch {
    uint4 qx[NCTA * 48];
    uint4 qc[NCTA * 48];
    uint4 cx[NCTA * 56];
    uint4 acc[2][256];
    uint4 ay[256];
    uint4 pad0[256];
    uint4 ah[NG * 8];
    uint2 mx[NH * 32];
    uint32_t ticket[32];
};
__device__ __align__(4096) Scratch g_scr;
struct Maps { CUtensorMap k, v, wq, wo, w1, w3, w2, ks, vs; const void *kp, *vp; Scratch* scr; };

__device__ __forceinline__ uint32_t smem_u32(const void* p) { return (uint32_t)__cvta_generic_to_shared(p); }
__device__ __forceinline__ void mbar_init(uint32_t bar, uint32_t cnt) {
    asm volatile("mbarrier.init.shared::cta.b64 [%0], %1;" ::"r"(bar), "r"(cnt) : "memory");
}
__device__ __forceinline__ void mbar_expect_tx(uint32_t bar, uint32_t bytes) {
    asm volatile("mbarrier.arrive.expect_tx.shared::cta.b64 _, [%0], %1;" ::"r"(bar), "r"(bytes) : "memory");
}
__device__ __forceinline__ bool mbar_test(uint32_t bar, uint32_t parity) {
    uint32_t done;
    asm volatile("{\n.reg .pred p;\nmbarrier.try_wait.parity.shared::cta.b64 p, [%1], %2;\nselp.u32 %0, 1, 0, p;\n}"
                 : "=r"(done) : "r"(bar), "r"(parity) : "memory");
    return done;
}
__device__ __forceinline__ void mbar_wait(uint32_t bar, uint32_t parity) {
    asm volatile("{\n.reg .pred p;\n.reg .u32 n;\nmov.u32 n, 0;\n"
                 "W: mbarrier.try_wait.parity.shared::cta.b64 p, [%0], %1;\n@p bra D;\n"
                 "add.u32 n, n, 1;\nsetp.lt.u32 p, n, %2;\n@p bra W;\nD:\n}" ::"r"(bar), "r"(parity), "n"(SPIN_CAP) : "memory");
}
__device__ __forceinline__ void tma2d(uint32_t dst, const CUtensorMap* map, int c0, int c1, uint32_t bar, unsigned long long pol) {
    asm volatile("cp.async.bulk.tensor.2d.shared::cluster.global.mbarrier::complete_tx::bytes.L2::cache_hint [%0], [%1, {%3, %4}], [%2], %5;"
                 ::"r"(dst), "l"(map), "r"(bar), "r"(c0), "r"(c1), "l"(pol) : "memory");
}
__device__ __forceinline__ void tma3d(uint32_t dst, const CUtensorMap* map, int c0, int c1, int c2, uint32_t bar, unsigned long long pol) {
    asm volatile("cp.async.bulk.tensor.3d.shared::cluster.global.mbarrier::complete_tx::bytes.L2::cache_hint [%0], [%1, {%3, %4, %5}], [%2], %6;"
                 ::"r"(dst), "l"(map), "r"(bar), "r"(c0), "r"(c1), "r"(c2), "l"(pol) : "memory");
}
__device__ __forceinline__ void tma5d(uint32_t dst, const CUtensorMap* map, int c2, int c3, uint32_t bar, unsigned long long pol) {
    asm volatile("cp.async.bulk.tensor.5d.shared::cluster.global.mbarrier::complete_tx::bytes.L2::cache_hint [%0], [%1, {0, 0, %3, %4, 0}], [%2], %5;"
                 ::"r"(dst), "l"(map), "r"(bar), "r"(c2), "r"(c3), "l"(pol) : "memory");
}
__device__ __forceinline__ void tile_load(uint32_t dst, const CUtensorMap* map, int row, uint32_t bar) {
    asm volatile("{\n.reg .pred p;\nelect.sync _|p, 0xffffffff;\n"
                 "@p mbarrier.arrive.expect_tx.shared::cta.b64 _, [%2], 6144;\n"
                 "@p cp.async.bulk.tensor.2d.shared::cluster.global.mbarrier::complete_tx::bytes.L2::cache_hint [%0], [%1, {0, %3}], [%2], %4;\n}"
                 ::"r"(dst), "l"(map), "r"(bar), "r"(row), "l"(POL_EF) : "memory");
}
__device__ __forceinline__ void tile_keep(const CUtensorMap* map, int row) {
    asm volatile("{\n.reg .pred p;\nelect.sync _|p, 0xffffffff;\n"
                 "@p cp.async.bulk.prefetch.tensor.2d.L2.global.L2::cache_hint [%0, {0, %1}], %2;\n}"
                 ::"l"(map), "r"(row), "l"(POL_EN) : "memory");
}
__device__ __forceinline__ void tile_load_l1(uint32_t dst, const void* base, int row, uint32_t bar, int lane) {
    const char* g = static_cast<const char*>(base) + (size_t)row * 128 + lane * 16;
    const uint32_t s0 = dst + (lane >> 3) * 128 + (((lane & 7) ^ (lane >> 3)) << 4), s1 = s0 ^ 64;
#pragma unroll
    for (int k = 0; k < 12; k++)
        asm volatile("cp.async.ca.shared.global.L2::cache_hint [%0], [%1], 16, %2;" ::"r"(((k & 1) ? s1 : s0) + k * 512), "l"(g + k * 512), "l"(POL_EF) : "memory");
    asm volatile("cp.async.mbarrier.arrive.shared::cta.b64 [%0];" ::"r"(bar) : "memory");
    __syncwarp();
    if (lane == 0) asm volatile("mbarrier.arrive.shared::cta.b64 _, [%0];" ::"r"(bar) : "memory");
}
__device__ __forceinline__ bool elect_one() {
    uint32_t p;
    asm volatile("{\n.reg .pred p;\nelect.sync _|p, 0xffffffff;\nselp.u32 %0, 1, 0, p;\n}" : "=r"(p));
    return p;
}
__device__ __forceinline__ void delay(uint32_t clocks) {
    uint32_t t0, t1;
    asm volatile("mov.u32 %0, %%clock;" : "=r"(t0));
    do asm volatile("mov.u32 %0, %%clock;" : "=r"(t1)); while (t1 - t0 < clocks);
}
__device__ __forceinline__ void lds128(uint32_t addr, uint32_t& a, uint32_t& b, uint32_t& c, uint32_t& d) {
    asm volatile("ld.shared.v4.u32 {%0,%1,%2,%3}, [%4];" : "=r"(a), "=r"(b), "=r"(c), "=r"(d) : "r"(addr) : "memory");
}
__device__ __forceinline__ void lds64(uint32_t addr, uint32_t& a, uint32_t& b) {
    asm volatile("ld.shared.v2.u32 {%0,%1}, [%2];" : "=r"(a), "=r"(b) : "r"(addr) : "memory");
}
__device__ __forceinline__ void ldsm4t(uint32_t addr, uint32_t (&a)[4]) {
    asm volatile("ldmatrix.sync.aligned.m8n8.x4.trans.shared.b16 {%0,%1,%2,%3}, [%4];" : "=r"(a[0]), "=r"(a[1]), "=r"(a[2]), "=r"(a[3]) : "r"(addr) : "memory");
}
__device__ __forceinline__ void mma16816(float (&c)[4], uint32_t a0, uint32_t a1, uint32_t a2, uint32_t a3, uint32_t b0, uint32_t b1) {
    asm("mma.sync.aligned.m16n8k16.row.col.f32.bf16.bf16.f32 {%0,%1,%2,%3}, {%4,%5,%6,%7}, {%8,%9}, {%0,%1,%2,%3};"
        : "+f"(c[0]), "+f"(c[1]), "+f"(c[2]), "+f"(c[3]) : "r"(a0), "r"(a1), "r"(a2), "r"(a3), "r"(b0), "r"(b1));
}
__device__ __forceinline__ void mma16816v(float (&c)[4], uint32_t a0, uint32_t a1, uint32_t a2, uint32_t a3, uint32_t b0, uint32_t b1) {
    asm volatile("mma.sync.aligned.m16n8k16.row.col.f32.bf16.bf16.f32 {%0,%1,%2,%3}, {%4,%5,%6,%7}, {%8,%9}, {%0,%1,%2,%3};"
        : "+f"(c[0]), "+f"(c[1]), "+f"(c[2]), "+f"(c[3]) : "r"(a0), "r"(a1), "r"(a2), "r"(a3), "r"(b0), "r"(b1));
}
__device__ __forceinline__ int xpos(int w) {
    const int seg = w / 40, r = w - 40 * seg;
    return 40 * seg + (r < 32 ? (r & 16) + 4 * (r & 3) + ((r >> 2) & 3) : 32 + 2 * (r & 3) + ((r >> 2) & 1));
}
__device__ __forceinline__ void st_pkt(uint4* p, uint32_t a, uint32_t b, uint32_t c, uint32_t d) {
    asm volatile("{\n.reg .b128 t;\n.reg .b64 lo, hi;\nmov.b64 lo, {%1,%2};\nmov.b64 hi, {%3,%4};\nmov.b128 t, {lo,hi};\nst.relaxed.gpu.global.b128 [%0], t;\n}"
                 ::"l"(p), "r"(a), "r"(b), "r"(c), "r"(d) : "memory");
}
__device__ __forceinline__ void st_pktf(uint4* p, float a, float b, float c, float d, uint32_t bit) {
    st_pkt(p, __float_as_uint(a), __float_as_uint(b), __float_as_uint(c), (__float_as_uint(d) & ~1u) | bit);
}
__device__ __forceinline__ void red_pkt(uint4* p, float a, float b, float c) {
    asm volatile("red.relaxed.gpu.global.add.v4.f32 [%0], {%1,%2,%3,%4};" ::"l"(p), "f"(a), "f"(b), "f"(c), "f"(1.0f) : "memory");
}
__device__ __forceinline__ uint4 ld_pkt(const uint4* p) {
    uint4 v;
    asm volatile("{\n.reg .b128 t;\n.reg .b64 lo, hi;\nld.relaxed.gpu.global.b128 t, [%4];\nmov.b128 {lo,hi}, t;\nmov.b64 {%0,%1}, lo;\nmov.b64 {%2,%3}, hi;\n}"
                 : "=r"(v.x), "=r"(v.y), "=r"(v.z), "=r"(v.w) : "l"(p) : "memory");
    return v;
}
__device__ __forceinline__ uint2 ld_pkt2(const uint2* p) {
    unsigned long long v;
    asm volatile("ld.relaxed.gpu.global.b64 %0, [%1];" : "=l"(v) : "l"(p) : "memory");
    return make_uint2((uint32_t)v, (uint32_t)(v >> 32));
}
__device__ __forceinline__ void st_pkt2(uint2* p, uint32_t a, uint32_t b) {
    asm volatile("st.relaxed.gpu.global.b64 [%0], %1;" ::"l"(p), "l"((unsigned long long)a | ((unsigned long long)b << 32)) : "memory");
}
__device__ __forceinline__ float ex2(float x) { float y; asm("ex2.approx.ftz.f32 %0, %1;" : "=f"(y) : "f"(x)); return y; }
__device__ __forceinline__ float rcp(float x) { float y; asm("rcp.approx.ftz.f32 %0, %1;" : "=f"(y) : "f"(x)); return y; }
__device__ __forceinline__ uint32_t pack2(float lo, float hi) {
    uint32_t r; asm("cvt.rn.bf16x2.f32 %0, %1, %2;" : "=r"(r) : "f"(hi), "f"(lo)); return r;
}
__device__ __forceinline__ float bf_lo(uint32_t w) { return __uint_as_float(w << 16); }
__device__ __forceinline__ float bf_hi(uint32_t w) { return __uint_as_float(w & 0xffff0000u); }
__device__ __forceinline__ float bfr(float x) { return bf_lo(pack2(x, 0.f)); }
__device__ __forceinline__ float f_(uint32_t u) { return __uint_as_float(u); }

__device__ __forceinline__ uint32_t add2(uint32_t a, uint32_t b) { uint32_t r; asm("add.rn.bf16x2 %0, %1, %2;" : "=r"(r) : "r"(a), "r"(b)); return r; }
__device__ __forceinline__ uint32_t mul2(uint32_t a, uint32_t b) { uint32_t r; asm("mul.rn.bf16x2 %0, %1, %2;" : "=r"(r) : "r"(a), "r"(b)); return r; }
__device__ __forceinline__ uint32_t f2key(float f) { const uint32_t u = __float_as_uint(f); return u ^ ((uint32_t)((int)u >> 31) | 0x80000000u); }
__device__ __forceinline__ float key2f(uint32_t k) { return __uint_as_float(k ^ ((uint32_t)((int)~k >> 31) | 0x80000000u)); }
__device__ __forceinline__ float4 lds128f(uint32_t a) {
    float4 v; asm volatile("ld.shared.v4.f32 {%0,%1,%2,%3}, [%4];" : "=f"(v.x), "=f"(v.y), "=f"(v.z), "=f"(v.w) : "r"(a) : "memory"); return v;
}
__device__ __forceinline__ float2 lds64f(uint32_t a) { float2 v; asm volatile("ld.shared.v2.f32 {%0,%1}, [%2];" : "=f"(v.x), "=f"(v.y) : "r"(a) : "memory"); return v; }
__device__ __forceinline__ uint32_t lds32(uint32_t a) { uint32_t v; asm volatile("ld.shared.u32 %0, [%1];" : "=r"(v) : "r"(a) : "memory"); return v; }
__device__ __forceinline__ uint32_t lds16(uint32_t a) { uint32_t v; asm volatile("ld.shared.u16 %0, [%1];" : "=r"(v) : "r"(a) : "memory"); return v; }
__device__ __forceinline__ void sts16(uint32_t a, uint32_t v) { asm volatile("st.shared.u16 [%0], %1;" ::"r"(a), "r"(v) : "memory"); }
__device__ __forceinline__ void sts32(uint32_t a, uint32_t v) { asm volatile("st.shared.u32 [%0], %1;" ::"r"(a), "r"(v) : "memory"); }
__device__ __forceinline__ void sts32(uint32_t a, float v) { asm volatile("st.shared.f32 [%0], %1;" ::"r"(a), "f"(v) : "memory"); }
__device__ __forceinline__ void sts128(uint32_t a, float x, float y, float z, float w) {
    asm volatile("st.shared.v4.f32 [%0], {%1,%2,%3,%4};" ::"r"(a), "f"(x), "f"(y), "f"(z), "f"(w) : "memory");
}
template <int N> struct IC { static constexpr int value = N; };
__device__ __forceinline__ int opq(int x) { asm volatile("" : "+r"(x)); return x; }
__device__ __forceinline__ uint32_t opq(uint32_t x) { asm volatile("" : "+r"(x)); return x; }
__device__ __forceinline__ uint32_t pin(uint32_t x) { x = opq(x); sts32(SM_MISC + 12, x); return x; }
__device__ __forceinline__ float pin(float x) { sts32(SM_MISC + 12, x); return x; }
template <typename T> __device__ __forceinline__ T* pin(T* p) {
    asm volatile("{\n.reg .b32 lo, hi;\nmov.b64 {lo, hi}, %0;\nst.shared.v2.b32 [%1], {lo, hi};\n}" : "+l"(p) : "r"(SM_MISC + 16) : "memory");
    return p;
}
template <typename T> __device__ __forceinline__ T* opq(T* p) { asm volatile("" : "+l"(p)); return p; }

__device__ __forceinline__ void ln_finish(float s1, float s2, float& mean, float& inv) {
    const float md = s1 * (1.0f / DM);
    const float var = fmaxf(s2 * (1.0f / DM) - md * md, 0.f);
    mean = bfr(md);
    asm("rsqrt.approx.ftz.f32 %0, %1;" : "=f"(inv) : "f"(var + 1e-5f));
}
__device__ __forceinline__ void ln_stats(float& mean, float& inv) {
    const float4 a = lds128f(SM_ST), b = lds128f(SM_ST + 16), c = lds128f(SM_ST + 32), d = lds128f(SM_ST + 48);
    ln_finish(((a.y + a.w) + (b.y + b.w)) + ((c.y + c.w) + (d.y + d.w)), ((a.x + a.z) + (b.x + b.z)) + ((c.x + c.z) + (d.x + d.z)), mean, inv);
}
template <int SK, bool GRAM, typename AddrF>
__device__ __forceinline__ void gemv15(float (&cc)[3][4], float (&gr)[4], uint32_t (&pre)[9][4], AddrF ad, uint32_t px, uint32_t px2) {
    uint32_t x0[4], x1[4];
    lds128(px, x0[0], x0[1], x0[2], x0[3]);
    lds128(px + 64, x1[0], x1[1], x1[2], x1[3]);
    gr[0] = gr[1] = gr[2] = gr[3] = 0.f;
#pragma unroll
    for (int i = 0; i < 3; i++) {
        cc[i][0] = cc[i][1] = cc[i][2] = cc[i][3] = 0.f;
        mma16816v(cc[i], pre[i][0], pre[i][1], pre[i][2], pre[i][3], x0[0], x0[1]);
    }
#pragma unroll
    for (int i = 0; i < 3; i++) ldsm4t(ad(i) + 3 * SK, pre[i]);
    if (GRAM) mma16816v(gr, x0[0], 0u, x0[1], 0u, x0[0], x0[1]);
#pragma unroll
    for (int i = 0; i < 3; i++) mma16816v(cc[i], pre[3 + i][0], pre[3 + i][1], pre[3 + i][2], pre[3 + i][3], x0[2], x0[3]);
#pragma unroll
    for (int i = 0; i < 3; i++) ldsm4t(ad(i) + 4 * SK, pre[3 + i]);
    lds64(px2, x0[0], x0[1]);
    if (GRAM) mma16816v(gr, x0[2], 0u, x0[3], 0u, x0[2], x0[3]);
#pragma unroll
    for (int i = 0; i < 3; i++) mma16816v(cc[i], pre[6 + i][0], pre[6 + i][1], pre[6 + i][2], pre[6 + i][3], x1[0], x1[1]);
    if (GRAM) mma16816v(gr, x1[0], 0u, x1[1], 0u, x1[0], x1[1]);
#pragma unroll
    for (int i = 0; i < 3; i++) mma16816v(cc[i], pre[i][0], pre[i][1], pre[i][2], pre[i][3], x1[2], x1[3]);
    if (GRAM) mma16816v(gr, x1[2], 0u, x1[3], 0u, x1[2], x1[3]);
    if (GRAM) mma16816v(gr, x0[0], 0u, x0[1], 0u, x0[0], x0[1]);
#pragma unroll
    for (int i = 0; i < 3; i++) mma16816v(cc[i], pre[3 + i][0], pre[3 + i][1], pre[3 + i][2], pre[3 + i][3], x0[0], x0[1]);
}
__device__ __forceinline__ void gemv15r(float (&cc)[3][4], float (&gr)[4], const uint32_t (&pre)[9][4], const uint32_t (&ext)[45][4], uint32_t px, uint32_t px2) {
    uint32_t x0[4], x1[4], x2[2];
    lds128(px, x0[0], x0[1], x0[2], x0[3]);
    lds128(px + 64, x1[0], x1[1], x1[2], x1[3]);
    lds64(px2, x2[0], x2[1]);
    gr[0] = gr[1] = gr[2] = gr[3] = 0.f;
#pragma unroll
    for (int ks = 0; ks < 5; ks++) {
        const uint32_t b0 = ks < 2 ? x0[2 * (ks & 1)] : ks < 4 ? x1[2 * (ks & 1)] : x2[0], b1 = ks < 2 ? x0[2 * (ks & 1) + 1] : ks < 4 ? x1[2 * (ks & 1) + 1] : x2[1];
        mma16816v(gr, b0, 0u, b1, 0u, b0, b1);
#pragma unroll
        for (int i = 0; i < 3; i++) {
            if (ks == 0) cc[i][0] = cc[i][1] = cc[i][2] = cc[i][3] = 0.f;
            const uint32_t (&f)[4] = ks < 3 ? pre[ks < 3 ? 3 * ks + i : 0] : ext[ks < 3 ? 0 : 3 * (ks - 3) + i];
            mma16816v(cc[i], f[0], f[1], f[2], f[3], b0, b1);
        }
    }
}

__device__ __forceinline__ void load_ffn(const Maps& maps, int b, uint32_t dst, uint32_t bar) {
    const bool gu = b < NG;
    mbar_expect_tx(bar, gu ? 61440 : 49152);
    tma3d(dst, gu ? (b < NG / 2 ? &maps.w1 : &maps.w3) : &maps.w2, gu ? 48 * (b & (NG / 2 - 1)) : 16 * (b - DN0), 0, 0, bar, POL_EF);
}

__device__ __forceinline__ void load_wo(const Maps& maps, uint32_t dst, int h, int c, uint32_t bar, int nbox) {
#pragma unroll 1
    for (int i = 0; i < nbox; i++) {
        mbar_expect_tx(bar + 8 * i, 12288);
        tma3d(dst + i * 12288, &maps.wo, 0, h * DH, 5 * c + i, bar + 8 * i, POL_EF);
    }
}

__global__ void __launch_bounds__(NT, 1)
decode_kernel(const __grid_constant__ Maps maps, const __nv_bfloat16* __restrict__ x_in, __nv_bfloat16* __restrict__ out) {
    extern __shared__ __align__(1024) unsigned char smem[];
    const int tid = threadIdx.x;
    const int wu = __shfl_sync(0xffffffffu, tid >> 5, 0);
    const int b = blockIdx.x, h = b >> 2, c = b & 3;
    if (smem_u32(smem) != SB) return;

    {
        const int warp = tid >> 5, lane = tid & 31;
        const uint32_t rbar = SM_BAR + warp * 16;
        if (lane == 0) {
            if (warp == 0) {
                mbar_init(QBAR, 1);
                asm volatile("fence.mbarrier_init.release.cluster;" ::: "memory");
                mbar_expect_tx(QBAR, 61440);
                tma5d(SM_Q, &maps.wq, 3 * h, 2 * c, QBAR, POL_EF);
            }
            mbar_init(rbar, 1); mbar_init(rbar + 8, 1); mbar_init(SM_XBAR + warp * 8, 1);
            mbar_init(FBAR + 8 * max(warp - 1, 0), warp == 7 ? 2 : 1);
            asm volatile("fence.mbarrier_init.release.cluster;" ::: "memory");
            if (warp >= 1 && warp < 7) {
                const CUtensorMap* mp = warp == 1 ? &maps.k : warp == 2 ? &maps.v : warp == 3 ? &maps.wo : warp == 4 ? &maps.w1 : warp == 5 ? &maps.w3 : &maps.w2;
                asm volatile("prefetch.tensormap [%0];" ::"l"(mp) : "memory");
            }
        }
        if (tid == 96) sts32(SM_MISC + 8, 0u);
        if (lane < 2) sts32(SM_KX + warp * 96 + 4 * lane, 0u);
        if (tid >= 128 && tid < 148) {
            const float v = f_(tid < 138 ? ONES : 0u);
            sts128(SM_ONE + 16 * (tid - 128), v, v, v, v);
        }
        if (b == 0 && tid == 255) asm volatile("st.relaxed.gpu.global.u32 [%0], %1;" ::"l"(maps.scr->ticket), "r"(0) : "memory");
        if (tid < 52) st_pkt(tid < 48 ? &maps.scr->qx[b * 48 + tid] : reinterpret_cast<uint4*>(&maps.scr->mx[h * 32 + c * 8]) + (tid - 48), 0, 0, 0, 0);
        if (tid >= 64 && tid < 66 && b < 108) st_pkt(&maps.scr->acc[1][(2 * b + tid - 64)], 0, 0, 0, 0);
        __syncthreads();
        if (lane == 0) {
            const int row = ROW0(warp);
            mbar_expect_tx(rbar, TILE);
            tma2d(SM_RING + warp * 2 * TILE, &maps.k, 0, row, rbar, POL_EF);
            mbar_expect_tx(rbar + 8, TILE);
            tma2d(SM_RING + (warp * 2 + 1) * TILE, &maps.k, 0, row + TS, rbar + 8, POL_EF);
        }
    }

    uint32_t kr[45][4];
#define KR(n) kr[(n) >> 2][(n) & 3]
    const float SC = 0.07216878364870322f * 1.4426950408889634f;
    int role = 0;

#pragma unroll 1
    for (int layer = 0; layer < 2; layer++) {
        const uint32_t tag = layer + 1, tbit = layer ^ 1;
        uint2 xv = make_uint2(0u, 0u);
        uint32_t qo;
        {
            const int tl = opq(tid), warp = tl >> 5, lane = tl & 31, g = lane >> 2, t = lane & 3, mat = lane >> 3, r8 = lane & 7;
            const int kh = warp >> 2, mg = warp & 3;
            const uint32_t aq = SM_Q + kh * TILE + ((mat >> 1) * 8 + r8) * 128 + (((2 * mg + (mat & 1)) ^ r8) << 4);
            if (layer == 0 && tl < 160) xv = reinterpret_cast<const uint2*>(x_in)[tl];
            mbar_wait(QBAR, 0);
            uint32_t pre[9][4];
#pragma unroll
            for (int n = 0; n < 9; n++) ldsm4t(aq + (n % 3) * 2048 + (n / 3) * 2 * TILE, pre[n]);
            if (layer == 1) {
                __syncthreads();
                delay(role >= DN0 + NDN ? 1500 : 0);
                if (role >= DN0 && role < DN0 + NDN) {
                    if (wu < 6) tile_load(SM_Q + wu * TILE, &maps.k, ROW0(wu) + 5 * TS, SM_XBAR + wu * 8);
                } else if (wu == 7) {
#pragma unroll 1
                    for (int w = 0; w < 6; w++) tile_load(SM_Q + w * TILE, &maps.k, ROW0(w) + 5 * TS, SM_XBAR + w * 8);
                }
            }
            const uint32_t pm = opq(g == 1 ? SM_ONE : SM_XS + 160 * (2 * c + kh) + 16 * t);
            const uint32_t pm2 = opq(pm + 128 - (g == 1 ? 0 : 8 * t));
            const uint32_t dq = opq(SM_R + 768 * kh + 4 * (16 * mg + g));
            qo = pin(16u * (b * 48 + (tl & 63) + (tl >= 64 ? NCTA * 48 : 0)));
            if (tl < 160) {
                const uint32_t xa0 = opq(SM_XS + 4 * xpos(2 * tl));
                const bool xl = tl % 20 < 16;
                if (layer == 1) {
                    const uint4* px = opq(&maps.scr->ay[tl]);
                    uint4 v;
                    int it = 0;
                    bool more;
                    do { v = ld_pkt(px); more = ++it < SPIN_CAP; } while (!__all_sync(0xffffffffu, (v.y & v.w) == 1) && more);
                    xv = make_uint2(v.x, v.z);
                }
                sts32(xa0, xv.x);
                if (xl) sts32(xa0 + 16, xv.y); else sts32(xa0 + 8, xv.y);
            }
            __syncthreads();
            float cc[3][4], gr[4];
            gemv15<2 * TILE, false>(cc, gr, pre, [&](int i) { return aq + i * 2048; }, pm, pm2);
            if (t == 0) {
#pragma unroll
                for (int i = 0; i < 3; i++) { sts32(dq + 256 * i, cc[i][0]); sts32(dq + 256 * i + 32, cc[i][2]); }
                if (layer == 0) {
#pragma unroll
                    for (int i = 0; i < 3; i++) { sts32(dq + 256 * i + 1536, cc[i][1]); sts32(dq + 256 * i + 1568, cc[i][3]); }
                }
            }
        }
        {
            const int tl = opq(tid), j = tl & 63;
            const bool snd = j < 48 && (tl < 64 || (tl < 128 && layer == 0));
            const uint32_t fa = opq(SM_R + 16 * tl + (tl >= 64 ? 512 : 0));
            uint4* pq = reinterpret_cast<uint4*>(reinterpret_cast<char*>(maps.scr->qx) + qo);
            __syncthreads();
            if (snd) {
                const float4 u = lds128f(fa), v = lds128f(fa + 768);
                st_pktf(pq, u.x + v.x, u.y + v.y, u.z + v.z, u.w + v.w, tbit);
            }
            if (layer == 1 && wu >= 5) {
                delay(300);
                if (wu >= 6) tile_load(SM_Q + wu * TILE, &maps.k, ROW0(wu) + 5 * TS, SM_XBAR + wu * 8);
                else if (role < NG && elect_one()) {
                    mbar_expect_tx(WBAR + 32, 12288);
                    tma3d(SM_Q + 4 * 12288, &maps.wo, 0, h * DH, 5 * c + 4, WBAR + 32, POL_EF);
                }
            }
            if (layer == 1 && tl >= 192 && tl < 194 && b < 108) st_pkt(&maps.scr->acc[0][(2 * b + tl - 192)], 0, 0, 0, 0);
        }

        float sc0 = -INFINITY, sc1 = -INFINITY, sc2 = 0.f, sc3 = 0.f, mw;
        uint32_t pk0, pk1;
        float acc[3][4];
        {
            const uint32_t ring = SM_RING + wu * 2 * TILE, rb = SM_BAR + wu * 16;
            const uint32_t xtile = SM_Q + wu * TILE, xb = SM_XBAR + wu * 8;
            const int row0 = ROW0(wu);
            const uint32_t bt = SM_B + wu * TILE;
            auto issue1 = [&](int n, bool vph = false) {
                const CUtensorMap* mp = n < 8 ? &maps.k : &maps.v;
                const int row = row0 + ((n + (n >= 8 ? 2 : 0)) & 7) * TS;
                if (vph && wu < L1R && n == 12 - (wu & 1)) {
                    tile_load_l1(ring + (n & 1) * TILE, maps.vp, row, rb + (n & 1) * 8, opq(tid) & 31);
                    return;
                }
                const int k = vph || n >= 6 ? n & 1 : n >= 3 ? n - 3 : n;
                tile_load(k == 2 ? bt : ring + k * TILE, mp, row, k == 2 ? xb : rb + k * 8);
                if ((((wu & 1) ? RT_ODD : RT_EVEN) >> n) & 1) tile_keep(n < 8 ? &maps.ks : &maps.vs, row);
            };
            auto refill1 = [&](int s, bool vph = false) { issue1(s + 2, vph); };
#define K_OFF(i) ((uint32_t)((3 * ((g >> 1) + 4 * (g & 1)) + ((i) >> 1)) * 128 + ((t ^ ((3 * ((g >> 1) + 4 * (g & 1)) + ((i) >> 1)) & 7) ^ (((i) & 1) << 2)) << 4)))
#define V_OFF(i) ((uint32_t)((6 * t + (i)) * 128 + ((g ^ ((6 * t + (i)) & 7)) << 4)))
#define LANE_IDS const int tl = opq(tid), lane = tl & 31, g = lane >> 2, t = lane & 3; (void)tl; (void)lane; (void)g; (void)t;
            const uint32_t kx = SM_KX + wu * 96;
#pragma unroll 1
            for (int s = layer ? 5 : 0; s < 5 + layer; s++) {
                if (s < 5) {
                    LANE_IDS
                    const int k = s >= 3 ? s - 3 : s;
                    mbar_wait(k == 2 ? xb : rb + k * 8, s >= 3);
                    refill1(s);
                    const uint32_t tile = k == 2 ? bt : ring + k * TILE;
                    uint32_t mx = 0u, mn = 0xffffffffu, mn2 = 0xffffffffu;
#pragma unroll
                    for (int q = 0; q < 12; q++) {
                        uint32_t a0, a1, a2, a3;
                        lds128(tile + K_OFF(q % 6) + (q / 6) * 3072, a0, a1, a2, a3);
                        a0 &= 0x7fff7fffu; a1 &= 0x7fff7fffu; a2 &= 0x7fff7fffu; a3 &= 0x7fff7fffu;
                        mx = __vimax3_u16x2(__vimax3_u16x2(mx, a0, a1), a2, a3);
                        mn = __viaddmin_u16x2(a0, 0xffffffffu, __viaddmin_u16x2(a1, 0xffffffffu, mn));
                        mn2 = __viaddmin_u16x2(a2, 0xffffffffu, __viaddmin_u16x2(a3, 0xffffffffu, mn2));
                    }
                    mn = __vminu2(mn, mn2);
                    const uint32_t emax = __reduce_max_sync(0xffffffffu, max(mx & 0xffffu, mx >> 16)) >> 7;
                    const uint32_t base = (max(emax, 16u) - 15u) << 7, lim = base + 0x7fu;
                    bool raw = emax < 80u || emax > 190u;
                    uint32_t fl = __ballot_sync(0xffffffffu, min(mn & 0xffffu, mn >> 16) < lim);
                    if (!raw && fl) {
                        const uint32_t n0 = lds32(kx);
                        __syncwarp();
#pragma unroll 1
                        for (; fl; fl &= fl - 1) {
                            const int g = (__ffs(fl) - 1) >> 2, t = (__ffs(fl) - 1) & 3, q = min(lane, 23) >> 1, i = q >= 6 ? q - 6 : q;
                            const uint32_t a = tile + K_OFF(i) + (q >= 6 ? 3072 : 0) + 8 * (lane & 1);
                            uint32_t w0, w1;
                            lds64(a, w0, w1);
#pragma unroll 1
                            for (int e = 0; e < 4; e++) {
                                const uint32_t x = __funnelshift_r(w0, w1, 16 * e) & 0xffffu;
                                if (e == 1) w0 = w1;
                                if ((x & 0x7fffu) - 1u < lim && lane < 24) {
                                    uint32_t n;
                                    asm volatile("atom.shared.add.u32 %0, [%1], 1;" : "=r"(n) : "r"(kx) : "memory");
                                    if (n < NEXC) sts32(kx + 32 + 4 * n, x | (2 * ((2 * t + (e >> 1)) * 12 + 2 * i + (lane & 1)) + (e & 1)) << 16 | (16 * s + (q >= 6 ? 8 : 0) + g) << 24);
                                    sts16(a + 2 * e, 0u);
                                }
                            }
                        }
                        __syncwarp();
                        raw = lds32(kx) > NEXC;
                        __syncwarp();
                        if (raw && lane == 0) sts32(kx, n0);
                    }
                    if (lane == 0) {
                        sts32(kx + 8 + 4 * s, (base + (31u << 7)) << 16);
                        if (raw) sts32(kx + 4, lds32(kx + 4) | 1u << s);
                    }
                    const uint32_t b2 = (0x10000u - base) * 0x10001u;
                    auto pack = [&](auto S) {
                        constexpr int n0 = 36 * decltype(S)::value;
#pragma unroll
                        for (int q = 0; q < 12; q++) {
                            uint32_t a0, a1, a2, a3;
                            lds128(tile + K_OFF(q % 6) + (q / 6) * 3072, a0, a1, a2, a3);
                            a0 = __viaddmax_s16x2(a0 & 0x7fff7fffu, b2, 0u) | (a0 & 0x80008000u); a1 = __viaddmax_s16x2(a1 & 0x7fff7fffu, b2, 0u) | (a1 & 0x80008000u);
                            a2 = __viaddmax_s16x2(a2 & 0x7fff7fffu, b2, 0u) | (a2 & 0x80008000u); a3 = __viaddmax_s16x2(a3 & 0x7fff7fffu, b2, 0u) | (a3 & 0x80008000u);
                            KR(n0 + 3 * q) = __byte_perm(a0, a1, 0x6420);
                            KR(n0 + 3 * q + 1) = __byte_perm(a2, a3, 0x6420);
                            const uint32_t ho = __byte_perm(a2, a3, 0x7531);
                            KR(n0 + 3 * q + 2) = __byte_perm(a0, a1, 0x7531) | __funnelshift_r(ho, ho, 4);
                        }
                    };
                    switch (s) {
                        case 0: pack(IC<0>()); break;
                        case 1: pack(IC<1>()); break;
                        case 2: pack(IC<2>()); break;
                        case 3: pack(IC<3>()); break;
                        default: pack(IC<4>()); break;
                    }
                    __syncwarp();
                }
                if (wu < 2 && (s == 3 || layer)) {
                    const int tc = min(opq(tid), 47);
                    const uint4* pq = opq(&maps.scr->qx[h * 4 * 48 + tc]);
                    uint4 v[4];
                    int it = 0;
                    bool more = true;
#pragma unroll
                    for (int k = 0; k < 4; k++) v[k] = ld_pkt(pq + 48 * k);
                    if (layer == 0) {
                        uint4 u[4];
                        do {
#pragma unroll
                            for (int k = 0; k < 4; k++) u[k] = ld_pkt(pq + NCTA * 48 + 48 * k);
                            more = ++it < SPIN_CAP;
                        } while (!__all_sync(0xffffffffu, u[0].w & u[1].w & u[2].w & u[3].w & 1) && more);
                        sts128(SM_CS + 16 * tc, (f_(u[0].x) + f_(u[1].x)) + (f_(u[2].x) + f_(u[3].x)), (f_(u[0].y) + f_(u[1].y)) + (f_(u[2].y) + f_(u[3].y)),
                               (f_(u[0].z) + f_(u[1].z)) + (f_(u[2].z) + f_(u[3].z)), (f_(u[0].w) + f_(u[1].w)) + (f_(u[2].w) + f_(u[3].w)));
                    }
                    float mean, inv;
                    {
                        const int lane = opq(tid) & 31;
                        uint32_t xw[10];
                        lds128(SM_XS + 16 * lane, xw[0], xw[1], xw[2], xw[3]);
                        lds128(SM_XS + 512 + 16 * lane, xw[4], xw[5], xw[6], xw[7]);
                        lds64(SM_XS + 1024 + 8 * lane, xw[8], xw[9]);
                        float s1 = 0.f, s2 = 0.f, s3 = 0.f, s4 = 0.f;
#pragma unroll
                        for (int i = 0; i < 10; i++) { const float e0 = bf_lo(xw[i]), e1 = bf_hi(xw[i]); s1 += e0; s3 += e1; s2 = fmaf(e0, e0, s2); s4 = fmaf(e1, e1, s4); }
                        s1 += s3; s2 += s4;
                        const bool lo = lane < 16;
                        float sv = (lo ? s1 : s2) + __shfl_xor_sync(0xffffffffu, lo ? s2 : s1, 16);
#pragma unroll
                        for (int o = 8; o > 0; o >>= 1) sv += __shfl_xor_sync(0xffffffffu, sv, o);
                        const float so = __shfl_xor_sync(0xffffffffu, sv, 16);
                        ln_finish(lo ? sv : so, lo ? so : sv, mean, inv);
                    }
                    const float4 cs = lds128f(SM_CS + 16 * tc);
                    mean *= -inv;
                    const float m0 = pin(mean * cs.x), m1 = pin(mean * cs.y), m2 = pin(mean * cs.z), m3 = pin(mean * cs.w);
                    const int w = 2 * tc;
                    const uint32_t qd = pin(SM_QS + 4 * (((w >> 2) & 3) * 24 + 2 * (w >> 4) + ((w >> 1) & 1)));
                    while (__any_sync(0xffffffffu, ((v[0].w ^ tbit) | (v[1].w ^ tbit) | (v[2].w ^ tbit) | (v[3].w ^ tbit)) & 1) && more) {
#pragma unroll
                        for (int k = 0; k < 4; k++) v[k] = ld_pkt(pq + 48 * k);
                        more = ++it < SPIN_CAP;
                    }
                    const float q0 = fmaf(inv, (f_(v[0].x) + f_(v[1].x)) + (f_(v[2].x) + f_(v[3].x)), m0), q1 = fmaf(inv, (f_(v[0].y) + f_(v[1].y)) + (f_(v[2].y) + f_(v[3].y)), m1);
                    const float q2 = fmaf(inv, (f_(v[0].z) + f_(v[1].z)) + (f_(v[2].z) + f_(v[3].z)), m2), q3 = fmaf(inv, (f_(v[0].w) + f_(v[1].w)) + (f_(v[2].w) + f_(v[3].w)), m3);
                    sts32(qd, pack2(q0, q1));
                    sts32(qd + 48, pack2(q2, q3));
                    __syncwarp();
                    if (elect_one()) asm volatile("mbarrier.arrive.shared::cta.b64 _, [%0];" ::"r"(QRDY) : "memory");
                }
            }
            uint32_t qa, ka[6];
            {
                LANE_IDS
                qa = opq(SM_QS + (2 * t + (g & 1)) * 48);
#pragma unroll
                for (int i = 0; i < 6; i++) ka[i] = opq(xtile + K_OFF(i));
            }
            mbar_wait(QRDY, layer);
            {
                uint32_t qf[12];
#pragma unroll
                for (int i = 0; i < 3; i++) lds128(qa + 16 * i, qf[4 * i], qf[4 * i + 1], qf[4 * i + 2], qf[4 * i + 3]);
                const int t = opq(tid) & 3;
                uint32_t qs[12];
#pragma unroll
                for (int i = 0; i < 12; i++) qs[i] = mul2(qf[i], 0x6f806f80u);
                auto kr_scores = [&](auto TAU, float& sa, float& sb) {
                    constexpr int tau = decltype(TAU)::value;
                    float cc[2][4] = {{0.f, 0.f, 0.f, 0.f}, {0.f, 0.f, 0.f, 0.f}};
#pragma unroll
                    for (int n = 0; n < 12; n++) {
                        const int q = (n & 1) * 6 + (n >> 1), i = n >> 1;
                        const uint32_t l0 = KR(36 * tau + 3 * q), l1 = KR(36 * tau + 3 * q + 1), hh = KR(36 * tau + 3 * q + 2);
                        const uint32_t h0 = hh & 0x87878787u, h1 = __funnelshift_l(hh, hh, 4) & 0x87878787u;
                        mma16816(cc[n & 1], __byte_perm(l0, h0, 0x5140), __byte_perm(l0, h0, 0x7362), __byte_perm(l1, h1, 0x5140), __byte_perm(l1, h1, 0x7362), qs[2 * i], qs[2 * i + 1]);
                    }
                    if (t == (tau & 3)) { sa = cc[0][0] + cc[0][3]; sb = cc[1][0] + cc[1][3]; }
                };
                auto stage_v = [&](auto S) {
                    constexpr int s = decltype(S)::value;
                    const int lane = opq(tid) & 31, g = lane >> 2, t = lane & 3;
#pragma unroll
                    for (int i = 0; i < 6; i++) {
                        const uint32_t a = ring + s * TILE + V_OFF(i);
                        lds128(a, kr[12 * s + i][0], kr[12 * s + i][1], kr[12 * s + i][2], kr[12 * s + i][3]);
                        lds128(a + 3072, kr[12 * s + 6 + i][0], kr[12 * s + 6 + i][1], kr[12 * s + 6 + i][2], kr[12 * s + 6 + i][3]);
                    }
                    __syncwarp();
                    tile_load(ring + s * TILE, s ? &maps.v : &maps.k, row0 + (s ? 2 : 7) * TS, rb + s * 8);
                };
                if (layer == 1) {
                    mbar_wait(xb, 0);
                    float cA[4] = {0.f, 0.f, 0.f, 0.f}, cB[4] = {0.f, 0.f, 0.f, 0.f};
                    uint32_t f[6][4];
#pragma unroll
                    for (int i = 0; i < 3; i++) {
                        lds128(ka[i], f[2 * i][0], f[2 * i][1], f[2 * i][2], f[2 * i][3]);
                        lds128(ka[i] + 3072, f[2 * i + 1][0], f[2 * i + 1][1], f[2 * i + 1][2], f[2 * i + 1][3]);
                    }
#pragma unroll
                    for (int i = 0; i < 3; i++) {
                        mma16816v(cA, f[2 * i][0], f[2 * i][1], f[2 * i][2], f[2 * i][3], qf[2 * i], qf[2 * i + 1]);
                        lds128(ka[3 + i], f[2 * i][0], f[2 * i][1], f[2 * i][2], f[2 * i][3]);
                        mma16816v(cB, f[2 * i + 1][0], f[2 * i + 1][1], f[2 * i + 1][2], f[2 * i + 1][3], qf[2 * i], qf[2 * i + 1]);
                        lds128(ka[3 + i] + 3072, f[2 * i + 1][0], f[2 * i + 1][1], f[2 * i + 1][2], f[2 * i + 1][3]);
                    }
                    __syncwarp();
                    tile_load(xtile, &maps.k, row0 + 6 * TS, xb);
#pragma unroll
                    for (int i = 0; i < 3; i++) {
                        mma16816v(cA, f[2 * i][0], f[2 * i][1], f[2 * i][2], f[2 * i][3], qf[6 + 2 * i], qf[7 + 2 * i]);
                        mma16816v(cB, f[2 * i + 1][0], f[2 * i + 1][1], f[2 * i + 1][2], f[2 * i + 1][3], qf[6 + 2 * i], qf[7 + 2 * i]);
                    }
                    sc2 = cA[0] + cA[3]; sc3 = cB[0] + cB[3];
                }
                kr_scores(IC<0>(), sc0, sc1);
                kr_scores(IC<1>(), sc0, sc1);
                if (layer == 1) stage_v(IC<0>());
                kr_scores(IC<2>(), sc0, sc1);
                if (layer == 1) stage_v(IC<1>());
                kr_scores(IC<3>(), sc0, sc1);
                kr_scores(IC<4>(), sc2, sc3);
                {
                    LANE_IDS
                    const float sa = f_(lds32(kx + 8 + 4 * t)), sb = t == 0 ? f_(lds32(kx + 24)) : 1.0f;
                    const int nx = (int)lds32(kx);
                    uint32_t rm = lds32(kx + 4), qm = 0u;
#pragma unroll
                    for (int i = 0; i < 6; i++) qm = __vimax3_u16x2(qm, qs[2 * i] & 0x7fff7fffu, qs[2 * i + 1] & 0x7fff7fffu);
                    if (__any_sync(0xffffffffu, max(qm & 0xffffu, qm >> 16) >= 0x7f80u)) rm = 31;
                    sc0 *= sa; sc1 *= sa; sc2 *= sb; sc3 *= sb;
#pragma unroll 1
                    for (int n = 0; n < nx; n++) {
                        const uint32_t w = lds32(kx + 32 + 4 * n);
                        const int tau = w >> 28;
                        const float d = bf_lo(lds16(SM_QS + ((w >> 15) & 0x1fe))) * bf_lo(w);
                        if (((w >> 24) & 7) == g && (tau & 3) == t) {
                            const int k = ((w >> 27) & 1) + (tau >> 2) * 2;
                            if (k == 0) sc0 += d; else if (k == 1) sc1 += d; else if (k == 2) sc2 += d; else sc3 += d;
                        }
                    }
#pragma unroll 1
                    for (; rm; rm &= rm - 1) {
                        const int tau = __ffs(rm) - 1;
#pragma unroll 1
                        for (int hf = 0; hf < 2; hf++) {
                            const char* gp = static_cast<const char*>(maps.kp) + (size_t)(row0 + tau * TS) * 128 + (8 * hf + (g >> 1) + 4 * (g & 1)) * 384 + 16 * t;
                            float cA[4] = {0.f, 0.f, 0.f, 0.f};
#pragma unroll
                            for (int i = 0; i < 6; i++) {
                                const uint4 a = __ldcg(reinterpret_cast<const uint4*>(gp + 64 * i));
                                mma16816(cA, a.x, a.y, a.z, a.w, qf[2 * i], qf[2 * i + 1]);
                            }
                            if ((tau & 3) == t) {
                                const int k = hf + (tau >> 2) * 2;
                                const float d = cA[0] + cA[3];
                                if (k == 0) sc0 = d; else if (k == 1) sc1 = d; else if (k == 2) sc2 = d; else sc3 = d;
                            }
                        }
                    }
                }
                if (layer == 0) {
                    LANE_IDS
#pragma unroll 1
                    for (int s = 5; s < 8; s++) {
                        mbar_wait(s == 5 ? xb : rb + (s & 1) * 8, s == 5);
                        const uint32_t tile = s == 5 ? bt : ring + (s & 1) * TILE;
                        float cA[4] = {0.f, 0.f, 0.f, 0.f}, cB[4] = {0.f, 0.f, 0.f, 0.f};
#pragma unroll
                        for (int i = 0; i < 6; i++) {
                            uint32_t a0, a1, a2, a3;
                            lds128(tile + K_OFF(i), a0, a1, a2, a3);
                            mma16816(cA, a0, a1, a2, a3, qf[2 * i], qf[2 * i + 1]);
                            lds128(tile + K_OFF(i) + 3072, a0, a1, a2, a3);
                            mma16816(cB, a0, a1, a2, a3, qf[2 * i], qf[2 * i + 1]);
                        }
                        if (t == (s & 3)) { sc2 = cA[0] + cA[3]; sc3 = cB[0] + cB[3]; }
                        __syncwarp();
                        refill1(s);
                    }
                } else {
                    LANE_IDS
#pragma unroll 1
                    for (int i = 2; i < 4; i++) {
                        const uint32_t tile = i == 3 ? ring : xtile, tb = i == 3 ? rb : xb;
                        mbar_wait(tb, 1);
#pragma unroll
                        for (int k = 0; k < 6; k++) {
                            const uint32_t a = tile + K_OFF(k);
                            lds128(a, kr[24 + k][0], kr[24 + k][1], kr[24 + k][2], kr[24 + k][3]);
                            lds128(a + 3072, kr[24 + 6 + k][0], kr[24 + 6 + k][1], kr[24 + 6 + k][2], kr[24 + 6 + k][3]);
                        }
                        float cA[4] = {0.f, 0.f, 0.f, 0.f}, cB[4] = {0.f, 0.f, 0.f, 0.f}, cC[4] = {0.f, 0.f, 0.f, 0.f}, cD[4] = {0.f, 0.f, 0.f, 0.f};
#pragma unroll
                        for (int k = 0; k < 3; k++) {
                            mma16816(cA, kr[24 + k][0], kr[24 + k][1], kr[24 + k][2], kr[24 + k][3], qf[2 * k], qf[2 * k + 1]);
                            mma16816(cB, kr[24 + 6 + k][0], kr[24 + 6 + k][1], kr[24 + 6 + k][2], kr[24 + 6 + k][3], qf[2 * k], qf[2 * k + 1]);
                            mma16816(cC, kr[24 + 3 + k][0], kr[24 + 3 + k][1], kr[24 + 3 + k][2], kr[24 + 3 + k][3], qf[6 + 2 * k], qf[7 + 2 * k]);
                            mma16816(cD, kr[24 + 9 + k][0], kr[24 + 9 + k][1], kr[24 + 9 + k][2], kr[24 + 9 + k][3], qf[6 + 2 * k], qf[7 + 2 * k]);
                        }
                        __syncwarp();
                        tile_load(tile, &maps.v, row0 + (i + 1) * TS, tb);
                        if (t == i) { sc2 = (cA[0] + cC[0]) + (cA[3] + cC[3]); sc3 = (cB[0] + cD[0]) + (cB[3] + cD[3]); }
                    }
                }
            }
            {
                const uint32_t mk = __reduce_max_sync(0xffffffffu, f2key(fmaxf(fmaxf(sc0, sc1), fmaxf(sc2, sc3))));
                if ((opq(tid) & 31) == 0) st_pkt2(&maps.scr->mx[h * 32 + c * 8 + wu], mk, tag);
                mw = key2f(mk);
            }
            pk0 = pack2(ex2((sc0 - mw) * SC), ex2((sc1 - mw) * SC));
            pk1 = pack2(ex2((sc2 - mw) * SC), ex2((sc3 - mw) * SC));
            sc2 = (bf_lo(pk0) + bf_hi(pk0)) + (bf_lo(pk1) + bf_hi(pk1));
#pragma unroll
            for (int o = 16; o > 0; o >>= 1) sc2 += __shfl_xor_sync(0xffffffffu, sc2, o);
#pragma unroll
            for (int s = 0; s < 3; s++) { acc[s][0] = acc[s][1] = acc[s][2] = acc[s][3] = 0.f; }
            auto head_ld = [&](int lane) { const uint2 mv = ld_pkt2(&maps.scr->mx[h * 32 + lane]); sc0 = f_(mv.x); sc1 = f_(mv.y); };
            auto head_factor = [&](int lane) {
                int it = 0;
                while (!__all_sync(0xffffffffu, __float_as_uint(sc1) == tag) && ++it < SPIN_CAP) head_ld(lane);
                sc3 = ex2((mw - key2f(__reduce_max_sync(0xffffffffu, __float_as_uint(sc0)))) * SC);
            };
#define P_CONSTS \
                const uint32_t sel0 = g == 0 ? 0x4410u : (g == 1 ? 0x1044u : 0x4444u); \
                const uint32_t sel1 = g == 2 ? 0x4410u : (g == 3 ? 0x1044u : 0x4444u); \
                const int src00 = 4 * (t < 2 ? 4 * t : 4 * (t - 2) + 1);
#define P_FRAGS(tau) \
                const uint32_t pk = ((tau) & 4) ? pk1 : pk0; \
                const uint32_t w0 = __shfl_sync(0xffffffffu, pk, src00 + ((tau) & 3)); \
                const uint32_t w1 = __shfl_sync(0xffffffffu, pk, src00 + ((tau) & 3) + 8); \
                uint32_t pb[4][2]; \
                _Pragma("unroll") for (int j = 0; j < 4; j++) { \
                    const uint32_t src = ((j & 1) ? w1 : w0) >> ((j >> 1) * 16); \
                    pb[j][0] = __byte_perm(src, 0, sel0); pb[j][1] = __byte_perm(src, 0, sel1); \
                }
            if (layer == 0) {
#pragma unroll 1
                for (int s = 8; s < 16; s++) {
                    LANE_IDS
                    P_CONSTS
                    if (s == 14) {
                        uint4* p = nullptr;
                        if (tl < 48) p = &maps.scr->qx[b * 48 + tl];
                        else if (tl < 98) p = &maps.scr->cx[b * 56 + tl - 48];
                        else if (tl < 145) {}
                        else if (tl >= 160) { if (tl < 208) p = &maps.scr->qc[b * 48 + tl - 160]; }
                        else if (b < NG) { if (tl < 153) p = &maps.scr->ah[b * 8 + tl - 145]; }
                        else if (b < DN0 + NDN && tl < 149) p = &maps.scr->ay[(b - DN0) * 4 + tl - 145];
                        if (p) st_pkt(p, 0, 0, 0, tl < 48);
                    }
                    if (s == 13) head_ld(lane);
                    P_FRAGS((s + 2) & 7)
                    mbar_wait(rb + (s & 1) * 8, ((s >> 1) + 1) & 1);
                    const uint32_t tile = ring + (s & 1) * TILE;
#pragma unroll
                    for (int j = 0; j < 4; j++) {
#pragma unroll
                        for (int u = 0; u < 3; u++) {
                            uint32_t a0, a1, a2, a3;
                            lds128(tile + (j >> 1) * 3072 + V_OFF(3 * (j & 1) + u), a0, a1, a2, a3);
                            mma16816(acc[u], a0, a1, a2, a3, pb[j][0], pb[j][1]);
                        }
                    }
                    __syncwarp();
                    if (s < 14) refill1(s, true);
                    if (s == 13) head_factor(lane);
                    if (s == 15 && elect_one()) {
                        uint32_t n;
                        asm volatile("atom.shared.add.u32 %0, [%1], 1;" : "=r"(n) : "r"(SM_MISC + 8) : "memory");
                        if (n == 7) load_wo(maps, SM_B, h, c, WBAR, 5);
                    }
                }
            } else {
                LANE_IDS
                P_CONSTS
#pragma unroll
                for (int s = 0; s < 2; s++) {
                    P_FRAGS(s)
#pragma unroll
                    for (int j = 0; j < 4; j++) {
#pragma unroll
                        for (int u = 0; u < 3; u++) {
                            const int k = 6 * (j >> 1) + 3 * (j & 1) + u;
                            mma16816(acc[u], kr[12 * s + k][0], kr[12 * s + k][1], kr[12 * s + k][2], kr[12 * s + k][3], pb[j][0], pb[j][1]);
                        }
                    }
                }
#pragma unroll 1
                for (int i = 4; i < 10; i++) {
                    const int sl = i == 5 ? 0 : (i == 6 || i == 8 ? 1 : 2);
                    const uint32_t tile = sl ? ring + (sl - 1) * TILE : xtile, tb = sl ? rb + (sl - 1) * 8 : xb;
                    if (i == 8) head_ld(lane);
                    if (i == 9) head_factor(lane);
                    P_FRAGS(i - 2)
                    mbar_wait(tb, (0x310 >> i) & 1);
#pragma unroll
                    for (int k = 0; k < 6; k++) {
                        const uint32_t a = tile + V_OFF(k);
                        lds128(a, kr[24 + k][0], kr[24 + k][1], kr[24 + k][2], kr[24 + k][3]);
                        lds128(a + 3072, kr[24 + 6 + k][0], kr[24 + 6 + k][1], kr[24 + 6 + k][2], kr[24 + 6 + k][3]);
                    }
#pragma unroll
                    for (int j = 0; j < 4; j++) {
#pragma unroll
                        for (int u = 0; u < 3; u++) {
                            const int k = 6 * (j >> 1) + 3 * (j & 1) + u;
                            mma16816(acc[u], kr[24 + k][0], kr[24 + k][1], kr[24 + k][2], kr[24 + k][3], pb[j][0], pb[j][1]);
                        }
                    }
                    __syncwarp();
                    if (wu < L1R && i == 6 - 2 * (wu & 1)) tile_load_l1(tile, maps.vp, row0 + (6 - (wu & 1)) * TS, tb, lane);
                    else if (i == 4 || i == 6 || i == 7) tile_load(tile, &maps.v, row0 + (i == 4 ? 5 : i) * TS, tb);
                    if (i == 7 && role < DN0 + NDN && elect_one()) {
                        uint32_t n;
                        asm volatile("atom.shared.add.u32 %0, [%1], 1;" : "=r"(n) : "r"(SM_MISC + 8) : "memory");
                        if (n == 15) load_wo(maps, SM_Q, h, c, WBAR, 4);
                    }
                }
            }
#undef P_FRAGS
#undef P_CONSTS
#undef LANE_IDS
#undef K_OFF
#undef V_OFF
        }

        uint32_t ticket = 0;
        uint4* pr;
        {
            const int tl = opq(tid), warp = tl >> 5, lane = tl & 31, g = lane >> 2, t = lane & 3, mat = lane >> 3, r8 = lane & 7;
            {
                const uint32_t d = SM_R + 4 * (warp * 196 + 8 * g + 4 * t);
                if (t < 2) {
#pragma unroll
                    for (int u = 0; u < 3; u++) sts128(d + 256 * u, acc[u][0] * sc3, acc[u][1] * sc3, acc[u][2] * sc3, acc[u][3] * sc3);
                }
                if (lane == 0) sts128(d + 768, sc2 * sc3, 0.f, 0.f, 0.f);
            }
            const int tc = min(tl, 48);
            uint4* pc = opq(&maps.scr->cx[h * 4 * 56 + tc]);
            uint4* po = opq(pc + c * 56);
            const uint32_t fa = opq(SM_R + 16 * tc);
            __syncthreads();
            const int kg = warp >> 1, mg = warp & 1;
            const bool wo2 = layer && role < DN0 + NDN;
            const bool wo4 = layer && role < NG;
            uint32_t aw, oa, ob0, dw;
            uint32_t* tk;
            auto addrs = [&]() {
                aw = pin((wo2 ? SM_Q : SM_B) + (48 * kg + (mat >> 1) * 8 + r8) * 64 + (((2 * mg + (mat & 1)) ^ ((r8 >> 1) & 3)) << 4));
                oa = pin(SM_OS + 96 * kg + 8 * t);
                ob0 = pin(oa + 8 * t);
                dw = pin(SM_R + 4 * (4 * (16 * mg + g) + kg));
                tk = opq(maps.scr->ticket + 0);
                pr = pin(&maps.scr->acc[layer][(54 * c + min(tl, 53))]);
            };
            uint32_t a[2][3][4];
            auto preload = [&]() {
#pragma unroll
                for (int i = 0; i < 2; i++) {
                    mbar_wait(WBAR + 8 * i, wo2);
#pragma unroll
                    for (int ks = 0; ks < 3; ks++) ldsm4t(aw + i * 12288 + ks * 1024, a[i][ks]);
                }
            };
            if (wu < 2) {
                if (tl < 49) {
                    float4 v[8];
#pragma unroll
                    for (int w = 0; w < 8; w++) v[w] = lds128f(fa + w * 784);
                    st_pktf(po, ((v[0].x + v[1].x) + (v[2].x + v[3].x)) + ((v[4].x + v[5].x) + (v[6].x + v[7].x)),
                            ((v[0].y + v[1].y) + (v[2].y + v[3].y)) + ((v[4].y + v[5].y) + (v[6].y + v[7].y)),
                            ((v[0].z + v[1].z) + (v[2].z + v[3].z)) + ((v[4].z + v[5].z) + (v[6].z + v[7].z)),
                            ((v[0].w + v[1].w) + (v[2].w + v[3].w)) + ((v[4].w + v[5].w) + (v[6].w + v[7].w)), tbit);
                }
                __syncwarp();
                uint4 v[4];
#pragma unroll
                for (int k = 0; k < 4; k++) v[k] = ld_pkt(pc + k * 56);
                asm volatile("bar.arrive 1, 256;" ::: "memory");
                addrs();
                const int w = 2 * tc, k3 = w / 24, r = w - 24 * k3;
                const uint32_t d0 = pin(tl < 48 ? SM_OS + 4 * (24 * k3 + (r < 16 ? 4 * (r & 3) + (r >> 2) : 16 + 2 * (r & 3) + ((r >> 2) & 1))) : SM_MISC);
                const uint32_t d1 = pin(tl < 48 ? d0 + (r < 16 ? 16 : 8) : SM_MISC + 12);
                int it = 0;
                bool more = true;
                while (__any_sync(0xffffffffu, ((v[0].w ^ tbit) | (v[1].w ^ tbit) | (v[2].w ^ tbit) | (v[3].w ^ tbit)) & 1) && more) {
#pragma unroll
                    for (int k = 0; k < 4; k++) v[k] = ld_pkt(pc + k * 56);
                    more = ++it < SPIN_CAP;
                }
                const float o0 = (f_(v[0].x) + f_(v[1].x)) + (f_(v[2].x) + f_(v[3].x));
                const uint32_t w0 = pack2(o0, (f_(v[0].y) + f_(v[1].y)) + (f_(v[2].y) + f_(v[3].y)));
                sts32(d1, pack2((f_(v[0].z) + f_(v[1].z)) + (f_(v[2].z) + f_(v[3].z)), (f_(v[0].w) + f_(v[1].w)) + (f_(v[2].w) + f_(v[3].w))));
                sts32(d0, tl < 48 ? w0 : __float_as_uint(o0));
                asm volatile("bar.arrive 2, 256;" ::: "memory");
                preload();
                asm volatile("bar.sync 3, 64;" ::: "memory");
            } else {
                addrs();
                asm volatile("bar.sync 1, 256;" ::: "memory");
                preload();
                asm volatile("bar.sync 2, 256;" ::: "memory");
            }
            uint32_t ob[6];
            lds128(ob0, ob[0], ob[1], ob[2], ob[3]);
            lds64(oa + 64, ob[4], ob[5]);
            if (tl == 224 && layer == 0)
                asm volatile("atom.relaxed.gpu.global.inc.u32 %0, [%1], 0x7fffffff;" : "=r"(ticket) : "l"(tk) : "memory");
            auto put = [&](int i, const float (&cc)[4]) { if (t == 0) { sts32(dw + 512 * i, cc[0]); sts32(dw + 512 * i + 128, cc[2]); } };
            {
                float c0[4] = {0.f, 0.f, 0.f, 0.f}, c1[4] = {0.f, 0.f, 0.f, 0.f}, c2[4] = {0.f, 0.f, 0.f, 0.f}, c3[4] = {0.f, 0.f, 0.f, 0.f};
                mbar_wait(WBAR + 16, wo2);
#pragma unroll
                for (int ks = 0; ks < 3; ks++) {
                    mma16816v(c0, a[0][ks][0], a[0][ks][1], a[0][ks][2], a[0][ks][3], ob[2 * ks], ob[2 * ks + 1]);
                    mma16816v(c1, a[1][ks][0], a[1][ks][1], a[1][ks][2], a[1][ks][3], ob[2 * ks], ob[2 * ks + 1]);
                    if (ks == 0) mbar_wait(WBAR + 24, wo2);
                    if (ks == 1) mbar_wait(WBAR + 32, wo4);
#pragma unroll
                    for (int i = 0; i < 2; i++) ldsm4t(aw + (2 + i) * 12288 + ks * 1024, a[i][ks]);
                }
                const uint32_t aw4 = aw + (wo2 && !wo4 ? SM_B - SM_Q : 0) + 4 * 12288;
#pragma unroll
                for (int ks = 0; ks < 3; ks++) {
                    mma16816v(c2, a[0][ks][0], a[0][ks][1], a[0][ks][2], a[0][ks][3], ob[2 * ks], ob[2 * ks + 1]);
                    mma16816v(c3, a[1][ks][0], a[1][ks][1], a[1][ks][2], a[1][ks][3], ob[2 * ks], ob[2 * ks + 1]);
                    if (ks == 0) { ldsm4t(aw4, a[0][0]); ldsm4t(aw4 + 1024, a[1][0]); put(0, c0); put(1, c1); }
                    if (ks == 1) ldsm4t(aw4 + 2048, a[0][1]);
                }
                float c4[4] = {0.f, 0.f, 0.f, 0.f}, c5[4] = {0.f, 0.f, 0.f, 0.f};
                mma16816v(c4, a[0][0][0], a[0][0][1], a[0][0][2], a[0][0][3], ob[0], ob[1]);
                mma16816v(c5, a[1][0][0], a[1][0][1], a[1][0][2], a[1][0][3], ob[2], ob[3]);
                mma16816v(c4, a[0][1][0], a[0][1][1], a[0][1][2], a[0][1][3], ob[4], ob[5]);
                put(2, c2); put(3, c3);
                c4[0] += c5[0]; c4[2] += c5[2];
                put(4, c4);
            }
        }
        {
            const int tl = opq(tid);
            const uint32_t fa = opq(SM_R + 48 * tl);
            const float il = rcp(f_(lds32(SM_MISC)));
            __syncthreads();
            if (tl < 54) {
                const float4 v0 = lds128f(fa), v1 = lds128f(fa + 16), v2 = lds128f(fa + 32);
                const float y0 = il * ((v0.x + v0.y) + (v0.z + v0.w)), y1 = il * ((v1.x + v1.y) + (v1.z + v1.w)), y2 = il * ((v2.x + v2.y) + (v2.z + v2.w));
                red_pkt(pr, y0, tl == 53 ? 0.f : y1, tl == 53 ? 0.f : y2);
            }
            if (tl == 224 && layer == 0) {
                sts32(SM_MISC + 4, ticket);
                if (ticket < NG) load_ffn(maps, ticket, SM_B, FBAR);
            }
        }
        __syncthreads();
        if (layer == 0) role = __shfl_sync(0xffffffffu, (int)lds32(SM_MISC + 4), 0);
        const uint32_t DONE32 = 0x42000000u;
        if (role < NG) {
            const int tl = opq(tid), warp = tl >> 5, lane = tl & 31, g = lane >> 2, t = lane & 3, mat = lane >> 3, r8 = lane & 7;
            const uint32_t ag = SM_B + (80 * warp + (mat >> 1) * 8 + r8) * 96 + (((mat & 1) ^ (r8 >> 2)) << 4);
            constexpr int GI = 32, GK = 16 * 96;
            const bool on = (g & 1) == (t >> 1), isx = (on && g < 2) || g == 4;
            const uint32_t pm = opq(isx ? SM_XS + 160 * warp + 16 * t : (on || g == 5 ? SM_ONE : SM_ZERO)), pm2 = opq(pm + 128 - (isx ? 8 * t : 0));
            const uint32_t dg = opq(SM_R + 4 * (2 * (warp * 48 + g) + t));
            const uint32_t ho = pin(16u * (role * 8 + 4 * warp + ((lane * 11) >> 5)));
            const uint32_t fa = pin(SM_R + 8 * (24 * warp + 2 * min(lane, 11)));
            uint32_t pre[9][4];
            {
                bool hx = wu == 7;
                int it = 0;
                const uint4* px = opq(&maps.scr->acc[layer][min(tl, 215)]);
                const int cq = tl / 54, r = tl - 54 * cq, k0 = min(160 * cq + 3 * r, DM - 1);
                const uint32_t w0 = SM_XS + 4 * xpos(k0 >> 1), w1 = SM_XS + 4 * xpos(min((k0 >> 1) + 1, DM / 2 - 1));
                const bool two = tl < 216 && r != 53;
                const uint32_t e0 = opq(tl < 216 ? w0 + 2 * (k0 & 1) : SM_MISC + 12);
                const uint32_t e1 = opq(two ? ((k0 & 1) ? w1 : w0 + 2) : SM_MISC + 12), e2 = opq(two ? w1 + 2 * (k0 & 1) : SM_MISC + 12);
                const uint32_t x01 = opq(lds16(e0) | (lds16(e1) << 16)), x2 = lds16(e2);
                auto take_x = [&](const uint4 v) {
                    if (__all_sync(0xffffffffu, v.w == DONE32)) {
                        hx = true;
                        const uint32_t y01 = add2(x01, pack2(f_(v.x), f_(v.y))), y2 = add2(x2, pack2(f_(v.z), 0.f));
                        sts16(e0, y01); sts16(e1, y01 >> 16); sts16(e2, y2);
                    }
                };
                while (!mbar_test(FBAR, 0) && ++it < SPIN_CAP) { if (!hx) take_x(ld_pkt(px)); }
                uint4 v = make_uint4(0u, 0u, 0u, 0u);
                if (!hx) v = ld_pkt(px);
#pragma unroll
                for (int n = 0; n < 9; n++) ldsm4t(ag + (n % 3) * GI + (n / 3) * GK, pre[n]);
                if (layer) {
#pragma unroll
                    for (int n = 9; n < 15; n++) ldsm4t(ag + (n % 3) * GI + (n / 3) * GK, kr[n - 9]);
                }
                if (!hx) {
                    bool more = true;
                    while (!__all_sync(0xffffffffu, v.w == DONE32) && more) { v = ld_pkt(px); more = ++it < SPIN_CAP; }
                    const uint32_t y01 = add2(x01, pack2(f_(v.x), f_(v.y))), y2 = add2(x2, pack2(f_(v.z), 0.f));
                    sts16(e0, y01); sts16(e1, y01 >> 16); sts16(e2, y2);
                }
            }
            __syncthreads();
            {
                float cc[3][4], gr[4];
                if (layer) gemv15r(cc, gr, pre, kr, pm, pm2);
                else gemv15<GK, true>(cc, gr, pre, [&](int i) { return ag + i * GI; }, pm, pm2);
                if (t < 2) {
#pragma unroll
                    for (int i = 0; i < 3; i++) { sts32(dg + 128 * i, cc[i][0] + cc[i][3]); sts32(dg + 128 * i + 64, cc[i][1] + cc[i][2]); }
                }
                if ((lane | 4) == 22) sts32(SM_ST + 8 * warp + (g & 1) * 4, gr[0]);
            }
            uint4* ph = reinterpret_cast<uint4*>(reinterpret_cast<char*>(maps.scr->ah) + ho);
            const bool snd = (0x249 >> lane) & 1;
            __syncthreads();
            if (wu < 2) {
                float mean, inv;
                float4 v[8];
#pragma unroll
                for (int w = 0; w < 8; w++) v[w] = lds128f(fa + w * 384);
                ln_stats(mean, inv);
                const float ga = inv * ((((v[0].x + v[1].x) + (v[2].x + v[3].x)) + ((v[4].x + v[5].x) + (v[6].x + v[7].x))) -
                                        mean * (((v[0].y + v[1].y) + (v[2].y + v[3].y)) + ((v[4].y + v[5].y) + (v[6].y + v[7].y))));
                const float gb = inv * ((((v[0].z + v[1].z) + (v[2].z + v[3].z)) + ((v[4].z + v[5].z) + (v[6].z + v[7].z))) -
                                        mean * (((v[0].w + v[1].w) + (v[2].w + v[3].w)) + ((v[4].w + v[5].w) + (v[6].w + v[7].w))));
                uint32_t wd = pack2(ga, gb);
                if (role < NG / 2) {
                    const float g0 = bf_lo(wd), g1 = bf_hi(wd);
                    wd = pack2(g0 * rcp(1.0f + ex2(-1.4426950408889634f * g0)), g1 * rcp(1.0f + ex2(-1.4426950408889634f * g1)));
                }
                const uint32_t wa = __shfl_down_sync(0xffffffffu, wd, 1), wb = __shfl_down_sync(0xffffffffu, wd, 2);
                if (snd) st_pkt(ph, wd, wa, wb, tag);
            }
            __syncthreads();
        } else if (role < DN0 + NDN) {
            const int j = role - DN0;
            const int tl = opq(tid), warp = tl >> 5, lane = tl & 31, g = lane >> 2, t = lane & 3, mat = lane >> 3, r8 = lane & 7;
            float xr0 = 0.f, xr1 = 0.f;
            if (wu == 0) {
                const int col = 16 * j + (lane & 15), cc = col / 160, r = col - 160 * cc, e = r % 3;
                const uint4* px = &maps.scr->acc[layer][(54 * cc + r / 3)];
                const float x0 = bf_lo(lds16(SM_XS + 4 * xpos(col >> 1) + 2 * (col & 1)));
                uint4 v;
                int it = 0;
                bool ld = layer == 0;
                do {
                    v = ld_pkt(px);
                    if (ld && f_(__shfl_sync(0xffffffffu, v.w, 0)) >= (float)DNTH) { ld = false; if (lane == 0) load_ffn(maps, role, SM_B, FBAR); }
                } while (!__all_sync(0xffffffffu, v.w == DONE32) && ++it < SPIN_CAP);
                if (ld && lane == 0) load_ffn(maps, role, SM_B, FBAR);
                const float xres = bfr(x0 + bfr(f_(e == 0 ? v.x : (e == 1 ? v.y : v.z))));
                xr0 = __shfl_sync(0xffffffffu, xres, 2 * (lane & 7));
                xr1 = __shfl_sync(0xffffffffu, xres, 2 * (lane & 7) + 1);
            }
            const uint32_t ad = SM_B + (192 * warp + (mat >> 1) * 8 + r8) * 32 + (((mat & 1) ^ (r8 >> 2)) << 4);
            const uint32_t hs = SM_R + 384 * warp, hb = opq(hs + 16 * t), dd = opq(SM_R + 3072 + 4 * (warp * 16 + g));
            uint32_t pre[NPRE][4];
            uint32_t pos[3];
#pragma unroll
            for (int i = 0; i < 3; i++) { const int w = 3 * lane + i; pos[i] = opq(hs + 4 * ((w & ~15) + 4 * (w & 3) + ((w >> 2) & 1) + ((w >> 2) & 2))); }
            const uint4* ph = opq(&maps.scr->ah[tl]);
            const uint32_t fa = opq(SM_R + 3072 + 8 * (lane & 7));
            uint2* py = opq(reinterpret_cast<uint2*>(maps.scr->ay) + 8 * j + (lane & 7));
            uint32_t* po = opq(reinterpret_cast<uint32_t*>(out) + 8 * j + (lane & 7));
            mbar_wait(FBAR, 0);
#pragma unroll
            for (int n = 0; n < NPRE; n++) ldsm4t(ad + n * 512, pre[n]);
            {
                uint4 v, u;
                int it = 0;
                bool more;
                do { v = ld_pkt(ph); u = ld_pkt(ph + 256); more = ++it < SPIN_CAP; }
                while (!__all_sync(0xffffffffu, v.w == tag && u.w == tag) && more);
                sts32(pos[0], mul2(v.x, u.x)); sts32(pos[1], mul2(v.y, u.y)); sts32(pos[2], mul2(v.z, u.z));
            }
            __syncwarp();
            {
                float cc[4][4];
                uint32_t hv[3][4];
#pragma unroll
                for (int jj = 0; jj < 3; jj++) lds128(hb + 64 * jj, hv[jj][0], hv[jj][1], hv[jj][2], hv[jj][3]);
#pragma unroll
                for (int n = 0; n < 12; n++) {
                    const int s = n < NPRE ? n : n - NPRE;
                    if (n < 4) cc[n][0] = cc[n][1] = cc[n][2] = cc[n][3] = 0.f;
                    mma16816v(cc[n & 3], pre[s][0], pre[s][1], pre[s][2], pre[s][3], hv[(n >> 1) % 3][2 * (n & 1)], hv[(n >> 1) % 3][2 * (n & 1) + 1]);
                    if (n + NPRE < 12) ldsm4t(ad + (n + NPRE) * 512, pre[n]);
                    if ((n & 1) && n < 6) lds128(hb + 64 * ((n >> 1) + 3), hv[n >> 1][0], hv[n >> 1][1], hv[n >> 1][2], hv[n >> 1][3]);
                }
                if (t == 0) { sts32(dd, (cc[0][0] + cc[1][0]) + (cc[2][0] + cc[3][0])); sts32(dd + 32, (cc[0][2] + cc[1][2]) + (cc[2][2] + cc[3][2])); }
            }
            __syncthreads();
            if (tl < 8) {
                float2 v[8];
#pragma unroll
                for (int w = 0; w < 8; w++) v[w] = lds64f(fa + 64 * w);
                const uint32_t y = pack2(((v[0].x + v[1].x) + (v[2].x + v[3].x)) + ((v[4].x + v[5].x) + (v[6].x + v[7].x)),
                                         ((v[0].y + v[1].y) + (v[2].y + v[3].y)) + ((v[4].y + v[5].y) + (v[6].y + v[7].y)));
                const uint32_t wd = pack2(xr0 + bf_lo(y), xr1 + bf_hi(y));
                if (layer) asm volatile("st.global.u32 [%0], %1;" ::"l"(po), "r"(wd) : "memory");
                st_pkt2(py, wd, tag);
            }
            __syncthreads();
        }
    }
}

typedef CUresult (*EncodeFn)(CUtensorMap*, CUtensorMapDataType, cuuint32_t, void*, const cuuint64_t*, const cuuint64_t*, const cuuint32_t*,
                             const cuuint32_t*, CUtensorMapInterleave, CUtensorMapSwizzle, CUtensorMapL2promotion, CUtensorMapFloatOOBfill);

void make_map(EncodeFn enc, CUtensorMap* m, const void* base, int rank, uint64_t d0, uint64_t d1, uint64_t d2, uint64_t s1, uint64_t s2,
              uint32_t b0, uint32_t b1, uint32_t b2, CUtensorMapSwizzle sw, CUtensorMapL2promotion pr = CU_TENSOR_MAP_L2_PROMOTION_NONE) {
    cuuint64_t dims[3] = {d0, d1, d2};
    cuuint64_t strides[2] = {s1, s2};
    cuuint32_t box[3] = {b0, b1, b2};
    cuuint32_t es[3] = {1, 1, 1};
    enc(m, CU_TENSOR_MAP_DATA_TYPE_BFLOAT16, rank, const_cast<void*>(base), dims, strides, box, es, CU_TENSOR_MAP_INTERLEAVE_NONE, sw,
        pr, CU_TENSOR_MAP_FLOAT_OOB_FILL_NONE);
}

}

extern "C" void kernel_launch(void* const* d_in, const int* in_sizes, int n_in, void* d_out, int out_size) {
    (void)in_sizes; (void)n_in; (void)out_size;
    static EncodeFn enc = nullptr;
    static Scratch* scr = nullptr;
    if (!enc) {
        void* fn = nullptr;
        cudaDriverEntryPointQueryResult qr;
        cudaGetDriverEntryPoint("cuTensorMapEncodeTiled", &fn, cudaEnableDefault, &qr);
        enc = reinterpret_cast<EncodeFn>(fn);
        cudaGetSymbolAddress(reinterpret_cast<void**>(&scr), g_scr);
        cudaFuncSetAttribute(decode_kernel, cudaFuncAttributeMaxDynamicSharedMemorySize, SM_TOTAL);
    }
    Maps maps;
    make_map(enc, &maps.k, d_in[1], 2, 64, (uint64_t)NH * SK * 3, 1, 128, 0, 64, 48, 1, CU_TENSOR_MAP_SWIZZLE_128B);
    make_map(enc, &maps.v, d_in[2], 2, 64, (uint64_t)NH * SK * 3, 1, 128, 0, 64, 48, 1, CU_TENSOR_MAP_SWIZZLE_128B);
    {
        cuuint64_t dims[5] = {64, 16, NH * DH / 64, DM / 80, 5};
        cuuint64_t strides[4] = {NH * DH * 2, 128, 80 * NH * DH * 2, 16 * NH * DH * 2};
        cuuint32_t box[5] = {64, 16, 3, 2, 5};
        cuuint32_t es[5] = {1, 1, 1, 1, 1};
        enc(&maps.wq, CU_TENSOR_MAP_DATA_TYPE_BFLOAT16, 5, d_in[3], dims, strides, box, es, CU_TENSOR_MAP_INTERLEAVE_NONE, CU_TENSOR_MAP_SWIZZLE_128B,
            CU_TENSOR_MAP_L2_PROMOTION_NONE, CU_TENSOR_MAP_FLOAT_OOB_FILL_NONE);
    }
    make_map(enc, &maps.wo, d_in[4], 3, 32, NH * DH, DM / 32, DM * 2, 64, 32, 192, 1, CU_TENSOR_MAP_SWIZZLE_64B);
    constexpr int GW = 48;
    make_map(enc, &maps.w1, d_in[6], 3, FF, 160, 4, FF * 2, 160 * FF * 2, GW, 160, 4, CU_TENSOR_MAP_SWIZZLE_NONE);
    make_map(enc, &maps.w3, d_in[7], 3, FF, 160, 4, FF * 2, 160 * FF * 2, GW, 160, 4, CU_TENSOR_MAP_SWIZZLE_NONE);
    make_map(enc, &maps.w2, d_in[8], 3, DM, 256, 6, DM * 2, 256 * DM * 2, 16, 256, 6, CU_TENSOR_MAP_SWIZZLE_32B);
    make_map(enc, &maps.ks, d_in[1], 2, 64, (uint64_t)NH * SK * 3, 1, 128, 0, 16, 48, 1, CU_TENSOR_MAP_SWIZZLE_NONE);
    make_map(enc, &maps.vs, d_in[2], 2, 64, (uint64_t)NH * SK * 3, 1, 128, 0, 16, 48, 1, CU_TENSOR_MAP_SWIZZLE_NONE);
    maps.kp = d_in[1];
    maps.vp = d_in[2];
    maps.scr = scr;
    decode_kernel<<<NCTA, NT, SM_TOTAL, cudaStreamPerThread>>>(maps, (const __nv_bfloat16*)d_in[0], (__nv_bfloat16*)d_out);
}
```

```cpp
#include <cuda_runtime.h>
#include <cuda_bf16.h>
#include <cuda.h>
#include <stdint.h>
#include <math.h>

#define HD 300
#define LTD 300
namespace {

constexpr int DM = 640;
constexpr int NH = 32;
constexpr int DH = 192;
constexpr int SK = 32768;
constexpr int WIN = 4096;
constexpr int FF = 1536;
constexpr int NCTA = 128;
constexpr int NT = 256;
constexpr int TILE = 6144;
constexpr int TS = 48;
constexpr int NG = 64;
constexpr int DN0 = 64;
constexpr int NDN = 40;

constexpr uint32_t SB = 1024;
constexpr uint32_t SM_RING = SB;
constexpr uint32_t SM_B = SM_RING + 8 * 2 * TILE;
constexpr uint32_t SM_Q = SM_B + 61440;
constexpr uint32_t SM_XS = SM_Q + 61440;
constexpr uint32_t SM_R = SM_XS + 1280;
constexpr uint32_t SM_ST = SM_R + 4096;
constexpr uint32_t SM_QS = SM_R + 6272;
constexpr uint32_t SM_OS = SM_QS + 384;
constexpr uint32_t SM_CS = SM_OS + 384;
constexpr uint32_t SM_BAR = SM_CS + 768;
constexpr uint32_t SM_XBAR = SM_BAR + 24 * 8;
constexpr uint32_t SM_MISC = SM_XBAR + 8 * 8;
constexpr uint32_t SM_ONE = SM_MISC + 32;
constexpr uint32_t SM_ZERO = SM_ONE + 160;
constexpr uint32_t SM_KX = SM_ZERO + 160;
constexpr uint32_t SM_TOTAL = SM_KX + 8 * 96 - SB;
constexpr int NEXC = 16;
static_assert(SM_TOTAL <= 232448, "shared memory");
constexpr uint32_t QBAR = SM_BAR + 16 * 8, FBAR = QBAR + 8, WBAR = QBAR + 16, QRDY = QBAR + 56;

constexpr unsigned long long POL_EF = 0x12F0000000000000ull;
constexpr unsigned long long POL_EN = 0x1000000000000000ull;

constexpr int L1R = 3;
constexpr int DNTH = 23;
constexpr int NPRE = 6;
constexpr int SPIN_CAP = 1 << 19;
constexpr uint32_t ONES = 0x3F803F80u;
#define ROW0(w) ((h * SK + (SK - WIN) + c * 1024 + (w) * 128) * 3)

struct Scratch {
    uint4 qx[NCTA * 48];
    uint4 qc[NCTA * 48];
    uint4 cx[NCTA * 56];
    uint4 acc[2][256];
    uint4 ay[256];
    uint4 pad0[256];
    uint4 ah[NG * 8];
    uint2 mx[NH * 32];
    uint32_t ticket[32];
};
__device__ __align__(4096) Scratch g_scr;
struct Maps { CUtensorMap k, v, wq, wo, w1, w3, w2, ks, vs, kh; const void *kp, *vp; Scratch* scr; uint32_t rt[8]; };

__device__ __forceinline__ uint32_t smem_u32(const void* p) { return (uint32_t)__cvta_generic_to_shared(p); }
__device__ __forceinline__ void mbar_init(uint32_t bar, uint32_t cnt) {
    asm volatile("mbarrier.init.shared::cta.b64 [%0], %1;" ::"r"(bar), "r"(cnt) : "memory");
}
__device__ __forceinline__ void mbar_expect_tx(uint32_t bar, uint32_t bytes) {
    asm volatile("mbarrier.arrive.expect_tx.shared::cta.b64 _, [%0], %1;" ::"r"(bar), "r"(bytes) : "memory");
}
__device__ __forceinline__ bool mbar_test(uint32_t bar, uint32_t parity) {
    uint32_t done;
    asm volatile("{\n.reg .pred p;\nmbarrier.try_wait.parity.shared::cta.b64 p, [%1], %2;\nselp.u32 %0, 1, 0, p;\n}"
                 : "=r"(done) : "r"(bar), "r"(parity) : "memory");
    return done;
}
__device__ __forceinline__ void mbar_wait(uint32_t bar, uint32_t parity) {
    asm volatile("{\n.reg .pred p;\n.reg .u32 n;\nmov.u32 n, 0;\n"
                 "W: mbarrier.try_wait.parity.shared::cta.b64 p, [%0], %1;\n@p bra D;\n"
                 "add.u32 n, n, 1;\nsetp.lt.u32 p, n, %2;\n@p bra W;\nD:\n}" ::"r"(bar), "r"(parity), "n"(SPIN_CAP) : "memory");
}
__device__ __forceinline__ void tma2d(uint32_t dst, const CUtensorMap* map, int c0, int c1, uint32_t bar, unsigned long long pol) {
    asm volatile("cp.async.bulk.tensor.2d.shared::cluster.global.mbarrier::complete_tx::bytes.L2::cache_hint [%0], [%1, {%3, %4}], [%2], %5;"
                 ::"r"(dst), "l"(map), "r"(bar), "r"(c0), "r"(c1), "l"(pol) : "memory");
}
__device__ __forceinline__ void tma3d(uint32_t dst, const CUtensorMap* map, int c0, int c1, int c2, uint32_t bar, unsigned long long pol) {
    asm volatile("cp.async.bulk.tensor.3d.shared::cluster.global.mbarrier::complete_tx::bytes.L2::cache_hint [%0], [%1, {%3, %4, %5}], [%2], %6;"
                 ::"r"(dst), "l"(map), "r"(bar), "r"(c0), "r"(c1), "r"(c2), "l"(pol) : "memory");
}
__device__ __forceinline__ void tma5d(uint32_t dst, const CUtensorMap* map, int c2, int c3, uint32_t bar, unsigned long long pol) {
    asm volatile("cp.async.bulk.tensor.5d.shared::cluster.global.mbarrier::complete_tx::bytes.L2::cache_hint [%0], [%1, {0, 0, %3, %4, 0}], [%2], %5;"
                 ::"r"(dst), "l"(map), "r"(bar), "r"(c2), "r"(c3), "l"(pol) : "memory");
}
__device__ __forceinline__ void tile_load(uint32_t dst, const CUtensorMap* map, int row, uint32_t bar) {
    asm volatile("{\n.reg .pred p;\nelect.sync _|p, 0xffffffff;\n"
                 "@p mbarrier.arrive.expect_tx.shared::cta.b64 _, [%2], 6144;\n"
                 "@p cp.async.bulk.tensor.2d.shared::cluster.global.mbarrier::complete_tx::bytes.L2::cache_hint [%0], [%1, {0, %3}], [%2], %4;\n}"
                 ::"r"(dst), "l"(map), "r"(bar), "r"(row), "l"(POL_EF) : "memory");
}
__device__ __forceinline__ void half_load(uint32_t dst, const CUtensorMap* map, int row, uint32_t bar, bool first) {
    if (first) asm volatile("{\n.reg .pred p;\nelect.sync _|p, 0xffffffff;\n@p mbarrier.arrive.expect_tx.shared::cta.b64 _, [%0], 6144;\n}" ::"r"(bar) : "memory");
    asm volatile("{\n.reg .pred p;\nelect.sync _|p, 0xffffffff;\n"
                 "@p cp.async.bulk.tensor.2d.shared::cluster.global.mbarrier::complete_tx::bytes.L2::cache_hint [%0], [%1, {0, %3}], [%2], %4;\n}"
                 ::"r"(dst), "l"(map), "r"(bar), "r"(row), "l"(POL_EF) : "memory");
}
__device__ __forceinline__ void tile_keep(const CUtensorMap* map, int row) {
    asm volatile("{\n.reg .pred p;\nelect.sync _|p, 0xffffffff;\n"
                 "@p cp.async.bulk.prefetch.tensor.2d.L2.global.L2::cache_hint [%0, {0, %1}], %2;\n}"
                 ::"l"(map), "r"(row), "l"(POL_EN) : "memory");
}
__device__ __forceinline__ void tile_load_l1(uint32_t dst, const void* base, int row, uint32_t bar, int lane) {
    const char* g = static_cast<const char*>(base) + (size_t)row * 128 + lane * 16;
    const uint32_t s0 = dst + (lane >> 3) * 128 + (((lane & 7) ^ (lane >> 3)) << 4), s1 = s0 ^ 64;
#pragma unroll
    for (int k = 0; k < 12; k++)
        asm volatile("cp.async.ca.shared.global.L2::cache_hint [%0], [%1], 16, %2;" ::"r"(((k & 1) ? s1 : s0) + k * 512), "l"(g + k * 512), "l"(POL_EF) : "memory");
    asm volatile("cp.async.mbarrier.arrive.shared::cta.b64 [%0];" ::"r"(bar) : "memory");
    __syncwarp();
    if (lane == 0) asm volatile("mbarrier.arrive.shared::cta.b64 _, [%0];" ::"r"(bar) : "memory");
}
__device__ __forceinline__ bool elect_one() {
    uint32_t p;
    asm volatile("{\n.reg .pred p;\nelect.sync _|p, 0xffffffff;\nselp.u32 %0, 1, 0, p;\n}" : "=r"(p));
    return p;
}
__device__ __forceinline__ void delay(uint32_t clocks) {
    uint32_t t0, t1;
    asm volatile("mov.u32 %0, %%clock;" : "=r"(t0));
    do asm volatile("mov.u32 %0, %%clock;" : "=r"(t1)); while (t1 - t0 < clocks);
}
__device__ __forceinline__ void lds128(uint32_t addr, uint32_t& a, uint32_t& b, uint32_t& c, uint32_t& d) {
    asm volatile("ld.shared.v4.u32 {%0,%1,%2,%3}, [%4];" : "=r"(a), "=r"(b), "=r"(c), "=r"(d) : "r"(addr) : "memory");
}
__device__ __forceinline__ void lds64(uint32_t addr, uint32_t& a, uint32_t& b) {
    asm volatile("ld.shared.v2.u32 {%0,%1}, [%2];" : "=r"(a), "=r"(b) : "r"(addr) : "memory");
}
__device__ __forceinline__ void ldsm4t(uint32_t addr, uint32_t (&a)[4]) {
    asm volatile("ldmatrix.sync.aligned.m8n8.x4.trans.shared.b16 {%0,%1,%2,%3}, [%4];" : "=r"(a[0]), "=r"(a[1]), "=r"(a[2]), "=r"(a[3]) : "r"(addr) : "memory");
}
__device__ __forceinline__ void mma16816(float (&c)[4], uint32_t a0, uint32_t a1, uint32_t a2, uint32_t a3, uint32_t b0, uint32_t b1) {
    asm("mma.sync.aligned.m16n8k16.row.col.f32.bf16.bf16.f32 {%0,%1,%2,%3}, {%4,%5,%6,%7}, {%8,%9}, {%0,%1,%2,%3};"
        : "+f"(c[0]), "+f"(c[1]), "+f"(c[2]), "+f"(c[3]) : "r"(a0), "r"(a1), "r"(a2), "r"(a3), "r"(b0), "r"(b1));
}
__device__ __forceinline__ void mma16816v(float (&c)[4], uint32_t a0, uint32_t a1, uint32_t a2, uint32_t a3, uint32_t b0, uint32_t b1) {
    asm volatile("mma.sync.aligned.m16n8k16.row.col.f32.bf16.bf16.f32 {%0,%1,%2,%3}, {%4,%5,%6,%7}, {%8,%9}, {%0,%1,%2,%3};"
        : "+f"(c[0]), "+f"(c[1]), "+f"(c[2]), "+f"(c[3]) : "r"(a0), "r"(a1), "r"(a2), "r"(a3), "r"(b0), "r"(b1));
}
__device__ __forceinline__ int xpos(int w) {
    const int seg = w / 40, r = w - 40 * seg;
    return 40 * seg + (r < 32 ? (r & 16) + 4 * (r & 3) + ((r >> 2) & 3) : 32 + 2 * (r & 3) + ((r >> 2) & 1));
}
__device__ __forceinline__ void st_pkt(uint4* p, uint32_t a, uint32_t b, uint32_t c, uint32_t d) {
    asm volatile("{\n.reg .b128 t;\n.reg .b64 lo, hi;\nmov.b64 lo, {%1,%2};\nmov.b64 hi, {%3,%4};\nmov.b128 t, {lo,hi};\nst.relaxed.gpu.global.b128 [%0], t;\n}"
                 ::"l"(p), "r"(a), "r"(b), "r"(c), "r"(d) : "memory");
}
__device__ __forceinline__ void st_pktf(uint4* p, float a, float b, float c, float d, uint32_t bit) {
    st_pkt(p, __float_as_uint(a), __float_as_uint(b), __float_as_uint(c), (__float_as_uint(d) & ~1u) | bit);
}
__device__ __forceinline__ void red_pkt(uint4* p, float a, float b, float c) {
    asm volatile("red.relaxed.gpu.global.add.v4.f32 [%0], {%1,%2,%3,%4};" ::"l"(p), "f"(a), "f"(b), "f"(c), "f"(1.0f) : "memory");
}
__device__ __forceinline__ uint4 ld_pkt(const uint4* p) {
    uint4 v;
    asm volatile("{\n.reg .b128 t;\n.reg .b64 lo, hi;\nld.relaxed.gpu.global.b128 t, [%4];\nmov.b128 {lo,hi}, t;\nmov.b64 {%0,%1}, lo;\nmov.b64 {%2,%3}, hi;\n}"
                 : "=r"(v.x), "=r"(v.y), "=r"(v.z), "=r"(v.w) : "l"(p) : "memory");
    return v;
}
__device__ __forceinline__ uint2 ld_pkt2(const uint2* p) {
    unsigned long long v;
    asm volatile("ld.relaxed.gpu.global.b64 %0, [%1];" : "=l"(v) : "l"(p) : "memory");
    return make_uint2((uint32_t)v, (uint32_t)(v >> 32));
}
__device__ __forceinline__ void st_pkt2(uint2* p, uint32_t a, uint32_t b) {
    asm volatile("st.relaxed.gpu.global.b64 [%0], %1;" ::"l"(p), "l"((unsigned long long)a | ((unsigned long long)b << 32)) : "memory");
}
__device__ __forceinline__ float ex2(float x) { float y; asm("ex2.approx.ftz.f32 %0, %1;" : "=f"(y) : "f"(x)); return y; }
__device__ __forceinline__ float rcp(float x) { float y; asm("rcp.approx.ftz.f32 %0, %1;" : "=f"(y) : "f"(x)); return y; }
__device__ __forceinline__ uint32_t pack2(float lo, float hi) {
    uint32_t r; asm("cvt.rn.bf16x2.f32 %0, %1, %2;" : "=r"(r) : "f"(hi), "f"(lo)); return r;
}
__device__ __forceinline__ float bf_lo(uint32_t w) { return __uint_as_float(w << 16); }
__device__ __forceinline__ float bf_hi(uint32_t w) { return __uint_as_float(w & 0xffff0000u); }
__device__ __forceinline__ float bfr(float x) { return bf_lo(pack2(x, 0.f)); }
__device__ __forceinline__ float f_(uint32_t u) { return __uint_as_float(u); }

__device__ __forceinline__ uint32_t add2(uint32_t a, uint32_t b) { uint32_t r; asm("add.rn.bf16x2 %0, %1, %2;" : "=r"(r) : "r"(a), "r"(b)); return r; }
__device__ __forceinline__ uint32_t mul2(uint32_t a, uint32_t b) { uint32_t r; asm("mul.rn.bf16x2 %0, %1, %2;" : "=r"(r) : "r"(a), "r"(b)); return r; }
__device__ __forceinline__ uint32_t f2key(float f) { const uint32_t u = __float_as_uint(f); return u ^ ((uint32_t)((int)u >> 31) | 0x80000000u); }
__device__ __forceinline__ float key2f(uint32_t k) { return __uint_as_float(k ^ ((uint32_t)((int)~k >> 31) | 0x80000000u)); }
__device__ __forceinline__ float4 lds128f(uint32_t a) {
    float4 v; asm volatile("ld.shared.v4.f32 {%0,%1,%2,%3}, [%4];" : "=f"(v.x), "=f"(v.y), "=f"(v.z), "=f"(v.w) : "r"(a) : "memory"); return v;
}
__device__ __forceinline__ float2 lds64f(uint32_t a) { float2 v; asm volatile("ld.shared.v2.f32 {%0,%1}, [%2];" : "=f"(v.x), "=f"(v.y) : "r"(a) : "memory"); return v; }
__device__ __forceinline__ uint32_t lds32(uint32_t a) { uint32_t v; asm volatile("ld.shared.u32 %0, [%1];" : "=r"(v) : "r"(a) : "memory"); return v; }
__device__ __forceinline__ uint32_t lds16(uint32_t a) { uint32_t v; asm volatile("ld.shared.u16 %0, [%1];" : "=r"(v) : "r"(a) : "memory"); return v; }
__device__ __forceinline__ void sts16(uint32_t a, uint32_t v) { asm volatile("st.shared.u16 [%0], %1;" ::"r"(a), "r"(v) : "memory"); }
__device__ __forceinline__ void sts32(uint32_t a, uint32_t v) { asm volatile("st.shared.u32 [%0], %1;" ::"r"(a), "r"(v) : "memory"); }
__device__ __forceinline__ void sts32(uint32_t a, float v) { asm volatile("st.shared.f32 [%0], %1;" ::"r"(a), "f"(v) : "memory"); }
__device__ __forceinline__ void sts128(uint32_t a, float x, float y, float z, float w) {
    asm volatile("st.shared.v4.f32 [%0], {%1,%2,%3,%4};" ::"r"(a), "f"(x), "f"(y), "f"(z), "f"(w) : "memory");
}
template <int N> struct IC { static constexpr int value = N; };
__device__ __forceinline__ int opq(int x) { asm volatile("" : "+r"(x)); return x; }
__device__ __forceinline__ uint32_t opq(uint32_t x) { asm volatile("" : "+r"(x)); return x; }
__device__ __forceinline__ uint32_t pin(uint32_t x) { x = opq(x); sts32(SM_MISC + 12, x); return x; }
__device__ __forceinline__ float pin(float x) { sts32(SM_MISC + 12, x); return x; }
template <typename T> __device__ __forceinline__ T* pin(T* p) {
    asm volatile("{\n.reg .b32 lo, hi;\nmov.b64 {lo, hi}, %0;\nst.shared.v2.b32 [%1], {lo, hi};\n}" : "+l"(p) : "r"(SM_MISC + 16) : "memory");
    return p;
}
template <typename T> __device__ __forceinline__ T* opq(T* p) { asm volatile("" : "+l"(p)); return p; }

__device__ __forceinline__ void ln_finish(float s1, float s2, float& mean, float& inv) {
    const float md = s1 * (1.0f / DM);
    const float var = fmaxf(s2 * (1.0f / DM) - md * md, 0.f);
    mean = bfr(md);
    asm("rsqrt.approx.ftz.f32 %0, %1;" : "=f"(inv) : "f"(var + 1e-5f));
}
__device__ __forceinline__ void ln_stats(float& mean, float& inv) {
    const float4 a = lds128f(SM_ST), b = lds128f(SM_ST + 16), c = lds128f(SM_ST + 32), d = lds128f(SM_ST + 48);
    ln_finish(((a.y + a.w) + (b.y + b.w)) + ((c.y + c.w) + (d.y + d.w)), ((a.x + a.z) + (b.x + b.z)) + ((c.x + c.z) + (d.x + d.z)), mean, inv);
}
template <int SK, bool GRAM, typename AddrF>
__device__ __forceinline__ void gemv15(float (&cc)[3][4], float (&gr)[4], uint32_t (&pre)[9][4], AddrF ad, uint32_t px, uint32_t px2) {
    uint32_t x0[4], x1[4];
    lds128(px, x0[0], x0[1], x0[2], x0[3]);
    lds128(px + 64, x1[0], x1[1], x1[2], x1[3]);
    gr[0] = gr[1] = gr[2] = gr[3] = 0.f;
#pragma unroll
    for (int i = 0; i < 3; i++) {
        cc[i][0] = cc[i][1] = cc[i][2] = cc[i][3] = 0.f;
        mma16816v(cc[i], pre[i][0], pre[i][1], pre[i][2], pre[i][3], x0[0], x0[1]);
    }
#pragma unroll
    for (int i = 0; i < 3; i++) ldsm4t(ad(i) + 3 * SK, pre[i]);
    if (GRAM) mma16816v(gr, x0[0], 0u, x0[1], 0u, x0[0], x0[1]);
#pragma unroll
    for (int i = 0; i < 3; i++) mma16816v(cc[i], pre[3 + i][0], pre[3 + i][1], pre[3 + i][2], pre[3 + i][3], x0[2], x0[3]);
#pragma unroll
    for (int i = 0; i < 3; i++) ldsm4t(ad(i) + 4 * SK, pre[3 + i]);
    lds64(px2, x0[0], x0[1]);
    if (GRAM) mma16816v(gr, x0[2], 0u, x0[3], 0u, x0[2], x0[3]);
#pragma unroll
    for (int i = 0; i < 3; i++) mma16816v(cc[i], pre[6 + i][0], pre[6 + i][1], pre[6 + i][2], pre[6 + i][3], x1[0], x1[1]);
    if (GRAM) mma16816v(gr, x1[0], 0u, x1[1], 0u, x1[0], x1[1]);
#pragma unroll
    for (int i = 0; i < 3; i++) mma16816v(cc[i], pre[i][0], pre[i][1], pre[i][2], pre[i][3], x1[2], x1[3]);
    if (GRAM) mma16816v(gr, x1[2], 0u, x1[3], 0u, x1[2], x1[3]);
    if (GRAM) mma16816v(gr, x0[0], 0u, x0[1], 0u, x0[0], x0[1]);
#pragma unroll
    for (int i = 0; i < 3; i++) mma16816v(cc[i], pre[3 + i][0], pre[3 + i][1], pre[3 + i][2], pre[3 + i][3], x0[0], x0[1]);
}
__device__ __forceinline__ void gemv15r(float (&cc)[3][4], float (&gr)[4], const uint32_t (&pre)[9][4], const uint32_t (&ext)[45][4], uint32_t px, uint32_t px2) {
    uint32_t x0[4], x1[4], x2[2];
    lds128(px, x0[0], x0[1], x0[2], x0[3]);
    lds128(px + 64, x1[0], x1[1], x1[2], x1[3]);
    lds64(px2, x2[0], x2[1]);
    gr[0] = gr[1] = gr[2] = gr[3] = 0.f;
#pragma unroll
    for (int ks = 0; ks < 5; ks++) {
        const uint32_t b0 = ks < 2 ? x0[2 * (ks & 1)] : ks < 4 ? x1[2 * (ks & 1)] : x2[0], b1 = ks < 2 ? x0[2 * (ks & 1) + 1] : ks < 4 ? x1[2 * (ks & 1) + 1] : x2[1];
        mma16816v(gr, b0, 0u, b1, 0u, b0, b1);
#pragma unroll
        for (int i = 0; i < 3; i++) {
            if (ks == 0) cc[i][0] = cc[i][1] = cc[i][2] = cc[i][3] = 0.f;
            const uint32_t (&f)[4] = ks < 3 ? pre[ks < 3 ? 3 * ks + i : 0] : ext[ks < 3 ? 0 : 3 * (ks - 3) + i];
            mma16816v(cc[i], f[0], f[1], f[2], f[3], b0, b1);
        }
    }
}

__device__ __forceinline__ void load_ffn(const Maps& maps, int b, uint32_t dst, uint32_t bar) {
    const bool gu = b < NG;
    mbar_expect_tx(bar, gu ? 61440 : 49152);
    tma3d(dst, gu ? (b < NG / 2 ? &maps.w1 : &maps.w3) : &maps.w2, gu ? 48 * (b & (NG / 2 - 1)) : 16 * (b - DN0), 0, 0, bar, POL_EF);
}

__device__ __forceinline__ void load_wo(const Maps& maps, uint32_t dst, int h, int c, uint32_t bar, int nbox) {
#pragma unroll 1
    for (int i = 0; i < nbox; i++) {
        mbar_expect_tx(bar + 8 * i, 12288);
        tma3d(dst + i * 12288, &maps.wo, 0, h * DH, 5 * c + i, bar + 8 * i, POL_EF);
    }
}

__global__ void __launch_bounds__(NT, 1)
decode_kernel(const __grid_constant__ Maps maps, const __nv_bfloat16* __restrict__ x_in, __nv_bfloat16* __restrict__ out) {
    extern __shared__ __align__(1024) unsigned char smem[];
    const int tid = threadIdx.x;
    const int wu = __shfl_sync(0xffffffffu, tid >> 5, 0);
    const int b = blockIdx.x, h = b >> 2, c = b & 3;
    if (smem_u32(smem) != SB) return;

    {
        const int warp = tid >> 5, lane = tid & 31;
        const uint32_t rbar = SM_BAR + warp * 16;
        if (lane == 0) {
            if (warp == 0) {
                mbar_init(QBAR, 1);
                asm volatile("fence.mbarrier_init.release.cluster;" ::: "memory");
                mbar_expect_tx(QBAR, 61440);
                tma5d(SM_Q, &maps.wq, 3 * h, 2 * c, QBAR, POL_EF);
            }
            mbar_init(rbar, 1); mbar_init(rbar + 8, 1); mbar_init(SM_XBAR + warp * 8, 1);
            mbar_init(FBAR + 8 * max(warp - 1, 0), warp == 7 ? 2 : 1);
            asm volatile("fence.mbarrier_init.release.cluster;" ::: "memory");
            if (warp >= 1 && warp < 7) {
                const CUtensorMap* mp = warp == 1 ? &maps.k : warp == 2 ? &maps.v : warp == 3 ? &maps.wo : warp == 4 ? &maps.w1 : warp == 5 ? &maps.w3 : &maps.w2;
                asm volatile("prefetch.tensormap [%0];" ::"l"(mp) : "memory");
            }
        }
        if (tid == 96) sts32(SM_MISC + 8, 0u);
        if (lane < 2) sts32(SM_KX + warp * 96 + 4 * lane, 0u);
        if (tid >= 128 && tid < 148) {
            const float v = f_(tid < 138 ? ONES : 0u);
            sts128(SM_ONE + 16 * (tid - 128), v, v, v, v);
        }
        if (b == 0 && tid == 255) asm volatile("st.relaxed.gpu.global.u32 [%0], %1;" ::"l"(maps.scr->ticket), "r"(0) : "memory");
        if (tid < 4) st_pkt(reinterpret_cast<uint4*>(&maps.scr->mx[h * 32 + c * 8]) + tid, 0, 0, 0, 0);
        if (tid >= 64 && tid < 66 && b < 108) st_pkt(&maps.scr->acc[1][(2 * b + tid - 64)], 0, 0, 0, 0);
        __syncthreads();
        if (lane == 0) {
            const int row = ROW0(warp);
            mbar_expect_tx(rbar, TILE);
            tma2d(SM_RING + warp * 2 * TILE, &maps.k, 0, row, rbar, POL_EF);
            mbar_expect_tx(rbar + 8, TILE);
            tma2d(SM_RING + (warp * 2 + 1) * TILE, &maps.k, 0, row + TS, rbar + 8, POL_EF);
        }
    }

    uint32_t kr[45][4];
#define KR(n) kr[(n) >> 2][(n) & 3]
    const float SC = 0.07216878364870322f * 1.4426950408889634f;
    int role = 0;
    uint32_t wk[3][4];

#pragma unroll 1
    for (int layer = 0; layer < 2; layer++) {
        const uint32_t tag = layer + 1, tbit = layer ^ 1;
        uint2 xv = make_uint2(0u, 0u);
        uint32_t qo;
        {
            const int tl = opq(tid), warp = tl >> 5, lane = tl & 31, g = lane >> 2, t = lane & 3, mat = lane >> 3, r8 = lane & 7;
            const int kh = warp >> 2, mg = warp & 3;
            const uint32_t aq = SM_Q + kh * TILE + ((mat >> 1) * 8 + r8) * 128 + (((2 * mg + (mat & 1)) ^ r8) << 4);
            if (layer == 0 && tl < 160) xv = reinterpret_cast<const uint2*>(x_in)[tl];
            mbar_wait(QBAR, 0);
            uint32_t pre[9][4];
#pragma unroll
            for (int n = 0; n < 9; n++) ldsm4t(aq + (n % 3) * 2048 + (n / 3) * 2 * TILE, pre[n]);
            if (layer == 1) {
                __syncthreads();
                delay(role >= DN0 + NDN ? 1500 : 0);
                if (role >= DN0 && role < DN0 + NDN) {
                    if (wu < 6) tile_load(SM_Q + wu * TILE, &maps.k, ROW0(wu) + 5 * TS, SM_XBAR + wu * 8);
                } else if (wu == 7) {
#pragma unroll 1
                    for (int w = 0; w < 6; w++) tile_load(SM_Q + w * TILE, &maps.k, ROW0(w) + 5 * TS, SM_XBAR + w * 8);
                }
            }
            const uint32_t pm = opq(g == 1 ? SM_ONE : SM_XS + 160 * (2 * c + kh) + 16 * t);
            const uint32_t pm2 = opq(pm + 128 - (g == 1 ? 0 : 8 * t));
            const uint32_t dq = opq(SM_R + 768 * kh + 4 * (16 * mg + g));
            qo = pin(16u * (b * 48 + (tl & 63) + (tl >= 64 ? NCTA * 48 : 0)));
            if (tl < 160) {
                const uint32_t xa0 = opq(SM_XS + 4 * xpos(2 * tl));
                const bool xl = tl % 20 < 16;
                if (layer == 1) {
                    const uint4* px = opq(&maps.scr->ay[tl]);
                    uint4 v;
                    int it = 0;
                    bool more;
                    do { v = ld_pkt(px); more = ++it < SPIN_CAP; } while (!__all_sync(0xffffffffu, (v.y & v.w) == 1) && more);
                    xv = make_uint2(v.x, v.z);
                }
                sts32(xa0, xv.x);
                if (xl) sts32(xa0 + 16, xv.y); else sts32(xa0 + 8, xv.y);
            }
            __syncthreads();
            float cc[3][4], gr[4];
            gemv15<2 * TILE, false>(cc, gr, pre, [&](int i) { return aq + i * 2048; }, pm, pm2);
            if (t == 0) {
#pragma unroll
                for (int i = 0; i < 3; i++) { sts32(dq + 256 * i, cc[i][0]); sts32(dq + 256 * i + 32, cc[i][2]); }
                if (layer == 0) {
#pragma unroll
                    for (int i = 0; i < 3; i++) { sts32(dq + 256 * i + 1536, cc[i][1]); sts32(dq + 256 * i + 1568, cc[i][3]); }
                }
            }
        }
        {
            const int tl = opq(tid), j = tl & 63;
            const bool snd = j < 48 && (tl < 64 || (tl < 128 && layer == 0));
            const uint32_t fa = opq(SM_R + 16 * tl + (tl >= 64 ? 512 : 0));
            uint4* pq = reinterpret_cast<uint4*>(reinterpret_cast<char*>(maps.scr->qx) + qo);
            __syncthreads();
            if (snd) {
                const float4 u = lds128f(fa), v = lds128f(fa + 768);
                st_pktf(pq, u.x + v.x, u.y + v.y, u.z + v.z, u.w + v.w, tbit);
            }
            if (layer == 1 && wu >= 5) {
                delay(300);
                if (wu >= 6) tile_load(SM_Q + wu * TILE, &maps.k, ROW0(wu) + 5 * TS, SM_XBAR + wu * 8);
                else if (role < NG && elect_one()) {
                    mbar_expect_tx(WBAR + 32, 12288);
                    tma3d(SM_Q + 4 * 12288, &maps.wo, 0, h * DH, 5 * c + 4, WBAR + 32, POL_EF);
                }
            }
            if (layer == 1 && tl >= 192 && tl < 194 && b < 108) st_pkt(&maps.scr->acc[0][(2 * b + tl - 192)], 0, 0, 0, 0);
        }

        float sc0 = -INFINITY, sc1 = -INFINITY, sc2 = 0.f, sc3 = 0.f, mw;
        uint32_t pk0, pk1;
        float acc[3][4];
        {
            const uint32_t ring = SM_RING + wu * 2 * TILE, rb = SM_BAR + wu * 16;
            const uint32_t xtile = SM_Q + wu * TILE, xb = SM_XBAR + wu * 8;
            const int row0 = ROW0(wu);
            const uint32_t bt = SM_B + wu * TILE;
            auto issue1 = [&](int n, bool vph = false) {
                const CUtensorMap* mp = n < 8 ? &maps.k : &maps.v;
                const int row = row0 + ((n + (n >= 8 ? 2 : 0)) & 7) * TS;
                if (vph && wu < L1R && n == 12 - (wu & 1)) {
                    tile_load_l1(ring + (n & 1) * TILE, maps.vp, row, rb + (n & 1) * 8, opq(tid) & 31);
                    return;
                }
                const int k = vph || n >= 6 ? n & 1 : n >= 3 ? n - 3 : n;
                tile_load(k == 2 ? bt : ring + k * TILE, mp, row, k == 2 ? xb : rb + k * 8);
                if ((maps.rt[wu] >> n) & 1) tile_keep(n < 8 ? &maps.ks : &maps.vs, row);
            };
            auto refill1 = [&](int s, bool vph = false) { issue1(s + 2, vph); };
#define K_OFF(i) ((uint32_t)((3 * ((g >> 1) + 4 * (g & 1)) + ((i) >> 1)) * 128 + ((t ^ ((3 * ((g >> 1) + 4 * (g & 1)) + ((i) >> 1)) & 7) ^ (((i) & 1) << 2)) << 4)))
#define V_OFF(i) ((uint32_t)((6 * t + (i)) * 128 + ((g ^ ((6 * t + (i)) & 7)) << 4)))
#define LANE_IDS const int tl = opq(tid), lane = tl & 31, g = lane >> 2, t = lane & 3; (void)tl; (void)lane; (void)g; (void)t;
            const uint32_t kx = SM_KX + wu * 96;
#pragma unroll 1
            for (int s = layer ? 5 : 0; s < 5 + layer; s++) {
                if (s < 5) {
                    LANE_IDS
                    const int k = s >= 3 ? s - 3 : s;
                    mbar_wait(k == 2 ? xb : rb + k * 8, s >= 3);
                    refill1(s);
                    const uint32_t tile = k == 2 ? bt : ring + k * TILE;
                    uint32_t mx = 0u, mn = 0xffffffffu, mn2 = 0xffffffffu;
#pragma unroll
                    for (int q = 0; q < 12; q++) {
                        uint32_t a0, a1, a2, a3;
                        lds128(tile + K_OFF(q % 6) + (q / 6) * 3072, a0, a1, a2, a3);
                        a0 &= 0x7fff7fffu; a1 &= 0x7fff7fffu; a2 &= 0x7fff7fffu; a3 &= 0x7fff7fffu;
                        mx = __vimax3_u16x2(__vimax3_u16x2(mx, a0, a1), a2, a3);
                        mn = __viaddmin_u16x2(a0, 0xffffffffu, __viaddmin_u16x2(a1, 0xffffffffu, mn));
                        mn2 = __viaddmin_u16x2(a2, 0xffffffffu, __viaddmin_u16x2(a3, 0xffffffffu, mn2));
                    }
                    mn = __vminu2(mn, mn2);
                    const uint32_t emax = __reduce_max_sync(0xffffffffu, max(mx & 0xffffu, mx >> 16)) >> 7;
                    const uint32_t base = (max(emax, 16u) - 15u) << 7, lim = base + 0x7fu;
                    bool raw = emax < 80u || emax > 190u;
                    uint32_t fl = __ballot_sync(0xffffffffu, min(mn & 0xffffu, mn >> 16) < lim);
                    if (!raw && fl) {
                        const uint32_t n0 = lds32(kx);
                        __syncwarp();
#pragma unroll 1
                        for (; fl; fl &= fl - 1) {
                            const int g = (__ffs(fl) - 1) >> 2, t = (__ffs(fl) - 1) & 3, q = min(lane, 23) >> 1, i = q >= 6 ? q - 6 : q;
                            const uint32_t a = tile + K_OFF(i) + (q >= 6 ? 3072 : 0) + 8 * (lane & 1);
                            uint32_t w0, w1;
                            lds64(a, w0, w1);
#pragma unroll 1
                            for (int e = 0; e < 4; e++) {
                                const uint32_t x = __funnelshift_r(w0, w1, 16 * e) & 0xffffu;
                                if (e == 1) w0 = w1;
                                if ((x & 0x7fffu) - 1u < lim && lane < 24) {
                                    uint32_t n;
                                    asm volatile("atom.shared.add.u32 %0, [%1], 1;" : "=r"(n) : "r"(kx) : "memory");
                                    if (n < NEXC) sts32(kx + 32 + 4 * n, x | (2 * ((2 * t + (e >> 1)) * 12 + 2 * i + (lane & 1)) + (e & 1)) << 16 | (16 * s + (q >= 6 ? 8 : 0) + g) << 24);
                                    sts16(a + 2 * e, 0u);
                                }
                            }
                        }
                        __syncwarp();
                        raw = lds32(kx) > NEXC;
                        __syncwarp();
                        if (raw && lane == 0) sts32(kx, n0);
                    }
                    if (lane == 0) {
                        sts32(kx + 8 + 4 * s, (base + (31u << 7)) << 16);
                        if (raw) sts32(kx + 4, lds32(kx + 4) | 1u << s);
                    }
                    const uint32_t b2 = (0x10000u - base) * 0x10001u;
                    auto pack = [&](auto S) {
                        constexpr int n0 = 36 * decltype(S)::value;
#pragma unroll
                        for (int q = 0; q < 12; q++) {
                            uint32_t a0, a1, a2, a3;
                            lds128(tile + K_OFF(q % 6) + (q / 6) * 3072, a0, a1, a2, a3);
                            a0 = __viaddmax_s16x2(a0 & 0x7fff7fffu, b2, 0u) | (a0 & 0x80008000u); a1 = __viaddmax_s16x2(a1 & 0x7fff7fffu, b2, 0u) | (a1 & 0x80008000u);
                            a2 = __viaddmax_s16x2(a2 & 0x7fff7fffu, b2, 0u) | (a2 & 0x80008000u); a3 = __viaddmax_s16x2(a3 & 0x7fff7fffu, b2, 0u) | (a3 & 0x80008000u);
                            KR(n0 + 3 * q) = __byte_perm(a0, a1, 0x6420);
                            KR(n0 + 3 * q + 1) = __byte_perm(a2, a3, 0x6420);
                            const uint32_t ho = __byte_perm(a2, a3, 0x7531);
                            KR(n0 + 3 * q + 2) = __byte_perm(a0, a1, 0x7531) | __funnelshift_r(ho, ho, 4);
                        }
                    };
                    switch (s) {
                        case 0: pack(IC<0>()); break;
                        case 1: pack(IC<1>()); break;
                        case 2: pack(IC<2>()); break;
                        case 3: pack(IC<3>()); break;
                        default: pack(IC<4>()); break;
                    }
                    __syncwarp();
                }
                if (wu < 2 && (s == 3 || layer)) {
                    const int tc = min(opq(tid), 47);
                    const uint4* pq = opq(&maps.scr->qx[h * 4 * 48 + tc]);
                    uint4 v[4];
                    int it = 0;
                    bool more = true;
#pragma unroll
                    for (int k = 0; k < 4; k++) v[k] = ld_pkt(pq + 48 * k);
                    if (layer == 0) {
                        uint4 u[4];
                        do {
#pragma unroll
                            for (int k = 0; k < 4; k++) u[k] = ld_pkt(pq + NCTA * 48 + 48 * k);
                            more = ++it < SPIN_CAP;
                        } while (!__all_sync(0xffffffffu, u[0].w & u[1].w & u[2].w & u[3].w & 1) && more);
                        sts128(SM_CS + 16 * tc, (f_(u[0].x) + f_(u[1].x)) + (f_(u[2].x) + f_(u[3].x)), (f_(u[0].y) + f_(u[1].y)) + (f_(u[2].y) + f_(u[3].y)),
                               (f_(u[0].z) + f_(u[1].z)) + (f_(u[2].z) + f_(u[3].z)), (f_(u[0].w) + f_(u[1].w)) + (f_(u[2].w) + f_(u[3].w)));
                    }
                    float mean, inv;
                    {
                        const int lane = opq(tid) & 31;
                        uint32_t xw[10];
                        lds128(SM_XS + 16 * lane, xw[0], xw[1], xw[2], xw[3]);
                        lds128(SM_XS + 512 + 16 * lane, xw[4], xw[5], xw[6], xw[7]);
                        lds64(SM_XS + 1024 + 8 * lane, xw[8], xw[9]);
                        float s1 = 0.f, s2 = 0.f, s3 = 0.f, s4 = 0.f;
#pragma unroll
                        for (int i = 0; i < 10; i++) { const float e0 = bf_lo(xw[i]), e1 = bf_hi(xw[i]); s1 += e0; s3 += e1; s2 = fmaf(e0, e0, s2); s4 = fmaf(e1, e1, s4); }
                        s1 += s3; s2 += s4;
                        const bool lo = lane < 16;
                        float sv = (lo ? s1 : s2) + __shfl_xor_sync(0xffffffffu, lo ? s2 : s1, 16);
#pragma unroll
                        for (int o = 8; o > 0; o >>= 1) sv += __shfl_xor_sync(0xffffffffu, sv, o);
                        const float so = __shfl_xor_sync(0xffffffffu, sv, 16);
                        ln_finish(lo ? sv : so, lo ? so : sv, mean, inv);
                    }
                    const float4 cs = lds128f(SM_CS + 16 * tc);
                    mean *= -inv;
                    const float m0 = pin(mean * cs.x), m1 = pin(mean * cs.y), m2 = pin(mean * cs.z), m3 = pin(mean * cs.w);
                    const int w = 2 * tc;
                    const uint32_t qd = pin(SM_QS + 4 * (((w >> 2) & 3) * 24 + 2 * (w >> 4) + ((w >> 1) & 1)));
                    while (__any_sync(0xffffffffu, ((v[0].w ^ tbit) | (v[1].w ^ tbit) | (v[2].w ^ tbit) | (v[3].w ^ tbit)) & 1) && more) {
#pragma unroll
                        for (int k = 0; k < 4; k++) v[k] = ld_pkt(pq + 48 * k);
                        more = ++it < SPIN_CAP;
                    }
                    const float q0 = fmaf(inv, (f_(v[0].x) + f_(v[1].x)) + (f_(v[2].x) + f_(v[3].x)), m0), q1 = fmaf(inv, (f_(v[0].y) + f_(v[1].y)) + (f_(v[2].y) + f_(v[3].y)), m1);
                    const float q2 = fmaf(inv, (f_(v[0].z) + f_(v[1].z)) + (f_(v[2].z) + f_(v[3].z)), m2), q3 = fmaf(inv, (f_(v[0].w) + f_(v[1].w)) + (f_(v[2].w) + f_(v[3].w)), m3);
                    sts32(qd, pack2(q0, q1));
                    sts32(qd + 48, pack2(q2, q3));
                    __syncwarp();
                    if (elect_one()) asm volatile("mbarrier.arrive.shared::cta.b64 _, [%0];" ::"r"(QRDY) : "memory");
                }
            }
            uint32_t qa, ka[3];
            {
                LANE_IDS
                qa = opq(SM_QS + (2 * t + (g & 1)) * 48);
#pragma unroll
                for (int i = 0; i < 3; i++) ka[i] = opq(xtile + K_OFF(2 * i));
            }
            uint32_t f[6][4];
            if (layer == 1) {
                if (wu >= 2 && wu < 5) delay(300);
                mbar_wait(xb, 0);
            }
#pragma unroll
            for (int i = 0; i < 6; i++) lds128(ka[i >> 1] ^ ((i & 1) << 6), f[i][0], f[i][1], f[i][2], f[i][3]);
            if (layer == 1) {
                __syncwarp();
                half_load(xtile, &maps.kh, row0 + 6 * TS, xb, true);
            }
            mbar_wait(QRDY, layer);
            {
                uint32_t qf[12];
#pragma unroll
                for (int i = 0; i < 3; i++) lds128(qa + 16 * i, qf[4 * i], qf[4 * i + 1], qf[4 * i + 2], qf[4 * i + 3]);
                const int t = opq(tid) & 3;
                auto kr_scores = [&](auto TAU, float& sa, float& sb) {
                    constexpr int tau = decltype(TAU)::value;
                    float cc[2][4] = {{0.f, 0.f, 0.f, 0.f}, {0.f, 0.f, 0.f, 0.f}};
#pragma unroll
                    for (int n = 0; n < 12; n++) {
                        const int q = (n & 1) * 6 + (n >> 1), i = n >> 1;
                        const uint32_t l0 = KR(36 * tau + 3 * q), l1 = KR(36 * tau + 3 * q + 1), hh = KR(36 * tau + 3 * q + 2);
                        const uint32_t h0 = hh & 0x87878787u, h1 = __funnelshift_l(hh, hh, 4) & 0x87878787u;
                        mma16816(cc[n & 1], __byte_perm(l0, h0, 0x5140), __byte_perm(l0, h0, 0x7362), __byte_perm(l1, h1, 0x5140), __byte_perm(l1, h1, 0x7362), qf[2 * i], qf[2 * i + 1]);
                    }
                    if (t == (tau & 3)) { sa = cc[0][0] + cc[0][3]; sb = cc[1][0] + cc[1][3]; }
                };
                auto stage_v = [&](auto S) {
                    constexpr int s = decltype(S)::value;
                    const int lane = opq(tid) & 31, g = lane >> 2, t = lane & 3;
#pragma unroll
                    for (int i = 0; i < 6; i++) {
                        const uint32_t a = ring + s * TILE + V_OFF(i);
                        lds128(a, kr[12 * s + i][0], kr[12 * s + i][1], kr[12 * s + i][2], kr[12 * s + i][3]);
                        lds128(a + 3072, kr[12 * s + 6 + i][0], kr[12 * s + 6 + i][1], kr[12 * s + 6 + i][2], kr[12 * s + 6 + i][3]);
                    }
                    __syncwarp();
                    tile_load(ring + s * TILE, s ? &maps.v : &maps.k, row0 + (s ? 2 : 7) * TS, rb + s * 8);
                };
                if (layer == 1) {
                    float cA[4] = {0.f, 0.f, 0.f, 0.f}, cB[4] = {0.f, 0.f, 0.f, 0.f};
#pragma unroll
                    for (int i = 0; i < 6; i++) {
                        mma16816v(cA, f[i][0], f[i][1], f[i][2], f[i][3], qf[2 * i], qf[2 * i + 1]);
                        lds128((opq(ka[i >> 1]) ^ ((i & 1) << 6)) + 3072, f[i][0], f[i][1], f[i][2], f[i][3]);
                    }
                    __syncwarp();
                    half_load(xtile + 3072, &maps.kh, row0 + 6 * TS + 24, xb, false);
#pragma unroll
                    for (int i = 0; i < 6; i++) mma16816v(cB, f[i][0], f[i][1], f[i][2], f[i][3], qf[2 * i], qf[2 * i + 1]);
                    sc2 = cA[0] + cA[3]; sc3 = cB[0] + cB[3];
                }
#pragma unroll
                for (int i = 0; i < 12; i++) qf[i] = mul2(qf[i], 0x6f806f80u);
                kr_scores(IC<0>(), sc0, sc1);
                kr_scores(IC<1>(), sc0, sc1);
                if (layer == 1) stage_v(IC<0>());
                kr_scores(IC<2>(), sc0, sc1);
                if (layer == 1) stage_v(IC<1>());
                kr_scores(IC<3>(), sc0, sc1);
                kr_scores(IC<4>(), sc2, sc3);
                {
                    LANE_IDS
                    const float sa = f_(lds32(kx + 8 + 4 * t)), sb = t == 0 ? f_(lds32(kx + 24)) : 1.0f;
                    const int nx = (int)lds32(kx);
                    uint32_t rm = lds32(kx + 4), qm = 0u;
#pragma unroll
                    for (int i = 0; i < 6; i++) qm = __vimax3_u16x2(qm, qf[2 * i] & 0x7fff7fffu, qf[2 * i + 1] & 0x7fff7fffu);
#pragma unroll
                    for (int i = 0; i < 3; i++) lds128(SM_QS + (2 * t + (g & 1)) * 48 + 16 * i, qf[4 * i], qf[4 * i + 1], qf[4 * i + 2], qf[4 * i + 3]);
                    if (__any_sync(0xffffffffu, max(qm & 0xffffu, qm >> 16) >= 0x7f80u)) rm = 31;
                    sc0 *= sa; sc1 *= sa; sc2 *= sb; sc3 *= sb;
#pragma unroll 1
                    for (int n = 0; n < nx; n++) {
                        const uint32_t w = lds32(kx + 32 + 4 * n);
                        const int tau = w >> 28;
                        const float d = bf_lo(lds16(SM_QS + ((w >> 15) & 0x1fe))) * bf_lo(w);
                        if (((w >> 24) & 7) == g && (tau & 3) == t) {
                            const int k = ((w >> 27) & 1) + (tau >> 2) * 2;
                            if (k == 0) sc0 += d; else if (k == 1) sc1 += d; else if (k == 2) sc2 += d; else sc3 += d;
                        }
                    }
#pragma unroll 1
                    for (; rm; rm &= rm - 1) {
                        const int tau = __ffs(rm) - 1;
#pragma unroll 1
                        for (int hf = 0; hf < 2; hf++) {
                            const char* gp = static_cast<const char*>(maps.kp) + (size_t)(row0 + tau * TS) * 128 + (8 * hf + (g >> 1) + 4 * (g & 1)) * 384 + 16 * t;
                            float cA[4] = {0.f, 0.f, 0.f, 0.f};
#pragma unroll
                            for (int i = 0; i < 6; i++) {
                                const uint4 a = __ldcg(reinterpret_cast<const uint4*>(gp + 64 * i));
                                mma16816(cA, a.x, a.y, a.z, a.w, qf[2 * i], qf[2 * i + 1]);
                            }
                            if ((tau & 3) == t) {
                                const int k = hf + (tau >> 2) * 2;
                                const float d = cA[0] + cA[3];
                                if (k == 0) sc0 = d; else if (k == 1) sc1 = d; else if (k == 2) sc2 = d; else sc3 = d;
                            }
                        }
                    }
                }
                if (layer == 0) {
                    LANE_IDS
#pragma unroll 1
                    for (int s = 5; s < 8; s++) {
                        mbar_wait(s == 5 ? xb : rb + (s & 1) * 8, s == 5);
                        const uint32_t tile = s == 5 ? bt : ring + (s & 1) * TILE;
                        float cA[4] = {0.f, 0.f, 0.f, 0.f}, cB[4] = {0.f, 0.f, 0.f, 0.f};
#pragma unroll
                        for (int i = 0; i < 6; i++) {
                            uint32_t a0, a1, a2, a3;
                            lds128(tile + K_OFF(i), a0, a1, a2, a3);
                            mma16816(cA, a0, a1, a2, a3, qf[2 * i], qf[2 * i + 1]);
                            lds128(tile + K_OFF(i) + 3072, a0, a1, a2, a3);
                            mma16816(cB, a0, a1, a2, a3, qf[2 * i], qf[2 * i + 1]);
                        }
                        if (t == (s & 3)) { sc2 = cA[0] + cA[3]; sc3 = cB[0] + cB[3]; }
                        __syncwarp();
                        refill1(s);
                    }
                } else {
                    LANE_IDS
#pragma unroll 1
                    for (int i = 2; i < 4; i++) {
                        const uint32_t tile = i == 3 ? ring : xtile, tb = i == 3 ? rb : xb;
                        mbar_wait(tb, 1);
#pragma unroll
                        for (int k = 0; k < 6; k++) {
                            const uint32_t a = tile + K_OFF(k);
                            lds128(a, kr[24 + k][0], kr[24 + k][1], kr[24 + k][2], kr[24 + k][3]);
                            lds128(a + 3072, kr[24 + 6 + k][0], kr[24 + 6 + k][1], kr[24 + 6 + k][2], kr[24 + 6 + k][3]);
                        }
                        float cA[4] = {0.f, 0.f, 0.f, 0.f}, cB[4] = {0.f, 0.f, 0.f, 0.f}, cC[4] = {0.f, 0.f, 0.f, 0.f}, cD[4] = {0.f, 0.f, 0.f, 0.f};
#pragma unroll
                        for (int k = 0; k < 3; k++) {
                            mma16816(cA, kr[24 + k][0], kr[24 + k][1], kr[24 + k][2], kr[24 + k][3], qf[2 * k], qf[2 * k + 1]);
                            mma16816(cB, kr[24 + 6 + k][0], kr[24 + 6 + k][1], kr[24 + 6 + k][2], kr[24 + 6 + k][3], qf[2 * k], qf[2 * k + 1]);
                            mma16816(cC, kr[24 + 3 + k][0], kr[24 + 3 + k][1], kr[24 + 3 + k][2], kr[24 + 3 + k][3], qf[6 + 2 * k], qf[7 + 2 * k]);
                            mma16816(cD, kr[24 + 9 + k][0], kr[24 + 9 + k][1], kr[24 + 9 + k][2], kr[24 + 9 + k][3], qf[6 + 2 * k], qf[7 + 2 * k]);
                        }
                        __syncwarp();
                        tile_load(tile, &maps.v, row0 + (i + 1) * TS, tb);
                        if (t == i) { sc2 = (cA[0] + cC[0]) + (cA[3] + cC[3]); sc3 = (cB[0] + cD[0]) + (cB[3] + cD[3]); }
                    }
                }
            }
            {
                const uint32_t mk = __reduce_max_sync(0xffffffffu, f2key(fmaxf(fmaxf(sc0, sc1), fmaxf(sc2, sc3))));
                if ((opq(tid) & 31) == 0) st_pkt2(&maps.scr->mx[h * 32 + c * 8 + wu], mk, tag);
                mw = key2f(mk);
            }
            pk0 = pack2(ex2((sc0 - mw) * SC), ex2((sc1 - mw) * SC));
            pk1 = pack2(ex2((sc2 - mw) * SC), ex2((sc3 - mw) * SC));
            sc2 = (bf_lo(pk0) + bf_hi(pk0)) + (bf_lo(pk1) + bf_hi(pk1));
#pragma unroll
            for (int o = 16; o > 0; o >>= 1) sc2 += __shfl_xor_sync(0xffffffffu, sc2, o);
#pragma unroll
            for (int s = 0; s < 3; s++) { acc[s][0] = acc[s][1] = acc[s][2] = acc[s][3] = 0.f; }
            auto head_ld = [&](int lane) { const uint2 mv = ld_pkt2(&maps.scr->mx[h * 32 + lane]); sc0 = f_(mv.x); sc1 = f_(mv.y); };
            auto head_factor = [&](int lane) {
                int it = 0;
                while (!__all_sync(0xffffffffu, __float_as_uint(sc1) == tag) && ++it < SPIN_CAP) head_ld(lane);
                sc3 = ex2((mw - key2f(__reduce_max_sync(0xffffffffu, __float_as_uint(sc0)))) * SC);
            };
#define P_CONSTS \
                const uint32_t sel0 = g == 0 ? 0x4410u : (g == 1 ? 0x1044u : 0x4444u); \
                const uint32_t sel1 = g == 2 ? 0x4410u : (g == 3 ? 0x1044u : 0x4444u); \
                const int src00 = 4 * (t < 2 ? 4 * t : 4 * (t - 2) + 1);
#define P_FRAGS(tau) \
                const uint32_t pk = ((tau) & 4) ? pk1 : pk0; \
                const uint32_t w0 = __shfl_sync(0xffffffffu, pk, src00 + ((tau) & 3)); \
                const uint32_t w1 = __shfl_sync(0xffffffffu, pk, src00 + ((tau) & 3) + 8); \
                uint32_t pb[4][2]; \
                _Pragma("unroll") for (int j = 0; j < 4; j++) { \
                    const uint32_t src = ((j & 1) ? w1 : w0) >> ((j >> 1) * 16); \
                    pb[j][0] = __byte_perm(src, 0, sel0); pb[j][1] = __byte_perm(src, 0, sel1); \
                }
            if (layer == 0) {
#pragma unroll 1
                for (int s = 8; s < 16; s++) {
                    LANE_IDS
                    P_CONSTS
                    if (s == 14) {
                        uint4* p = nullptr;
                        if (tl < 48) p = &maps.scr->qx[b * 48 + tl];
                        else if (tl < 98) p = &maps.scr->cx[b * 56 + tl - 48];
                        else if (tl < 145) {}
                        else if (tl >= 160) { if (tl < 208) p = &maps.scr->qc[b * 48 + tl - 160]; }
                        else if (b < NG) { if (tl < 153) p = &maps.scr->ah[b * 8 + tl - 145]; }
                        else if (b < DN0 + NDN && tl < 149) p = &maps.scr->ay[(b - DN0) * 4 + tl - 145];
                        if (p) st_pkt(p, 0, 0, 0, tl < 48);
                    }
                    if (s == 13) head_ld(lane);
                    P_FRAGS((s + 2) & 7)
                    mbar_wait(rb + (s & 1) * 8, ((s >> 1) + 1) & 1);
                    const uint32_t tile = ring + (s & 1) * TILE;
#pragma unroll
                    for (int j = 0; j < 4; j++) {
#pragma unroll
                        for (int u = 0; u < 3; u++) {
                            uint32_t a0, a1, a2, a3;
                            lds128(tile + (j >> 1) * 3072 + V_OFF(3 * (j & 1) + u), a0, a1, a2, a3);
                            mma16816(acc[u], a0, a1, a2, a3, pb[j][0], pb[j][1]);
                        }
                    }
                    __syncwarp();
                    if (s < 14) refill1(s, true);
                    if (s == 13) head_factor(lane);
                    if (s == 15 && elect_one()) {
                        uint32_t n;
                        asm volatile("atom.shared.add.u32 %0, [%1], 1;" : "=r"(n) : "r"(SM_MISC + 8) : "memory");
                        if (n == 7) load_wo(maps, SM_B, h, c, WBAR, 5);
                    }
                }
            } else {
                LANE_IDS
                P_CONSTS
#pragma unroll
                for (int s = 0; s < 2; s++) {
                    P_FRAGS(s)
#pragma unroll
                    for (int j = 0; j < 4; j++) {
#pragma unroll
                        for (int u = 0; u < 3; u++) {
                            const int k = 6 * (j >> 1) + 3 * (j & 1) + u;
                            mma16816(acc[u], kr[12 * s + k][0], kr[12 * s + k][1], kr[12 * s + k][2], kr[12 * s + k][3], pb[j][0], pb[j][1]);
                        }
                    }
                }
#pragma unroll 1
                for (int i = 4; i < 10; i++) {
                    const int sl = i == 5 ? 0 : (i == 6 || i == 8 ? 1 : 2);
                    const uint32_t tile = sl ? ring + (sl - 1) * TILE : xtile, tb = sl ? rb + (sl - 1) * 8 : xb;
                    if (i == 8) head_ld(lane);
                    if (i == 9) head_factor(lane);
                    P_FRAGS(i - 2)
                    mbar_wait(tb, (0x310 >> i) & 1);
#pragma unroll
                    for (int k = 0; k < 6; k++) {
                        const uint32_t a = tile + V_OFF(k);
                        lds128(a, kr[24 + k][0], kr[24 + k][1], kr[24 + k][2], kr[24 + k][3]);
                        lds128(a + 3072, kr[24 + 6 + k][0], kr[24 + 6 + k][1], kr[24 + 6 + k][2], kr[24 + 6 + k][3]);
                    }
#pragma unroll
                    for (int j = 0; j < 4; j++) {
#pragma unroll
                        for (int u = 0; u < 3; u++) {
                            const int k = 6 * (j >> 1) + 3 * (j & 1) + u;
                            mma16816(acc[u], kr[24 + k][0], kr[24 + k][1], kr[24 + k][2], kr[24 + k][3], pb[j][0], pb[j][1]);
                        }
                    }
                    __syncwarp();
                    if (wu < L1R && i == 6 - 2 * (wu & 1)) tile_load_l1(tile, maps.vp, row0 + (6 - (wu & 1)) * TS, tb, lane);
                    else if (i == 4 || i == 6 || i == 7) tile_load(tile, &maps.v, row0 + (i == 4 ? 5 : i) * TS, tb);
                    if (i == 7 && role < DN0 + NDN && elect_one()) {
                        uint32_t n;
                        asm volatile("atom.shared.add.u32 %0, [%1], 1;" : "=r"(n) : "r"(SM_MISC + 8) : "memory");
                        if (n == 15) load_wo(maps, SM_Q, h, c, WBAR, 3);
                    }
                }
            }
#undef P_FRAGS
#undef P_CONSTS
#undef LANE_IDS
#undef K_OFF
#undef V_OFF
        }

        uint32_t ticket = 0;
        {
            const int tl = opq(tid), warp = tl >> 5, lane = tl & 31, g = lane >> 2, t = lane & 3, mat = lane >> 3, r8 = lane & 7;
            {
                const uint32_t d = SM_R + 4 * (warp * 196 + 8 * g + 4 * t);
                if (t < 2) {
#pragma unroll
                    for (int u = 0; u < 3; u++) sts128(d + 256 * u, acc[u][0] * sc3, acc[u][1] * sc3, acc[u][2] * sc3, acc[u][3] * sc3);
                }
                if (lane == 0) sts128(d + 768, sc2 * sc3, 0.f, 0.f, 0.f);
            }
            const int tc = min(tl, 48);
            uint4* pc = opq(&maps.scr->cx[h * 4 * 56 + tc]);
            uint4* po = opq(pc + c * 56);
            const uint32_t fa = opq(SM_R + 16 * tc);
            __syncthreads();
            const int kg = warp >> 1, mg = warp & 1;
            const bool wo2 = layer && role < DN0 + NDN;
            const bool wo4 = layer && role < NG;
            uint32_t aw, oa, ob0, dw;
            uint32_t* tk;
            auto addrs = [&]() {
                aw = pin((wo2 ? SM_Q : SM_B) + (48 * kg + (mat >> 1) * 8 + r8) * 64 + (((2 * mg + (mat & 1)) ^ ((r8 >> 1) & 3)) << 4));
                oa = pin(SM_OS + 96 * kg + 8 * t);
                ob0 = pin(oa + 8 * t);
                dw = pin(SM_R + 4 * (4 * (16 * mg + g) + kg));
                tk = opq(maps.scr->ticket + 0);
            };
            uint32_t a[2][3][4];
            auto preload = [&]() {
#pragma unroll
                for (int i = 0; i < 2; i++) {
                    mbar_wait(WBAR + 8 * i, wo2);
#pragma unroll
                    for (int ks = 0; ks < 3; ks++) ldsm4t(aw + i * 12288 + ks * 1024, a[i][ks]);
                }
            };
            if (wu < 2) {
                if (tl < 49) {
                    float4 v[8];
#pragma unroll
                    for (int w = 0; w < 8; w++) v[w] = lds128f(fa + w * 784);
                    st_pktf(po, ((v[0].x + v[1].x) + (v[2].x + v[3].x)) + ((v[4].x + v[5].x) + (v[6].x + v[7].x)),
                            ((v[0].y + v[1].y) + (v[2].y + v[3].y)) + ((v[4].y + v[5].y) + (v[6].y + v[7].y)),
                            ((v[0].z + v[1].z) + (v[2].z + v[3].z)) + ((v[4].z + v[5].z) + (v[6].z + v[7].z)),
                            ((v[0].w + v[1].w) + (v[2].w + v[3].w)) + ((v[4].w + v[5].w) + (v[6].w + v[7].w)), tbit);
                }
                __syncwarp();
                uint4 v[4];
#pragma unroll
                for (int k = 0; k < 4; k++) v[k] = ld_pkt(pc + k * 56);
                asm volatile("bar.arrive 1, 256;" ::: "memory");
                addrs();
                const int w = 2 * tc, k3 = w / 24, r = w - 24 * k3;
                const uint32_t d0 = pin(tl < 48 ? SM_OS + 4 * (24 * k3 + (r < 16 ? 4 * (r & 3) + (r >> 2) : 16 + 2 * (r & 3) + ((r >> 2) & 1))) : SM_MISC);
                const uint32_t d1 = pin(tl < 48 ? d0 + (r < 16 ? 16 : 8) : SM_MISC + 12);
                int it = 0;
                bool more = true;
                while (__any_sync(0xffffffffu, ((v[0].w ^ tbit) | (v[1].w ^ tbit) | (v[2].w ^ tbit) | (v[3].w ^ tbit)) & 1) && more) {
#pragma unroll
                    for (int k = 0; k < 4; k++) v[k] = ld_pkt(pc + k * 56);
                    more = ++it < SPIN_CAP;
                }
                const float o0 = (f_(v[0].x) + f_(v[1].x)) + (f_(v[2].x) + f_(v[3].x));
                const uint32_t w0 = pack2(o0, (f_(v[0].y) + f_(v[1].y)) + (f_(v[2].y) + f_(v[3].y)));
                sts32(d1, pack2((f_(v[0].z) + f_(v[1].z)) + (f_(v[2].z) + f_(v[3].z)), (f_(v[0].w) + f_(v[1].w)) + (f_(v[2].w) + f_(v[3].w))));
                sts32(d0, tl < 48 ? w0 : __float_as_uint(o0));
                asm volatile("bar.arrive 2, 256;" ::: "memory");
                preload();
                asm volatile("bar.sync 3, 64;" ::: "memory");
            } else {
                addrs();
                asm volatile("bar.sync 1, 256;" ::: "memory");
                preload();
                asm volatile("bar.sync 2, 256;" ::: "memory");
            }
            uint32_t ob[6];
            lds128(ob0, ob[0], ob[1], ob[2], ob[3]);
            lds64(oa + 64, ob[4], ob[5]);
            if (tl == 224 && layer == 0)
                asm volatile("atom.relaxed.gpu.global.inc.u32 %0, [%1], 0x7fffffff;" : "=r"(ticket) : "l"(tk) : "memory");
            auto put = [&](int i, const float (&cc)[4]) { if (t == 0) { sts32(dw + 512 * i, cc[0]); sts32(dw + 512 * i + 128, cc[2]); } };
            {
                float c0[4] = {0.f, 0.f, 0.f, 0.f}, c1[4] = {0.f, 0.f, 0.f, 0.f}, c2[4] = {0.f, 0.f, 0.f, 0.f}, c3[4] = {0.f, 0.f, 0.f, 0.f};
                mbar_wait(WBAR + 16, wo2);
#pragma unroll
                for (int ks = 0; ks < 3; ks++) {
                    mma16816v(c0, a[0][ks][0], a[0][ks][1], a[0][ks][2], a[0][ks][3], ob[2 * ks], ob[2 * ks + 1]);
                    mma16816v(c1, a[1][ks][0], a[1][ks][1], a[1][ks][2], a[1][ks][3], ob[2 * ks], ob[2 * ks + 1]);
                    if (ks == 0 && layer == 0) {
                        mbar_wait(WBAR + 24, 0);
#pragma unroll
                        for (int k = 0; k < 3; k++) ldsm4t(aw + 3 * 12288 + k * 1024, wk[k]);
                    }
                    if (ks == 1) mbar_wait(WBAR + 32, wo4);
                    ldsm4t(aw + 2 * 12288 + ks * 1024, a[0][ks]);
                }
                const uint32_t aw4 = aw + (wo2 && !wo4 ? SM_B - SM_Q : 0) + 4 * 12288;
                ldsm4t(aw4 + 1024, a[1][0]);
#pragma unroll
                for (int ks = 0; ks < 3; ks++) {
                    mma16816v(c2, a[0][ks][0], a[0][ks][1], a[0][ks][2], a[0][ks][3], ob[2 * ks], ob[2 * ks + 1]);
                    mma16816v(c3, wk[ks][0], wk[ks][1], wk[ks][2], wk[ks][3], ob[2 * ks], ob[2 * ks + 1]);
                    if (ks == 0) { ldsm4t(aw4, a[0][0]); put(0, c0); put(1, c1); }
                    if (ks == 1) ldsm4t(aw4 + 2048, a[0][1]);
                }
                float c4[4] = {0.f, 0.f, 0.f, 0.f}, c5[4] = {0.f, 0.f, 0.f, 0.f};
                mma16816v(c4, a[0][0][0], a[0][0][1], a[0][0][2], a[0][0][3], ob[0], ob[1]);
                mma16816v(c5, a[1][0][0], a[1][0][1], a[1][0][2], a[1][0][3], ob[2], ob[3]);
                mma16816v(c4, a[0][1][0], a[0][1][1], a[0][1][2], a[0][1][3], ob[4], ob[5]);
                put(2, c2); put(3, c3);
                c4[0] += c5[0]; c4[2] += c5[2];
                put(4, c4);
            }
        }
        {
            const int tl = opq(tid);
            uint4* pr = opq(&maps.scr->acc[layer][54 * c + min(tl, 53)]);
            const uint32_t fa = opq(SM_R + 48 * tl);
            const float il = rcp(f_(lds32(SM_MISC)));
            __syncthreads();
            if (tl < 54) {
                const float4 v0 = lds128f(fa), v1 = lds128f(fa + 16), v2 = lds128f(fa + 32);
                const float y0 = il * ((v0.x + v0.y) + (v0.z + v0.w)), y1 = il * ((v1.x + v1.y) + (v1.z + v1.w)), y2 = il * ((v2.x + v2.y) + (v2.z + v2.w));
                red_pkt(pr, y0, tl == 53 ? 0.f : y1, tl == 53 ? 0.f : y2);
            }
            if (tl == 224 && layer == 0) {
                sts32(SM_MISC + 4, ticket);
                if (ticket < NG) load_ffn(maps, ticket, SM_B, FBAR);
            }
        }
        __syncthreads();
        if (layer == 0) role = __shfl_sync(0xffffffffu, (int)lds32(SM_MISC + 4), 0);
        const uint32_t DONE32 = 0x42000000u;
        if (role < NG) {
            const int tl = opq(tid), warp = tl >> 5, lane = tl & 31, g = lane >> 2, t = lane & 3, mat = lane >> 3, r8 = lane & 7;
            const uint32_t ag = SM_B + (80 * warp + (mat >> 1) * 8 + r8) * 96 + (((mat & 1) ^ (r8 >> 2)) << 4);
            constexpr int GI = 32, GK = 16 * 96;
            const bool on = (g & 1) == (t >> 1), isx = (on && g < 2) || g == 4;
            const uint32_t pm = opq(isx ? SM_XS + 160 * warp + 16 * t : (on || g == 5 ? SM_ONE : SM_ZERO)), pm2 = opq(pm + 128 - (isx ? 8 * t : 0));
            const uint32_t dg = opq(SM_R + 4 * (2 * (warp * 48 + g) + t));
            const uint32_t ho = pin(16u * (role * 8 + 4 * warp + ((lane * 11) >> 5)));
            const uint32_t fa = pin(SM_R + 8 * (24 * warp + 2 * min(lane, 11)));
            uint32_t pre[9][4];
            {
                bool hx = wu == 7;
                int it = 0;
                const uint4* px = opq(&maps.scr->acc[layer][min(tl, 215)]);
                const int cq = tl / 54, r = tl - 54 * cq, k0 = min(160 * cq + 3 * r, DM - 1);
                const uint32_t w0 = SM_XS + 4 * xpos(k0 >> 1), w1 = SM_XS + 4 * xpos(min((k0 >> 1) + 1, DM / 2 - 1));
                const bool two = tl < 216 && r != 53;
                const uint32_t e0 = opq(tl < 216 ? w0 + 2 * (k0 & 1) : SM_MISC + 12);
                const uint32_t e1 = opq(two ? ((k0 & 1) ? w1 : w0 + 2) : SM_MISC + 12), e2 = opq(two ? w1 + 2 * (k0 & 1) : SM_MISC + 12);
                const uint32_t x01 = opq(lds16(e0) | (lds16(e1) << 16)), x2 = lds16(e2);
                auto take_x = [&](const uint4 v) {
                    if (__all_sync(0xffffffffu, v.w == DONE32)) {
                        hx = true;
                        const uint32_t y01 = add2(x01, pack2(f_(v.x), f_(v.y))), y2 = add2(x2, pack2(f_(v.z), 0.f));
                        sts16(e0, y01); sts16(e1, y01 >> 16); sts16(e2, y2);
                    }
                };
                while (!mbar_test(FBAR, 0) && ++it < SPIN_CAP) { if (!hx) take_x(ld_pkt(px)); }
                uint4 v = make_uint4(0u, 0u, 0u, 0u);
                if (!hx) v = ld_pkt(px);
#pragma unroll
                for (int n = 0; n < 9; n++) ldsm4t(ag + (n % 3) * GI + (n / 3) * GK, pre[n]);
                if (layer) {
#pragma unroll
                    for (int n = 9; n < 15; n++) ldsm4t(ag + (n % 3) * GI + (n / 3) * GK, kr[n - 9]);
                }
                if (!hx) {
                    bool more = true;
                    while (!__all_sync(0xffffffffu, v.w == DONE32) && more) { v = ld_pkt(px); more = ++it < SPIN_CAP; }
                    const uint32_t y01 = add2(x01, pack2(f_(v.x), f_(v.y))), y2 = add2(x2, pack2(f_(v.z), 0.f));
                    sts16(e0, y01); sts16(e1, y01 >> 16); sts16(e2, y2);
                }
            }
            __syncthreads();
            {
                float cc[3][4], gr[4];
                if (layer) gemv15r(cc, gr, pre, kr, pm, pm2);
                else gemv15<GK, true>(cc, gr, pre, [&](int i) { return ag + i * GI; }, pm, pm2);
                if (t < 2) {
#pragma unroll
                    for (int i = 0; i < 3; i++) { sts32(dg + 128 * i, cc[i][0] + cc[i][3]); sts32(dg + 128 * i + 64, cc[i][1] + cc[i][2]); }
                }
                if ((lane | 4) == 22) sts32(SM_ST + 8 * warp + (g & 1) * 4, gr[0]);
            }
            uint4* ph = reinterpret_cast<uint4*>(reinterpret_cast<char*>(maps.scr->ah) + ho);
            const bool snd = (0x249 >> lane) & 1;
            __syncthreads();
            if (wu < 2) {
                float mean, inv;
                float4 v[8];
#pragma unroll
                for (int w = 0; w < 8; w++) v[w] = lds128f(fa + w * 384);
                ln_stats(mean, inv);
                const float ga = inv * ((((v[0].x + v[1].x) + (v[2].x + v[3].x)) + ((v[4].x + v[5].x) + (v[6].x + v[7].x))) -
                                        mean * (((v[0].y + v[1].y) + (v[2].y + v[3].y)) + ((v[4].y + v[5].y) + (v[6].y + v[7].y))));
                const float gb = inv * ((((v[0].z + v[1].z) + (v[2].z + v[3].z)) + ((v[4].z + v[5].z) + (v[6].z + v[7].z))) -
                                        mean * (((v[0].w + v[1].w) + (v[2].w + v[3].w)) + ((v[4].w + v[5].w) + (v[6].w + v[7].w))));
                uint32_t wd = pack2(ga, gb);
                if (role < NG / 2) {
                    const float g0 = bf_lo(wd), g1 = bf_hi(wd);
                    wd = pack2(g0 * rcp(1.0f + ex2(-1.4426950408889634f * g0)), g1 * rcp(1.0f + ex2(-1.4426950408889634f * g1)));
                }
                const uint32_t wa = __shfl_down_sync(0xffffffffu, wd, 1), wb = __shfl_down_sync(0xffffffffu, wd, 2);
                if (snd) st_pkt(ph, wd, wa, wb, tag);
            }
            __syncthreads();
        } else if (role < DN0 + NDN) {
            const int j = role - DN0;
            const int tl = opq(tid), warp = tl >> 5, lane = tl & 31, g = lane >> 2, t = lane & 3, mat = lane >> 3, r8 = lane & 7;
            float xr0 = 0.f, xr1 = 0.f;
            if (wu == 0) {
                const int col = 16 * j + (lane & 15), cc = col / 160, r = col - 160 * cc, e = r % 3;
                const uint4* px = &maps.scr->acc[layer][(54 * cc + r / 3)];
                const float x0 = bf_lo(lds16(SM_XS + 4 * xpos(col >> 1) + 2 * (col & 1)));
                uint4 v;
                int it = 0;
                bool ld = layer == 0;
                do {
                    v = ld_pkt(px);
                    if (ld && f_(__shfl_sync(0xffffffffu, v.w, 0)) >= (float)DNTH) { ld = false; if (lane == 0) load_ffn(maps, role, SM_B, FBAR); }
                } while (!__all_sync(0xffffffffu, v.w == DONE32) && ++it < SPIN_CAP);
                if (ld && lane == 0) load_ffn(maps, role, SM_B, FBAR);
                const float xres = bfr(x0 + bfr(f_(e == 0 ? v.x : (e == 1 ? v.y : v.z))));
                xr0 = __shfl_sync(0xffffffffu, xres, 2 * (lane & 7));
                xr1 = __shfl_sync(0xffffffffu, xres, 2 * (lane & 7) + 1);
            }
            const uint32_t ad = SM_B + (192 * warp + (mat >> 1) * 8 + r8) * 32 + (((mat & 1) ^ (r8 >> 2)) << 4);
            const uint32_t hs = SM_R + 384 * warp, hb = opq(hs + 16 * t), dd = opq(SM_R + 3072 + 4 * (warp * 16 + g));
            uint32_t pre[NPRE][4];
            uint32_t pos[3];
#pragma unroll
            for (int i = 0; i < 3; i++) { const int w = 3 * lane + i; pos[i] = opq(hs + 4 * ((w & ~15) + 4 * (w & 3) + ((w >> 2) & 1) + ((w >> 2) & 2))); }
            const uint4* ph = opq(&maps.scr->ah[tl]);
            const uint32_t fa = opq(SM_R + 3072 + 8 * (lane & 7));
            uint2* py = opq(reinterpret_cast<uint2*>(maps.scr->ay) + 8 * j + (lane & 7));
            uint32_t* po = opq(reinterpret_cast<uint32_t*>(out) + 8 * j + (lane & 7));
            mbar_wait(FBAR, 0);
#pragma unroll
            for (int n = 0; n < NPRE; n++) ldsm4t(ad + n * 512, pre[n]);
            {
                uint4 v, u;
                int it = 0;
                bool more;
                do { v = ld_pkt(ph); u = ld_pkt(ph + 256); more = ++it < SPIN_CAP; }
                while (!__all_sync(0xffffffffu, v.w == tag && u.w == tag) && more);
                sts32(pos[0], mul2(v.x, u.x)); sts32(pos[1], mul2(v.y, u.y)); sts32(pos[2], mul2(v.z, u.z));
            }
            __syncwarp();
            {
                float cc[4][4];
                uint32_t hv[3][4];
#pragma unroll
                for (int jj = 0; jj < 3; jj++) lds128(hb + 64 * jj, hv[jj][0], hv[jj][1], hv[jj][2], hv[jj][3]);
#pragma unroll
                for (int n = 0; n < 12; n++) {
                    const int s = n < NPRE ? n : n - NPRE;
                    if (n < 4) cc[n][0] = cc[n][1] = cc[n][2] = cc[n][3] = 0.f;
                    mma16816v(cc[n & 3], pre[s][0], pre[s][1], pre[s][2], pre[s][3], hv[(n >> 1) % 3][2 * (n & 1)], hv[(n >> 1) % 3][2 * (n & 1) + 1]);
                    if (n + NPRE < 12) ldsm4t(ad + (n + NPRE) * 512, pre[n]);
                    if ((n & 1) && n < 6) lds128(hb + 64 * ((n >> 1) + 3), hv[n >> 1][0], hv[n >> 1][1], hv[n >> 1][2], hv[n >> 1][3]);
                }
                if (t == 0) { sts32(dd, (cc[0][0] + cc[1][0]) + (cc[2][0] + cc[3][0])); sts32(dd + 32, (cc[0][2] + cc[1][2]) + (cc[2][2] + cc[3][2])); }
            }
            __syncthreads();
            if (tl < 8) {
                float2 v[8];
#pragma unroll
                for (int w = 0; w < 8; w++) v[w] = lds64f(fa + 64 * w);
                const uint32_t y = pack2(((v[0].x + v[1].x) + (v[2].x + v[3].x)) + ((v[4].x + v[5].x) + (v[6].x + v[7].x)),
                                         ((v[0].y + v[1].y) + (v[2].y + v[3].y)) + ((v[4].y + v[5].y) + (v[6].y + v[7].y)));
                const uint32_t wd = pack2(xr0 + bf_lo(y), xr1 + bf_hi(y));
                if (layer) asm volatile("st.global.u32 [%0], %1;" ::"l"(po), "r"(wd) : "memory");
                st_pkt2(py, wd, tag);
            }
            __syncthreads();
        }
    }
}

typedef CUresult (*EncodeFn)(CUtensorMap*, CUtensorMapDataType, cuuint32_t, void*, const cuuint64_t*, const cuuint64_t*, const cuuint32_t*,
                             const cuuint32_t*, CUtensorMapInterleave, CUtensorMapSwizzle, CUtensorMapL2promotion, CUtensorMapFloatOOBfill);

void make_map(EncodeFn enc, CUtensorMap* m, const void* base, int rank, uint64_t d0, uint64_t d1, uint64_t d2, uint64_t s1, uint64_t s2,
              uint32_t b0, uint32_t b1, uint32_t b2, CUtensorMapSwizzle sw, CUtensorMapL2promotion pr = CU_TENSOR_MAP_L2_PROMOTION_NONE) {
    cuuint64_t dims[3] = {d0, d1, d2};
    cuuint64_t strides[2] = {s1, s2};
    cuuint32_t box[3] = {b0, b1, b2};
    cuuint32_t es[3] = {1, 1, 1};
    enc(m, CU_TENSOR_MAP_DATA_TYPE_BFLOAT16, rank, const_cast<void*>(base), dims, strides, box, es, CU_TENSOR_MAP_INTERLEAVE_NONE, sw,
        pr, CU_TENSOR_MAP_FLOAT_OOB_FILL_NONE);
}

}

extern "C" void kernel_launch(void* const* d_in, const int* in_sizes, int n_in, void* d_out, int out_size) {
    (void)in_sizes; (void)n_in; (void)out_size;
    static EncodeFn enc = nullptr;
    static Scratch* scr = nullptr;
    if (!enc) {
        void* fn = nullptr;
        cudaDriverEntryPointQueryResult qr;
        cudaGetDriverEntryPoint("cuTensorMapEncodeTiled", &fn, cudaEnableDefault, &qr);
        enc = reinterpret_cast<EncodeFn>(fn);
        cudaGetSymbolAddress(reinterpret_cast<void**>(&scr), g_scr);
        cudaFuncSetAttribute(decode_kernel, cudaFuncAttributeMaxDynamicSharedMemorySize, SM_TOTAL);
    }
    Maps maps;
    make_map(enc, &maps.k, d_in[1], 2, 64, (uint64_t)NH * SK * 3, 1, 128, 0, 64, 48, 1, CU_TENSOR_MAP_SWIZZLE_128B);
    make_map(enc, &maps.v, d_in[2], 2, 64, (uint64_t)NH * SK * 3, 1, 128, 0, 64, 48, 1, CU_TENSOR_MAP_SWIZZLE_128B);
    {
        cuuint64_t dims[5] = {64, 16, NH * DH / 64, DM / 80, 5};
        cuuint64_t strides[4] = {NH * DH * 2, 128, 80 * NH * DH * 2, 16 * NH * DH * 2};
        cuuint32_t box[5] = {64, 16, 3, 2, 5};
        cuuint32_t es[5] = {1, 1, 1, 1, 1};
        enc(&maps.wq, CU_TENSOR_MAP_DATA_TYPE_BFLOAT16, 5, d_in[3], dims, strides, box, es, CU_TENSOR_MAP_INTERLEAVE_NONE, CU_TENSOR_MAP_SWIZZLE_128B,
            CU_TENSOR_MAP_L2_PROMOTION_NONE, CU_TENSOR_MAP_FLOAT_OOB_FILL_NONE);
    }
    make_map(enc, &maps.wo, d_in[4], 3, 32, NH * DH, DM / 32, DM * 2, 64, 32, 192, 1, CU_TENSOR_MAP_SWIZZLE_64B);
    constexpr int GW = 48;
    make_map(enc, &maps.w1, d_in[6], 3, FF, 160, 4, FF * 2, 160 * FF * 2, GW, 160, 4, CU_TENSOR_MAP_SWIZZLE_NONE);
    make_map(enc, &maps.w3, d_in[7], 3, FF, 160, 4, FF * 2, 160 * FF * 2, GW, 160, 4, CU_TENSOR_MAP_SWIZZLE_NONE);
    make_map(enc, &maps.w2, d_in[8], 3, DM, 256, 6, DM * 2, 256 * DM * 2, 16, 256, 6, CU_TENSOR_MAP_SWIZZLE_32B);
    make_map(enc, &maps.ks, d_in[1], 2, 64, (uint64_t)NH * SK * 3, 1, 128, 0, 16, 48, 1, CU_TENSOR_MAP_SWIZZLE_NONE);
    make_map(enc, &maps.vs, d_in[2], 2, 64, (uint64_t)NH * SK * 3, 1, 128, 0, 16, 48, 1, CU_TENSOR_MAP_SWIZZLE_NONE);
    make_map(enc, &maps.kh, d_in[1], 2, 64, (uint64_t)NH * SK * 3, 1, 128, 0, 64, 24, 1, CU_TENSOR_MAP_SWIZZLE_128B);
    maps.kp = d_in[1];
    maps.vp = d_in[2];
    maps.scr = scr;
    const uint32_t rt[8] = {0x2EE0, 0x35E0, 0x2EE0, 0x35E0, 0x3EE0, 0x35E0, 0x3EE0, 0x35E0};
    for (int i = 0; i < 8; i++) maps.rt[i] = rt[i];
    decode_kernel<<<NCTA, NT, SM_TOTAL, cudaStreamPerThread>>>(maps, (const __nv_bfloat16*)d_in[0], (__nv_bfloat16*)d_out);
}
```

```cpp
#include <cuda_runtime.h>
#include <cuda_bf16.h>
#include <cuda.h>
#include <stdint.h>
#include <math.h>

namespace {

constexpr int DM = 640;
constexpr int NH = 32;
constexpr int DH = 192;
constexpr int SK = 32768;
constexpr int WIN = 4096;
constexpr int FF = 1536;
constexpr int NCTA = 128;
constexpr int NT = 256;
constexpr int TILE = 6144;
constexpr int TS = 48;
constexpr int NG = 64;
constexpr int DN0 = 64;
constexpr int NDN = 40;

constexpr uint32_t SB = 1024;
constexpr uint32_t SM_RING = SB;
constexpr uint32_t SM_B = SM_RING + 8 * 2 * TILE;
constexpr uint32_t SM_Q = SM_B + 61440;
constexpr uint32_t SM_XS = SM_Q + 61440;
constexpr uint32_t SM_R = SM_XS + 1280;
constexpr uint32_t SM_ST = SM_R + 4096;
constexpr uint32_t SM_QS = SM_R + 6272;
constexpr uint32_t SM_OS = SM_QS + 384;
constexpr uint32_t SM_CS = SM_OS + 384;
constexpr uint32_t SM_BAR = SM_CS + 768;
constexpr uint32_t SM_XBAR = SM_BAR + 24 * 8;
constexpr uint32_t SM_MISC = SM_XBAR + 8 * 8;
constexpr uint32_t SM_ONE = SM_MISC + 32;
constexpr uint32_t SM_ZERO = SM_ONE + 160;
constexpr uint32_t SM_KX = SM_ZERO + 160;
constexpr uint32_t SM_TOTAL = SM_KX + 8 * 96 - SB;
constexpr int NEXC = 16;
static_assert(SM_TOTAL <= 232448, "shared memory");
constexpr uint32_t QBAR = SM_BAR + 16 * 8, FBAR = QBAR + 8, WBAR = QBAR + 16, QRDY = QBAR + 56;

constexpr unsigned long long POL_EF = 0x12F0000000000000ull;
constexpr unsigned long long POL_EN = 0x1000000000000000ull;

constexpr int L1R = 3;
constexpr int DNTH = 23;
constexpr int NPRE = 6;
constexpr int SPIN_CAP = 1 << 19;
constexpr uint32_t ONES = 0x3F803F80u;
#define AFTER(x) ((x) & maps.zero)
#define ALL6(a, n) (a[n][0] | a[n + 1][0] | a[n + 2][0] | a[n + 3][0] | a[n + 4][0] | a[n + 5][0])
#define ROW0(w) ((h * SK + (SK - WIN) + c * 1024 + (w) * 128) * 3)

struct Scratch {
    uint4 qx[NCTA * 48];
    uint4 qc[NCTA * 48];
    uint4 cx[NCTA * 56];
    uint4 acc[2][256];
    uint4 ay[256];
    uint4 pad0[256];
    uint4 ah[NG * 8];
    uint2 mx[NH * 32];
    uint32_t ticket[32];
};
__device__ __align__(4096) Scratch g_scr;
struct Maps { CUtensorMap k, v, wq, wo, w1, w3, w2, ks, vs, kh; const void *kp, *vp; Scratch* scr; uint32_t rt[8], zero; };

__device__ __forceinline__ uint32_t smem_u32(const void* p) { return (uint32_t)__cvta_generic_to_shared(p); }
__device__ __forceinline__ void mbar_init(uint32_t bar, uint32_t cnt) {
    asm volatile("mbarrier.init.shared::cta.b64 [%0], %1;" ::"r"(bar), "r"(cnt) : "memory");
}
__device__ __forceinline__ void mbar_expect_tx(uint32_t bar, uint32_t bytes) {
    asm volatile("mbarrier.arrive.expect_tx.shared::cta.b64 _, [%0], %1;" ::"r"(bar), "r"(bytes) : "memory");
}
__device__ __forceinline__ bool mbar_test(uint32_t bar, uint32_t parity) {
    uint32_t done;
    asm volatile("{\n.reg .pred p;\nmbarrier.try_wait.parity.shared::cta.b64 p, [%1], %2;\nselp.u32 %0, 1, 0, p;\n}"
                 : "=r"(done) : "r"(bar), "r"(parity) : "memory");
    return done;
}
__device__ __forceinline__ void mbar_wait(uint32_t bar, uint32_t parity) {
    asm volatile("{\n.reg .pred p;\n.reg .u32 n;\nmov.u32 n, 0;\n"
                 "W: mbarrier.try_wait.parity.shared::cta.b64 p, [%0], %1;\n@p bra D;\n"
                 "add.u32 n, n, 1;\nsetp.lt.u32 p, n, %2;\n@p bra W;\nD:\n}" ::"r"(bar), "r"(parity), "n"(SPIN_CAP) : "memory");
}
__device__ __forceinline__ void tma2d(uint32_t dst, const CUtensorMap* map, int c0, int c1, uint32_t bar, unsigned long long pol) {
    asm volatile("cp.async.bulk.tensor.2d.shared::cluster.global.mbarrier::complete_tx::bytes.L2::cache_hint [%0], [%1, {%3, %4}], [%2], %5;"
                 ::"r"(dst), "l"(map), "r"(bar), "r"(c0), "r"(c1), "l"(pol) : "memory");
}
__device__ __forceinline__ void tma3d(uint32_t dst, const CUtensorMap* map, int c0, int c1, int c2, uint32_t bar, unsigned long long pol) {
    asm volatile("cp.async.bulk.tensor.3d.shared::cluster.global.mbarrier::complete_tx::bytes.L2::cache_hint [%0], [%1, {%3, %4, %5}], [%2], %6;"
                 ::"r"(dst), "l"(map), "r"(bar), "r"(c0), "r"(c1), "r"(c2), "l"(pol) : "memory");
}
__device__ __forceinline__ void tma5d(uint32_t dst, const CUtensorMap* map, int c2, int c3, uint32_t bar, unsigned long long pol) {
    asm volatile("cp.async.bulk.tensor.5d.shared::cluster.global.mbarrier::complete_tx::bytes.L2::cache_hint [%0], [%1, {0, 0, %3, %4, 0}], [%2], %5;"
                 ::"r"(dst), "l"(map), "r"(bar), "r"(c2), "r"(c3), "l"(pol) : "memory");
}
__device__ __forceinline__ void tile_load(uint32_t dst, const CUtensorMap* map, int row, uint32_t bar) {
    asm volatile("{\n.reg .pred p;\nelect.sync _|p, 0xffffffff;\n"
                 "@p mbarrier.arrive.expect_tx.shared::cta.b64 _, [%2], 6144;\n"
                 "@p cp.async.bulk.tensor.2d.shared::cluster.global.mbarrier::complete_tx::bytes.L2::cache_hint [%0], [%1, {0, %3}], [%2], %4;\n}"
                 ::"r"(dst), "l"(map), "r"(bar), "r"(row), "l"(POL_EF) : "memory");
}
__device__ __forceinline__ void half_load(uint32_t dst, const CUtensorMap* map, int row, uint32_t bar, bool first) {
    if (first) asm volatile("{\n.reg .pred p;\nelect.sync _|p, 0xffffffff;\n@p mbarrier.arrive.expect_tx.shared::cta.b64 _, [%0], 6144;\n}" ::"r"(bar) : "memory");
    asm volatile("{\n.reg .pred p;\nelect.sync _|p, 0xffffffff;\n"
                 "@p cp.async.bulk.tensor.2d.shared::cluster.global.mbarrier::complete_tx::bytes.L2::cache_hint [%0], [%1, {0, %3}], [%2], %4;\n}"
                 ::"r"(dst), "l"(map), "r"(bar), "r"(row), "l"(POL_EF) : "memory");
}
__device__ __forceinline__ void tile_keep(const CUtensorMap* map, int row) {
    asm volatile("{\n.reg .pred p;\nelect.sync _|p, 0xffffffff;\n"
                 "@p cp.async.bulk.prefetch.tensor.2d.L2.global.L2::cache_hint [%0, {0, %1}], %2;\n}"
                 ::"l"(map), "r"(row), "l"(POL_EN) : "memory");
}
__device__ __forceinline__ void tile_load_l1(uint32_t dst, const void* base, int row, uint32_t bar, int lane) {
    const char* g = static_cast<const char*>(base) + (size_t)row * 128 + lane * 16;
    const uint32_t s0 = dst + (lane >> 3) * 128 + (((lane & 7) ^ (lane >> 3)) << 4), s1 = s0 ^ 64;
#pragma unroll
    for (int k = 0; k < 12; k++)
        asm volatile("cp.async.ca.shared.global.L2::cache_hint [%0], [%1], 16, %2;" ::"r"(((k & 1) ? s1 : s0) + k * 512), "l"(g + k * 512), "l"(POL_EF) : "memory");
    asm volatile("cp.async.mbarrier.arrive.shared::cta.b64 [%0];" ::"r"(bar) : "memory");
    __syncwarp();
    if (lane == 0) asm volatile("mbarrier.arrive.shared::cta.b64 _, [%0];" ::"r"(bar) : "memory");
}
__device__ __forceinline__ bool elect_one() {
    uint32_t p;
    asm volatile("{\n.reg .pred p;\nelect.sync _|p, 0xffffffff;\nselp.u32 %0, 1, 0, p;\n}" : "=r"(p));
    return p;
}
__device__ __forceinline__ void delay(uint32_t clocks) {
    uint32_t t0, t1;
    asm volatile("mov.u32 %0, %%clock;" : "=r"(t0));
    do asm volatile("mov.u32 %0, %%clock;" : "=r"(t1)); while (t1 - t0 < clocks);
}
__device__ __forceinline__ void lds128(uint32_t addr, uint32_t& a, uint32_t& b, uint32_t& c, uint32_t& d) {
    asm volatile("ld.shared.v4.u32 {%0,%1,%2,%3}, [%4];" : "=r"(a), "=r"(b), "=r"(c), "=r"(d) : "r"(addr) : "memory");
}
__device__ __forceinline__ void lds64(uint32_t addr, uint32_t& a, uint32_t& b) {
    asm volatile("ld.shared.v2.u32 {%0,%1}, [%2];" : "=r"(a), "=r"(b) : "r"(addr) : "memory");
}
__device__ __forceinline__ void ldsm4t(uint32_t addr, uint32_t (&a)[4]) {
    asm volatile("ldmatrix.sync.aligned.m8n8.x4.trans.shared.b16 {%0,%1,%2,%3}, [%4];" : "=r"(a[0]), "=r"(a[1]), "=r"(a[2]), "=r"(a[3]) : "r"(addr) : "memory");
}
__device__ __forceinline__ void mma16816(float (&c)[4], uint32_t a0, uint32_t a1, uint32_t a2, uint32_t a3, uint32_t b0, uint32_t b1) {
    asm("mma.sync.aligned.m16n8k16.row.col.f32.bf16.bf16.f32 {%0,%1,%2,%3}, {%4,%5,%6,%7}, {%8,%9}, {%0,%1,%2,%3};"
        : "+f"(c[0]), "+f"(c[1]), "+f"(c[2]), "+f"(c[3]) : "r"(a0), "r"(a1), "r"(a2), "r"(a3), "r"(b0), "r"(b1));
}
__device__ __forceinline__ void mma16816v(float (&c)[4], uint32_t a0, uint32_t a1, uint32_t a2, uint32_t a3, uint32_t b0, uint32_t b1) {
    asm volatile("mma.sync.aligned.m16n8k16.row.col.f32.bf16.bf16.f32 {%0,%1,%2,%3}, {%4,%5,%6,%7}, {%8,%9}, {%0,%1,%2,%3};"
        : "+f"(c[0]), "+f"(c[1]), "+f"(c[2]), "+f"(c[3]) : "r"(a0), "r"(a1), "r"(a2), "r"(a3), "r"(b0), "r"(b1));
}
__device__ __forceinline__ int xpos(int w) {
    const int seg = w / 40, r = w - 40 * seg;
    return 40 * seg + (r < 32 ? (r & 16) + 4 * (r & 3) + ((r >> 2) & 3) : 32 + 2 * (r & 3) + ((r >> 2) & 1));
}
__device__ __forceinline__ void st_pkt(uint4* p, uint32_t a, uint32_t b, uint32_t c, uint32_t d) {
    asm volatile("{\n.reg .b128 t;\n.reg .b64 lo, hi;\nmov.b64 lo, {%1,%2};\nmov.b64 hi, {%3,%4};\nmov.b128 t, {lo,hi};\nst.relaxed.gpu.global.b128 [%0], t;\n}"
                 ::"l"(p), "r"(a), "r"(b), "r"(c), "r"(d) : "memory");
}
__device__ __forceinline__ void st_pktf(uint4* p, float a, float b, float c, float d, uint32_t bit) {
    st_pkt(p, __float_as_uint(a), __float_as_uint(b), __float_as_uint(c), (__float_as_uint(d) & ~1u) | bit);
}
__device__ __forceinline__ void red_pkt(uint4* p, float a, float b, float c) {
    asm volatile("red.relaxed.gpu.global.add.v4.f32 [%0], {%1,%2,%3,%4};" ::"l"(p), "f"(a), "f"(b), "f"(c), "f"(1.0f) : "memory");
}
__device__ __forceinline__ uint4 ld_pkt(const uint4* p) {
    uint4 v;
    asm volatile("{\n.reg .b128 t;\n.reg .b64 lo, hi;\nld.relaxed.gpu.global.b128 t, [%4];\nmov.b128 {lo,hi}, t;\nmov.b64 {%0,%1}, lo;\nmov.b64 {%2,%3}, hi;\n}"
                 : "=r"(v.x), "=r"(v.y), "=r"(v.z), "=r"(v.w) : "l"(p) : "memory");
    return v;
}
__device__ __forceinline__ uint2 ld_pkt2(const uint2* p) {
    unsigned long long v;
    asm volatile("ld.relaxed.gpu.global.b64 %0, [%1];" : "=l"(v) : "l"(p) : "memory");
    return make_uint2((uint32_t)v, (uint32_t)(v >> 32));
}
__device__ __forceinline__ void st_pkt2(uint2* p, uint32_t a, uint32_t b) {
    asm volatile("st.relaxed.gpu.global.b64 [%0], %1;" ::"l"(p), "l"((unsigned long long)a | ((unsigned long long)b << 32)) : "memory");
}
__device__ __forceinline__ float ex2(float x) { float y; asm("ex2.approx.ftz.f32 %0, %1;" : "=f"(y) : "f"(x)); return y; }
__device__ __forceinline__ float rcp(float x) { float y; asm("rcp.approx.ftz.f32 %0, %1;" : "=f"(y) : "f"(x)); return y; }
__device__ __forceinline__ uint32_t pack2(float lo, float hi) {
    uint32_t r; asm("cvt.rn.bf16x2.f32 %0, %1, %2;" : "=r"(r) : "f"(hi), "f"(lo)); return r;
}
__device__ __forceinline__ float bf_lo(uint32_t w) { return __uint_as_float(w << 16); }
__device__ __forceinline__ float bf_hi(uint32_t w) { return __uint_as_float(w & 0xffff0000u); }
__device__ __forceinline__ float bfr(float x) { return bf_lo(pack2(x, 0.f)); }
__device__ __forceinline__ float f_(uint32_t u) { return __uint_as_float(u); }

__device__ __forceinline__ uint32_t add2(uint32_t a, uint32_t b) { uint32_t r; asm("add.rn.bf16x2 %0, %1, %2;" : "=r"(r) : "r"(a), "r"(b)); return r; }
__device__ __forceinline__ uint32_t mul2(uint32_t a, uint32_t b) { uint32_t r; asm("mul.rn.bf16x2 %0, %1, %2;" : "=r"(r) : "r"(a), "r"(b)); return r; }
__device__ __forceinline__ uint32_t f2key(float f) { const uint32_t u = __float_as_uint(f); return u ^ ((uint32_t)((int)u >> 31) | 0x80000000u); }
__device__ __forceinline__ float key2f(uint32_t k) { return __uint_as_float(k ^ ((uint32_t)((int)~k >> 31) | 0x80000000u)); }
__device__ __forceinline__ float4 lds128f(uint32_t a) {
    float4 v; asm volatile("ld.shared.v4.f32 {%0,%1,%2,%3}, [%4];" : "=f"(v.x), "=f"(v.y), "=f"(v.z), "=f"(v.w) : "r"(a) : "memory"); return v;
}
__device__ __forceinline__ float2 lds64f(uint32_t a) { float2 v; asm volatile("ld.shared.v2.f32 {%0,%1}, [%2];" : "=f"(v.x), "=f"(v.y) : "r"(a) : "memory"); return v; }
__device__ __forceinline__ uint32_t lds32(uint32_t a) { uint32_t v; asm volatile("ld.shared.u32 %0, [%1];" : "=r"(v) : "r"(a) : "memory"); return v; }
__device__ __forceinline__ uint32_t lds16(uint32_t a) { uint32_t v; asm volatile("ld.shared.u16 %0, [%1];" : "=r"(v) : "r"(a) : "memory"); return v; }
__device__ __forceinline__ void sts16(uint32_t a, uint32_t v) { asm volatile("st.shared.u16 [%0], %1;" ::"r"(a), "r"(v) : "memory"); }
__device__ __forceinline__ void sts32(uint32_t a, uint32_t v) { asm volatile("st.shared.u32 [%0], %1;" ::"r"(a), "r"(v) : "memory"); }
__device__ __forceinline__ void sts32(uint32_t a, float v) { asm volatile("st.shared.f32 [%0], %1;" ::"r"(a), "f"(v) : "memory"); }
__device__ __forceinline__ void sts128(uint32_t a, float x, float y, float z, float w) {
    asm volatile("st.shared.v4.f32 [%0], {%1,%2,%3,%4};" ::"r"(a), "f"(x), "f"(y), "f"(z), "f"(w) : "memory");
}
template <int N> struct IC { static constexpr int value = N; };
__device__ __forceinline__ int opq(int x) { asm volatile("" : "+r"(x)); return x; }
__device__ __forceinline__ uint32_t opq(uint32_t x) { asm volatile("" : "+r"(x)); return x; }
__device__ __forceinline__ uint32_t pin(uint32_t x) { x = opq(x); sts32(SM_MISC + 12, x); return x; }
__device__ __forceinline__ float pin(float x) { sts32(SM_MISC + 12, x); return x; }
template <typename T> __device__ __forceinline__ T* pin(T* p) {
    asm volatile("{\n.reg .b32 lo, hi;\nmov.b64 {lo, hi}, %0;\nst.shared.v2.b32 [%1], {lo, hi};\n}" : "+l"(p) : "r"(SM_MISC + 16) : "memory");
    return p;
}
template <typename T> __device__ __forceinline__ T* opq(T* p) { asm volatile("" : "+l"(p)); return p; }

__device__ __forceinline__ void ln_finish(float s1, float s2, float& mean, float& inv) {
    const float md = s1 * (1.0f / DM);
    const float var = fmaxf(s2 * (1.0f / DM) - md * md, 0.f);
    mean = bfr(md);
    asm("rsqrt.approx.ftz.f32 %0, %1;" : "=f"(inv) : "f"(var + 1e-5f));
}
__device__ __forceinline__ void ln_stats(float& mean, float& inv) {
    const float4 a = lds128f(SM_ST), b = lds128f(SM_ST + 16), c = lds128f(SM_ST + 32), d = lds128f(SM_ST + 48);
    ln_finish(((a.y + a.w) + (b.y + b.w)) + ((c.y + c.w) + (d.y + d.w)), ((a.x + a.z) + (b.x + b.z)) + ((c.x + c.z) + (d.x + d.z)), mean, inv);
}
template <int SK, bool GRAM, typename AddrF>
__device__ __forceinline__ void gemv15(float (&cc)[3][4], float (&gr)[4], uint32_t (&pre)[9][4], AddrF ad, uint32_t px, uint32_t px2) {
    uint32_t x0[4], x1[4];
    lds128(px, x0[0], x0[1], x0[2], x0[3]);
    lds128(px + 64, x1[0], x1[1], x1[2], x1[3]);
    gr[0] = gr[1] = gr[2] = gr[3] = 0.f;
#pragma unroll
    for (int i = 0; i < 3; i++) {
        cc[i][0] = cc[i][1] = cc[i][2] = cc[i][3] = 0.f;
        mma16816v(cc[i], pre[i][0], pre[i][1], pre[i][2], pre[i][3], x0[0], x0[1]);
    }
#pragma unroll
    for (int i = 0; i < 3; i++) ldsm4t(ad(i) + 3 * SK, pre[i]);
    if (GRAM) mma16816v(gr, x0[0], 0u, x0[1], 0u, x0[0], x0[1]);
#pragma unroll
    for (int i = 0; i < 3; i++) mma16816v(cc[i], pre[3 + i][0], pre[3 + i][1], pre[3 + i][2], pre[3 + i][3], x0[2], x0[3]);
#pragma unroll
    for (int i = 0; i < 3; i++) ldsm4t(ad(i) + 4 * SK, pre[3 + i]);
    lds64(px2, x0[0], x0[1]);
    if (GRAM) mma16816v(gr, x0[2], 0u, x0[3], 0u, x0[2], x0[3]);
#pragma unroll
    for (int i = 0; i < 3; i++) mma16816v(cc[i], pre[6 + i][0], pre[6 + i][1], pre[6 + i][2], pre[6 + i][3], x1[0], x1[1]);
    if (GRAM) mma16816v(gr, x1[0], 0u, x1[1], 0u, x1[0], x1[1]);
#pragma unroll
    for (int i = 0; i < 3; i++) mma16816v(cc[i], pre[i][0], pre[i][1], pre[i][2], pre[i][3], x1[2], x1[3]);
    if (GRAM) mma16816v(gr, x1[2], 0u, x1[3], 0u, x1[2], x1[3]);
    if (GRAM) mma16816v(gr, x0[0], 0u, x0[1], 0u, x0[0], x0[1]);
#pragma unroll
    for (int i = 0; i < 3; i++) mma16816v(cc[i], pre[3 + i][0], pre[3 + i][1], pre[3 + i][2], pre[3 + i][3], x0[0], x0[1]);
}
__device__ __forceinline__ void gemv15r(float (&cc)[3][4], float (&gr)[4], const uint32_t (&pre)[9][4], const uint32_t (&ext)[45][4], uint32_t px, uint32_t px2) {
    uint32_t x0[4], x1[4], x2[2];
    lds128(px, x0[0], x0[1], x0[2], x0[3]);
    lds128(px + 64, x1[0], x1[1], x1[2], x1[3]);
    lds64(px2, x2[0], x2[1]);
    gr[0] = gr[1] = gr[2] = gr[3] = 0.f;
#pragma unroll
    for (int ks = 0; ks < 5; ks++) {
        const uint32_t b0 = ks < 2 ? x0[2 * (ks & 1)] : ks < 4 ? x1[2 * (ks & 1)] : x2[0], b1 = ks < 2 ? x0[2 * (ks & 1) + 1] : ks < 4 ? x1[2 * (ks & 1) + 1] : x2[1];
        mma16816v(gr, b0, 0u, b1, 0u, b0, b1);
#pragma unroll
        for (int i = 0; i < 3; i++) {
            if (ks == 0) cc[i][0] = cc[i][1] = cc[i][2] = cc[i][3] = 0.f;
            const uint32_t (&f)[4] = ks < 3 ? pre[ks < 3 ? 3 * ks + i : 0] : ext[ks < 3 ? 0 : 3 * (ks - 3) + i];
            mma16816v(cc[i], f[0], f[1], f[2], f[3], b0, b1);
        }
    }
}

__device__ __forceinline__ void load_ffn(const Maps& maps, int b, uint32_t dst, uint32_t bar) {
    const bool gu = b < NG;
    mbar_expect_tx(bar, gu ? 61440 : 49152);
    tma3d(dst, gu ? (b < NG / 2 ? &maps.w1 : &maps.w3) : &maps.w2, gu ? 48 * (b & (NG / 2 - 1)) : 16 * (b - DN0), 0, 0, bar, POL_EF);
}

__device__ __forceinline__ void load_wo(const Maps& maps, uint32_t dst, int h, int c, uint32_t bar, int nbox) {
#pragma unroll 1
    for (int i = 0; i < nbox; i++) {
        mbar_expect_tx(bar + 8 * i, 12288);
        tma3d(dst + i * 12288, &maps.wo, 0, h * DH, 5 * c + i, bar + 8 * i, POL_EF);
    }
}

__global__ void __launch_bounds__(NT, 1)
decode_kernel(const __grid_constant__ Maps maps, const __nv_bfloat16* __restrict__ x_in, __nv_bfloat16* __restrict__ out) {
    extern __shared__ __align__(1024) unsigned char smem[];
    const int tid = threadIdx.x;
    const int wu = __shfl_sync(0xffffffffu, tid >> 5, 0);
    const int b = blockIdx.x, h = b >> 2, c = b & 3;
    if (smem_u32(smem) != SB) return;

    {
        const int warp = tid >> 5, lane = tid & 31;
        const uint32_t rbar = SM_BAR + warp * 16;
        if (lane == 0) {
            if (warp == 0) {
                mbar_init(QBAR, 1);
                asm volatile("fence.mbarrier_init.release.cluster;" ::: "memory");
                mbar_expect_tx(QBAR, 61440);
                tma5d(SM_Q, &maps.wq, 3 * h, 2 * c, QBAR, POL_EF);
            }
            mbar_init(rbar, 1); mbar_init(rbar + 8, 1); mbar_init(SM_XBAR + warp * 8, 1);
            mbar_init(FBAR + 8 * max(warp - 1, 0), warp == 7 ? 2 : 1);
            asm volatile("fence.mbarrier_init.release.cluster;" ::: "memory");
            if (warp >= 1 && warp < 7) {
                const CUtensorMap* mp = warp == 1 ? &maps.k : warp == 2 ? &maps.v : warp == 3 ? &maps.wo : warp == 4 ? &maps.w1 : warp == 5 ? &maps.w3 : &maps.w2;
                asm volatile("prefetch.tensormap [%0];" ::"l"(mp) : "memory");
            }
        }
        if (tid == 96) sts32(SM_MISC + 8, 0u);
        if (lane < 2) sts32(SM_KX + warp * 96 + 4 * lane, 0u);
        if (tid >= 128 && tid < 148) {
            const float v = f_(tid < 138 ? ONES : 0u);
            sts128(SM_ONE + 16 * (tid - 128), v, v, v, v);
        }
        if (b == 0 && tid == 255) asm volatile("st.relaxed.gpu.global.u32 [%0], %1;" ::"l"(maps.scr->ticket), "r"(0) : "memory");
        if (tid < 4) st_pkt(reinterpret_cast<uint4*>(&maps.scr->mx[h * 32 + c * 8]) + tid, 0, 0, 0, 0);
        if (tid >= 64 && tid < 66 && b < 108) st_pkt(&maps.scr->acc[1][(2 * b + tid - 64)], 0, 0, 0, 0);
        __syncthreads();
        if (lane == 0) {
            const int row = ROW0(warp);
            mbar_expect_tx(rbar, TILE);
            tma2d(SM_RING + warp * 2 * TILE, &maps.k, 0, row, rbar, POL_EF);
            mbar_expect_tx(rbar + 8, TILE);
            tma2d(SM_RING + (warp * 2 + 1) * TILE, &maps.k, 0, row + TS, rbar + 8, POL_EF);
        }
    }

    uint32_t kr[45][4];
#define KR(n) kr[(n) >> 2][(n) & 3]
    const float SC = 0.07216878364870322f * 1.4426950408889634f;
    int role = 0;
    uint32_t wk[3][4];

#pragma unroll 1
    for (int layer = 0; layer < 2; layer++) {
        const uint32_t tag = layer + 1, tbit = layer ^ 1;
        uint2 xv = make_uint2(0u, 0u);
        uint32_t qo;
        {
            const int tl = opq(tid), warp = tl >> 5, lane = tl & 31, g = lane >> 2, t = lane & 3, mat = lane >> 3, r8 = lane & 7;
            const int kh = warp >> 2, mg = warp & 3;
            const uint32_t aq = SM_Q + kh * TILE + ((mat >> 1) * 8 + r8) * 128 + (((2 * mg + (mat & 1)) ^ r8) << 4);
            if (layer == 0 && tl < 160) xv = reinterpret_cast<const uint2*>(x_in)[tl];
            mbar_wait(QBAR, 0);
            uint32_t pre[9][4];
#pragma unroll
            for (int n = 0; n < 9; n++) ldsm4t(aq + (n % 3) * 2048 + (n / 3) * 2 * TILE, pre[n]);
            if (layer == 1) {
                pin(ALL6(pre, 0) | ALL6(pre, 3));
                __syncthreads();
                delay(role >= DN0 + NDN ? 1500 : 0);
                if (role >= DN0 && role < DN0 + NDN) {
                    if (wu < 6) tile_load(SM_Q + wu * TILE, &maps.k, ROW0(wu) + 5 * TS, SM_XBAR + wu * 8);
                } else if (wu == 7) {
#pragma unroll 1
                    for (int w = 0; w < 6; w++) tile_load(SM_Q + w * TILE, &maps.k, ROW0(w) + 5 * TS, SM_XBAR + w * 8);
                }
            }
            const uint32_t pm = opq(g == 1 ? SM_ONE : SM_XS + 160 * (2 * c + kh) + 16 * t);
            const uint32_t pm2 = opq(pm + 128 - (g == 1 ? 0 : 8 * t));
            const uint32_t dq = opq(SM_R + 768 * kh + 4 * (16 * mg + g));
            qo = pin(16u * (b * 48 + (tl & 63) + (tl >= 64 ? NCTA * 48 : 0)));
            if (tl < 160) {
                const uint32_t xa0 = opq(SM_XS + 4 * xpos(2 * tl));
                const bool xl = tl % 20 < 16;
                if (layer == 1) {
                    const uint4* px = opq(&maps.scr->ay[tl]);
                    uint4 v;
                    int it = 0;
                    bool more;
                    do { v = ld_pkt(px); more = ++it < SPIN_CAP; } while (!__all_sync(0xffffffffu, (v.y & v.w) == 1) && more);
                    xv = make_uint2(v.x, v.z);
                }
                sts32(xa0, xv.x);
                if (xl) sts32(xa0 + 16, xv.y); else sts32(xa0 + 8, xv.y);
            }
            __syncthreads();
            float cc[3][4], gr[4];
            gemv15<2 * TILE, false>(cc, gr, pre, [&](int i) { return aq + i * 2048; }, pm, pm2);
            if (t == 0) {
#pragma unroll
                for (int i = 0; i < 3; i++) { sts32(dq + 256 * i, cc[i][0]); sts32(dq + 256 * i + 32, cc[i][2]); }
                if (layer == 0) {
#pragma unroll
                    for (int i = 0; i < 3; i++) { sts32(dq + 256 * i + 1536, cc[i][1]); sts32(dq + 256 * i + 1568, cc[i][3]); }
                }
            }
        }
        {
            const int tl = opq(tid), j = tl & 63;
            const bool snd = j < 48 && (tl < 64 || (tl < 128 && layer == 0));
            const uint32_t fa = opq(SM_R + 16 * tl + (tl >= 64 ? 512 : 0));
            uint4* pq = reinterpret_cast<uint4*>(reinterpret_cast<char*>(maps.scr->qx) + qo);
            __syncthreads();
            if (snd) {
                const float4 u = lds128f(fa), v = lds128f(fa + 768);
                st_pktf(pq, u.x + v.x, u.y + v.y, u.z + v.z, u.w + v.w, tbit);
            }
            if (layer == 1 && wu >= 5) {
                delay(300);
                if (wu >= 6) tile_load(SM_Q + wu * TILE, &maps.k, ROW0(wu) + 5 * TS, SM_XBAR + wu * 8);
                else if (role < NG && elect_one()) {
                    mbar_expect_tx(WBAR + 32, 12288);
                    tma3d(SM_Q + 4 * 12288, &maps.wo, 0, h * DH, 5 * c + 4, WBAR + 32, POL_EF);
                }
            }
            if (layer == 1 && tl >= 192 && tl < 194 && b < 108) st_pkt(&maps.scr->acc[0][(2 * b + tl - 192)], 0, 0, 0, 0);
        }

        float sc0 = -INFINITY, sc1 = -INFINITY, sc2 = 0.f, sc3 = 0.f, mw;
        uint32_t pk0, pk1;
        float acc[3][4];
        {
            const uint32_t ring = SM_RING + wu * 2 * TILE, rb = SM_BAR + wu * 16;
            const uint32_t xtile = SM_Q + wu * TILE, xb = SM_XBAR + wu * 8;
            const int row0 = ROW0(wu);
            const uint32_t bt = SM_B + wu * TILE;
            auto issue1 = [&](int n, uint32_t dep, bool vph) {
                const CUtensorMap* mp = n < 8 ? &maps.k : &maps.v;
                const int row = row0 + ((n + (n >= 8 ? 2 : 0)) & 7) * TS;
                if (vph && wu < L1R && n == 12 - (wu & 1)) {
                    tile_load_l1(ring + (n & 1) * TILE, maps.vp, row, rb + (n & 1) * 8, opq(tid) & 31);
                    return;
                }
                const int k = vph || n >= 6 ? n & 1 : n >= 3 ? n - 3 : n;
                tile_load(k == 2 ? bt : ring + k * TILE, mp, row + dep, k == 2 ? xb : rb + k * 8);
                if ((maps.rt[wu] >> n) & 1) tile_keep(n < 8 ? &maps.ks : &maps.vs, row);
            };
            auto refill1 = [&](int s, uint32_t dep, bool vph = false) { issue1(s + 2, dep, vph); };
#define K_OFF(i) ((uint32_t)((3 * ((g >> 1) + 4 * (g & 1)) + ((i) >> 1)) * 128 + ((t ^ ((3 * ((g >> 1) + 4 * (g & 1)) + ((i) >> 1)) & 7) ^ (((i) & 1) << 2)) << 4)))
#define V_OFF(i) ((uint32_t)((6 * t + (i)) * 128 + ((g ^ ((6 * t + (i)) & 7)) << 4)))
#define LANE_IDS const int tl = opq(tid), lane = tl & 31, g = lane >> 2, t = lane & 3; (void)tl; (void)lane; (void)g; (void)t;
            const uint32_t kx = SM_KX + wu * 96;
#pragma unroll 1
            for (int s = layer ? 5 : 0; s < 5 + layer; s++) {
                if (s < 5) {
                    LANE_IDS
                    const int k = s >= 3 ? s - 3 : s;
                    mbar_wait(k == 2 ? xb : rb + k * 8, s >= 3);
                    refill1(s, 0);
                    const uint32_t tile = k == 2 ? bt : ring + k * TILE;
                    uint32_t mx = 0u, mn = 0xffffffffu, mn2 = 0xffffffffu;
#pragma unroll
                    for (int q = 0; q < 12; q++) {
                        uint32_t a0, a1, a2, a3;
                        lds128(tile + K_OFF(q % 6) + (q / 6) * 3072, a0, a1, a2, a3);
                        a0 &= 0x7fff7fffu; a1 &= 0x7fff7fffu; a2 &= 0x7fff7fffu; a3 &= 0x7fff7fffu;
                        mx = __vimax3_u16x2(__vimax3_u16x2(mx, a0, a1), a2, a3);
                        mn = __viaddmin_u16x2(a0, 0xffffffffu, __viaddmin_u16x2(a1, 0xffffffffu, mn));
                        mn2 = __viaddmin_u16x2(a2, 0xffffffffu, __viaddmin_u16x2(a3, 0xffffffffu, mn2));
                    }
                    mn = __vminu2(mn, mn2);
                    const uint32_t emax = __reduce_max_sync(0xffffffffu, max(mx & 0xffffu, mx >> 16)) >> 7;
                    const uint32_t base = (max(emax, 16u) - 15u) << 7, lim = base + 0x7fu;
                    bool raw = emax < 80u || emax > 190u;
                    uint32_t fl = __ballot_sync(0xffffffffu, min(mn & 0xffffu, mn >> 16) < lim);
                    if (!raw && fl) {
                        const uint32_t n0 = lds32(kx);
                        __syncwarp();
#pragma unroll 1
                        for (; fl; fl &= fl - 1) {
                            const int g = (__ffs(fl) - 1) >> 2, t = (__ffs(fl) - 1) & 3, q = min(lane, 23) >> 1, i = q >= 6 ? q - 6 : q;
                            const uint32_t a = tile + K_OFF(i) + (q >= 6 ? 3072 : 0) + 8 * (lane & 1);
                            uint32_t w0, w1;
                            lds64(a, w0, w1);
#pragma unroll 1
                            for (int e = 0; e < 4; e++) {
                                const uint32_t x = __funnelshift_r(w0, w1, 16 * e) & 0xffffu;
                                if (e == 1) w0 = w1;
                                if ((x & 0x7fffu) - 1u < lim && lane < 24) {
                                    uint32_t n;
                                    asm volatile("atom.shared.add.u32 %0, [%1], 1;" : "=r"(n) : "r"(kx) : "memory");
                                    if (n < NEXC) sts32(kx + 32 + 4 * n, x | (2 * ((2 * t + (e >> 1)) * 12 + 2 * i + (lane & 1)) + (e & 1)) << 16 | (16 * s + (q >= 6 ? 8 : 0) + g) << 24);
                                    sts16(a + 2 * e, 0u);
                                }
                            }
                        }
                        __syncwarp();
                        raw = lds32(kx) > NEXC;
                        __syncwarp();
                        if (raw && lane == 0) sts32(kx, n0);
                    }
                    if (lane == 0) {
                        sts32(kx + 8 + 4 * s, (base + (31u << 7)) << 16);
                        if (raw) sts32(kx + 4, lds32(kx + 4) | 1u << s);
                    }
                    const uint32_t b2 = (0x10000u - base) * 0x10001u;
                    auto pack = [&](auto S) {
                        constexpr int n0 = 36 * decltype(S)::value;
#pragma unroll
                        for (int q = 0; q < 12; q++) {
                            uint32_t a0, a1, a2, a3;
                            lds128(tile + K_OFF(q % 6) + (q / 6) * 3072, a0, a1, a2, a3);
                            a0 = __viaddmax_s16x2(a0 & 0x7fff7fffu, b2, 0u) | (a0 & 0x80008000u); a1 = __viaddmax_s16x2(a1 & 0x7fff7fffu, b2, 0u) | (a1 & 0x80008000u);
                            a2 = __viaddmax_s16x2(a2 & 0x7fff7fffu, b2, 0u) | (a2 & 0x80008000u); a3 = __viaddmax_s16x2(a3 & 0x7fff7fffu, b2, 0u) | (a3 & 0x80008000u);
                            KR(n0 + 3 * q) = __byte_perm(a0, a1, 0x6420);
                            KR(n0 + 3 * q + 1) = __byte_perm(a2, a3, 0x6420);
                            const uint32_t ho = __byte_perm(a2, a3, 0x7531);
                            KR(n0 + 3 * q + 2) = __byte_perm(a0, a1, 0x7531) | __funnelshift_r(ho, ho, 4);
                        }
                    };
                    switch (s) {
                        case 0: pack(IC<0>()); break;
                        case 1: pack(IC<1>()); break;
                        case 2: pack(IC<2>()); break;
                        case 3: pack(IC<3>()); break;
                        default: pack(IC<4>()); break;
                    }
                    __syncwarp();
                }
                if (wu < 2 && (s == 3 || layer)) {
                    const int tc = min(opq(tid), 47);
                    const uint4* pq = opq(&maps.scr->qx[h * 4 * 48 + tc]);
                    uint4 v[4];
                    int it = 0;
                    bool more = true;
#pragma unroll
                    for (int k = 0; k < 4; k++) v[k] = ld_pkt(pq + 48 * k);
                    if (layer == 0) {
                        uint4 u[4];
                        do {
#pragma unroll
                            for (int k = 0; k < 4; k++) u[k] = ld_pkt(pq + NCTA * 48 + 48 * k);
                            more = ++it < SPIN_CAP;
                        } while (!__all_sync(0xffffffffu, u[0].w & u[1].w & u[2].w & u[3].w & 1) && more);
                        sts128(SM_CS + 16 * tc, (f_(u[0].x) + f_(u[1].x)) + (f_(u[2].x) + f_(u[3].x)), (f_(u[0].y) + f_(u[1].y)) + (f_(u[2].y) + f_(u[3].y)),
                               (f_(u[0].z) + f_(u[1].z)) + (f_(u[2].z) + f_(u[3].z)), (f_(u[0].w) + f_(u[1].w)) + (f_(u[2].w) + f_(u[3].w)));
                    }
                    float mean, inv;
                    {
                        const int lane = opq(tid) & 31;
                        uint32_t xw[10];
                        lds128(SM_XS + 16 * lane, xw[0], xw[1], xw[2], xw[3]);
                        lds128(SM_XS + 512 + 16 * lane, xw[4], xw[5], xw[6], xw[7]);
                        lds64(SM_XS + 1024 + 8 * lane, xw[8], xw[9]);
                        float s1 = 0.f, s2 = 0.f, s3 = 0.f, s4 = 0.f;
#pragma unroll
                        for (int i = 0; i < 10; i++) { const float e0 = bf_lo(xw[i]), e1 = bf_hi(xw[i]); s1 += e0; s3 += e1; s2 = fmaf(e0, e0, s2); s4 = fmaf(e1, e1, s4); }
                        s1 += s3; s2 += s4;
                        const bool lo = lane < 16;
                        float sv = (lo ? s1 : s2) + __shfl_xor_sync(0xffffffffu, lo ? s2 : s1, 16);
#pragma unroll
                        for (int o = 8; o > 0; o >>= 1) sv += __shfl_xor_sync(0xffffffffu, sv, o);
                        const float so = __shfl_xor_sync(0xffffffffu, sv, 16);
                        ln_finish(lo ? sv : so, lo ? so : sv, mean, inv);
                    }
                    const float4 cs = lds128f(SM_CS + 16 * tc);
                    mean *= -inv;
                    const float m0 = pin(mean * cs.x), m1 = pin(mean * cs.y), m2 = pin(mean * cs.z), m3 = pin(mean * cs.w);
                    const int w = 2 * tc;
                    const uint32_t qd = pin(SM_QS + 4 * (((w >> 2) & 3) * 24 + 2 * (w >> 4) + ((w >> 1) & 1)));
                    while (__any_sync(0xffffffffu, ((v[0].w ^ tbit) | (v[1].w ^ tbit) | (v[2].w ^ tbit) | (v[3].w ^ tbit)) & 1) && more) {
#pragma unroll
                        for (int k = 0; k < 4; k++) v[k] = ld_pkt(pq + 48 * k);
                        more = ++it < SPIN_CAP;
                    }
                    const float q0 = fmaf(inv, (f_(v[0].x) + f_(v[1].x)) + (f_(v[2].x) + f_(v[3].x)), m0), q1 = fmaf(inv, (f_(v[0].y) + f_(v[1].y)) + (f_(v[2].y) + f_(v[3].y)), m1);
                    const float q2 = fmaf(inv, (f_(v[0].z) + f_(v[1].z)) + (f_(v[2].z) + f_(v[3].z)), m2), q3 = fmaf(inv, (f_(v[0].w) + f_(v[1].w)) + (f_(v[2].w) + f_(v[3].w)), m3);
                    sts32(qd, pack2(q0, q1));
                    sts32(qd + 48, pack2(q2, q3));
                    __syncwarp();
                    if (elect_one()) asm volatile("mbarrier.arrive.shared::cta.b64 _, [%0];" ::"r"(QRDY) : "memory");
                }
            }
            uint32_t qa, ka[3];
            {
                LANE_IDS
                qa = opq(SM_QS + (2 * t + (g & 1)) * 48);
#pragma unroll
                for (int i = 0; i < 3; i++) ka[i] = opq(xtile + K_OFF(2 * i));
            }
            uint32_t f[6][4];
            if (layer == 1) {
                if (wu >= 2 && wu < 5) delay(300);
                mbar_wait(xb, 0);
            }
#pragma unroll
            for (int i = 0; i < 6; i++) lds128(ka[i >> 1] ^ ((i & 1) << 6), f[i][0], f[i][1], f[i][2], f[i][3]);
            if (layer == 1) {
                __syncwarp();
                half_load(xtile, &maps.kh, row0 + 6 * TS + AFTER(ALL6(f, 0)), xb, true);
            }
            mbar_wait(QRDY, layer);
            {
                uint32_t qf[12];
#pragma unroll
                for (int i = 0; i < 3; i++) lds128(qa + 16 * i, qf[4 * i], qf[4 * i + 1], qf[4 * i + 2], qf[4 * i + 3]);
                const int t = opq(tid) & 3;
                auto kr_scores = [&](auto TAU, float& sa, float& sb) {
                    constexpr int tau = decltype(TAU)::value;
                    float cc[2][4] = {{0.f, 0.f, 0.f, 0.f}, {0.f, 0.f, 0.f, 0.f}};
#pragma unroll
                    for (int n = 0; n < 12; n++) {
                        const int q = (n & 1) * 6 + (n >> 1), i = n >> 1;
                        const uint32_t l0 = KR(36 * tau + 3 * q), l1 = KR(36 * tau + 3 * q + 1), hh = KR(36 * tau + 3 * q + 2);
                        const uint32_t h0 = hh & 0x87878787u, h1 = __funnelshift_l(hh, hh, 4) & 0x87878787u;
                        mma16816(cc[n & 1], __byte_perm(l0, h0, 0x5140), __byte_perm(l0, h0, 0x7362), __byte_perm(l1, h1, 0x5140), __byte_perm(l1, h1, 0x7362), qf[2 * i], qf[2 * i + 1]);
                    }
                    if (t == (tau & 3)) { sa = cc[0][0] + cc[0][3]; sb = cc[1][0] + cc[1][3]; }
                };
                auto stage_v = [&](auto S) {
                    constexpr int s = decltype(S)::value;
                    const int lane = opq(tid) & 31, g = lane >> 2, t = lane & 3;
#pragma unroll
                    for (int i = 0; i < 6; i++) {
                        const uint32_t a = ring + s * TILE + V_OFF(i);
                        lds128(a, kr[12 * s + i][0], kr[12 * s + i][1], kr[12 * s + i][2], kr[12 * s + i][3]);
                        lds128(a + 3072, kr[12 * s + 6 + i][0], kr[12 * s + 6 + i][1], kr[12 * s + 6 + i][2], kr[12 * s + 6 + i][3]);
                    }
                    __syncwarp();
                    tile_load(ring + s * TILE, s ? &maps.v : &maps.k, row0 + (s ? 2 : 7) * TS + AFTER(ALL6(kr, 12 * s) | ALL6(kr, 12 * s + 6)), rb + s * 8);
                };
                if (layer == 1) {
                    float cA[4] = {0.f, 0.f, 0.f, 0.f}, cB[4] = {0.f, 0.f, 0.f, 0.f};
#pragma unroll
                    for (int i = 0; i < 6; i++) {
                        mma16816v(cA, f[i][0], f[i][1], f[i][2], f[i][3], qf[2 * i], qf[2 * i + 1]);
                        lds128((opq(ka[i >> 1]) ^ ((i & 1) << 6)) + 3072, f[i][0], f[i][1], f[i][2], f[i][3]);
                    }
                    __syncwarp();
                    half_load(xtile + 3072, &maps.kh, row0 + 6 * TS + 24 + AFTER(ALL6(f, 0)), xb, false);
#pragma unroll
                    for (int i = 0; i < 6; i++) mma16816v(cB, f[i][0], f[i][1], f[i][2], f[i][3], qf[2 * i], qf[2 * i + 1]);
                    sc2 = cA[0] + cA[3]; sc3 = cB[0] + cB[3];
                }
#pragma unroll
                for (int i = 0; i < 12; i++) qf[i] = mul2(qf[i], 0x6f806f80u);
                kr_scores(IC<0>(), sc0, sc1);
                kr_scores(IC<1>(), sc0, sc1);
                if (layer == 1) stage_v(IC<0>());
                kr_scores(IC<2>(), sc0, sc1);
                if (layer == 1) stage_v(IC<1>());
                kr_scores(IC<3>(), sc0, sc1);
                kr_scores(IC<4>(), sc2, sc3);
                {
                    LANE_IDS
                    const float sa = f_(lds32(kx + 8 + 4 * t)), sb = t == 0 ? f_(lds32(kx + 24)) : 1.0f;
                    const int nx = (int)lds32(kx);
                    uint32_t rm = lds32(kx + 4), qm = 0u;
#pragma unroll
                    for (int i = 0; i < 6; i++) qm = __vimax3_u16x2(qm, qf[2 * i] & 0x7fff7fffu, qf[2 * i + 1] & 0x7fff7fffu);
#pragma unroll
                    for (int i = 0; i < 3; i++) lds128(SM_QS + (2 * t + (g & 1)) * 48 + 16 * i, qf[4 * i], qf[4 * i + 1], qf[4 * i + 2], qf[4 * i + 3]);
                    if (__any_sync(0xffffffffu, max(qm & 0xffffu, qm >> 16) >= 0x7f80u)) rm = 31;
                    sc0 *= sa; sc1 *= sa; sc2 *= sb; sc3 *= sb;
#pragma unroll 1
                    for (int n = 0; n < nx; n++) {
                        const uint32_t w = lds32(kx + 32 + 4 * n);
                        const int tau = w >> 28;
                        const float d = bf_lo(lds16(SM_QS + ((w >> 15) & 0x1fe))) * bf_lo(w);
                        if (((w >> 24) & 7) == g && (tau & 3) == t) {
                            const int k = ((w >> 27) & 1) + (tau >> 2) * 2;
                            if (k == 0) sc0 += d; else if (k == 1) sc1 += d; else if (k == 2) sc2 += d; else sc3 += d;
                        }
                    }
#pragma unroll 1
                    for (; rm; rm &= rm - 1) {
                        const int tau = __ffs(rm) - 1;
#pragma unroll 1
                        for (int hf = 0; hf < 2; hf++) {
                            const char* gp = static_cast<const char*>(maps.kp) + (size_t)(row0 + tau * TS) * 128 + (8 * hf + (g >> 1) + 4 * (g & 1)) * 384 + 16 * t;
                            float cA[4] = {0.f, 0.f, 0.f, 0.f};
#pragma unroll
                            for (int i = 0; i < 6; i++) {
                                const uint4 a = __ldcg(reinterpret_cast<const uint4*>(gp + 64 * i));
                                mma16816(cA, a.x, a.y, a.z, a.w, qf[2 * i], qf[2 * i + 1]);
                            }
                            if ((tau & 3) == t) {
                                const int k = hf + (tau >> 2) * 2;
                                const float d = cA[0] + cA[3];
                                if (k == 0) sc0 = d; else if (k == 1) sc1 = d; else if (k == 2) sc2 = d; else sc3 = d;
                            }
                        }
                    }
                }
                if (layer == 0) {
                    LANE_IDS
#pragma unroll 1
                    for (int s = 5; s < 8; s++) {
                        mbar_wait(s == 5 ? xb : rb + (s & 1) * 8, s == 5);
                        const uint32_t tile = s == 5 ? bt : ring + (s & 1) * TILE;
                        float cA[4] = {0.f, 0.f, 0.f, 0.f}, cB[4] = {0.f, 0.f, 0.f, 0.f};
#pragma unroll
                        for (int i = 0; i < 6; i++) {
                            uint32_t a0, a1, a2, a3;
                            lds128(tile + K_OFF(i), a0, a1, a2, a3);
                            mma16816(cA, a0, a1, a2, a3, qf[2 * i], qf[2 * i + 1]);
                            lds128(tile + K_OFF(i) + 3072, a0, a1, a2, a3);
                            mma16816(cB, a0, a1, a2, a3, qf[2 * i], qf[2 * i + 1]);
                        }
                        if (t == (s & 3)) { sc2 = cA[0] + cA[3]; sc3 = cB[0] + cB[3]; }
                        __syncwarp();
                        refill1(s, AFTER(__float_as_uint(cA[0]) | __float_as_uint(cB[0])));
                    }
                } else {
                    LANE_IDS
#pragma unroll 1
                    for (int i = 2; i < 4; i++) {
                        const uint32_t tile = i == 3 ? ring : xtile, tb = i == 3 ? rb : xb;
                        mbar_wait(tb, 1);
#pragma unroll
                        for (int k = 0; k < 6; k++) {
                            const uint32_t a = tile + K_OFF(k);
                            lds128(a, kr[24 + k][0], kr[24 + k][1], kr[24 + k][2], kr[24 + k][3]);
                            lds128(a + 3072, kr[24 + 6 + k][0], kr[24 + 6 + k][1], kr[24 + 6 + k][2], kr[24 + 6 + k][3]);
                        }
                        float cA[4] = {0.f, 0.f, 0.f, 0.f}, cB[4] = {0.f, 0.f, 0.f, 0.f}, cC[4] = {0.f, 0.f, 0.f, 0.f}, cD[4] = {0.f, 0.f, 0.f, 0.f};
#pragma unroll
                        for (int k = 0; k < 3; k++) {
                            mma16816(cA, kr[24 + k][0], kr[24 + k][1], kr[24 + k][2], kr[24 + k][3], qf[2 * k], qf[2 * k + 1]);
                            mma16816(cB, kr[24 + 6 + k][0], kr[24 + 6 + k][1], kr[24 + 6 + k][2], kr[24 + 6 + k][3], qf[2 * k], qf[2 * k + 1]);
                            mma16816(cC, kr[24 + 3 + k][0], kr[24 + 3 + k][1], kr[24 + 3 + k][2], kr[24 + 3 + k][3], qf[6 + 2 * k], qf[7 + 2 * k]);
                            mma16816(cD, kr[24 + 9 + k][0], kr[24 + 9 + k][1], kr[24 + 9 + k][2], kr[24 + 9 + k][3], qf[6 + 2 * k], qf[7 + 2 * k]);
                        }
                        __syncwarp();
                        tile_load(tile, &maps.v, row0 + (i + 1) * TS + AFTER(__float_as_uint(cA[0]) | __float_as_uint(cB[0]) | __float_as_uint(cC[0]) | __float_as_uint(cD[0])), tb);
                        if (t == i) { sc2 = (cA[0] + cC[0]) + (cA[3] + cC[3]); sc3 = (cB[0] + cD[0]) + (cB[3] + cD[3]); }
                    }
                }
            }
            {
                const uint32_t mk = __reduce_max_sync(0xffffffffu, f2key(fmaxf(fmaxf(sc0, sc1), fmaxf(sc2, sc3))));
                if ((opq(tid) & 31) == 0) st_pkt2(&maps.scr->mx[h * 32 + c * 8 + wu], mk, tag);
                mw = key2f(mk);
            }
            pk0 = pack2(ex2((sc0 - mw) * SC), ex2((sc1 - mw) * SC));
            pk1 = pack2(ex2((sc2 - mw) * SC), ex2((sc3 - mw) * SC));
            sc2 = (bf_lo(pk0) + bf_hi(pk0)) + (bf_lo(pk1) + bf_hi(pk1));
#pragma unroll
            for (int o = 16; o > 0; o >>= 1) sc2 += __shfl_xor_sync(0xffffffffu, sc2, o);
#pragma unroll
            for (int s = 0; s < 3; s++) { acc[s][0] = acc[s][1] = acc[s][2] = acc[s][3] = 0.f; }
            auto head_ld = [&](int lane) { const uint2 mv = ld_pkt2(&maps.scr->mx[h * 32 + lane]); sc0 = f_(mv.x); sc1 = f_(mv.y); };
            auto head_factor = [&](int lane) {
                int it = 0;
                while (!__all_sync(0xffffffffu, __float_as_uint(sc1) == tag) && ++it < SPIN_CAP) head_ld(lane);
                sc3 = ex2((mw - key2f(__reduce_max_sync(0xffffffffu, __float_as_uint(sc0)))) * SC);
            };
#define P_CONSTS \
                const uint32_t sel0 = g == 0 ? 0x4410u : (g == 1 ? 0x1044u : 0x4444u); \
                const uint32_t sel1 = g == 2 ? 0x4410u : (g == 3 ? 0x1044u : 0x4444u); \
                const int src00 = 4 * (t < 2 ? 4 * t : 4 * (t - 2) + 1);
#define P_FRAGS(tau) \
                const uint32_t pk = ((tau) & 4) ? pk1 : pk0; \
                const uint32_t w0 = __shfl_sync(0xffffffffu, pk, src00 + ((tau) & 3)); \
                const uint32_t w1 = __shfl_sync(0xffffffffu, pk, src00 + ((tau) & 3) + 8); \
                uint32_t pb[4][2]; \
                _Pragma("unroll") for (int j = 0; j < 4; j++) { \
                    const uint32_t src = ((j & 1) ? w1 : w0) >> ((j >> 1) * 16); \
                    pb[j][0] = __byte_perm(src, 0, sel0); pb[j][1] = __byte_perm(src, 0, sel1); \
                }
            if (layer == 0) {
#pragma unroll 1
                for (int s = 8; s < 16; s++) {
                    LANE_IDS
                    P_CONSTS
                    if (s == 14) {
                        uint4* p = nullptr;
                        if (tl < 48) p = &maps.scr->qx[b * 48 + tl];
                        else if (tl < 98) p = &maps.scr->cx[b * 56 + tl - 48];
                        else if (tl < 145) {}
                        else if (tl >= 160) { if (tl < 208) p = &maps.scr->qc[b * 48 + tl - 160]; }
                        else if (b < NG) { if (tl < 153) p = &maps.scr->ah[b * 8 + tl - 145]; }
                        else if (b < DN0 + NDN && tl < 149) p = &maps.scr->ay[(b - DN0) * 4 + tl - 145];
                        if (p) st_pkt(p, 0, 0, 0, tl < 48);
                    }
                    if (s == 13) head_ld(lane);
                    P_FRAGS((s + 2) & 7)
                    mbar_wait(rb + (s & 1) * 8, ((s >> 1) + 1) & 1);
                    const uint32_t tile = ring + (s & 1) * TILE;
#pragma unroll
                    for (int j = 0; j < 4; j++) {
#pragma unroll
                        for (int u = 0; u < 3; u++) {
                            uint32_t a0, a1, a2, a3;
                            lds128(tile + (j >> 1) * 3072 + V_OFF(3 * (j & 1) + u), a0, a1, a2, a3);
                            mma16816(acc[u], a0, a1, a2, a3, pb[j][0], pb[j][1]);
                        }
                    }
                    __syncwarp();
                    if (s < 14) refill1(s, AFTER(__float_as_uint(acc[0][0]) | __float_as_uint(acc[1][0]) | __float_as_uint(acc[2][0])), true);
                    if (s == 13) head_factor(lane);
                    if (s == 15 && elect_one()) {
                        uint32_t n;
                        asm volatile("atom.shared.add.u32 %0, [%1], 1;" : "=r"(n) : "r"(SM_MISC + 8) : "memory");
                        if (n == 7) load_wo(maps, SM_B, h, c, WBAR, 5);
                    }
                }
            } else {
                LANE_IDS
                P_CONSTS
#pragma unroll
                for (int s = 0; s < 2; s++) {
                    P_FRAGS(s)
#pragma unroll
                    for (int j = 0; j < 4; j++) {
#pragma unroll
                        for (int u = 0; u < 3; u++) {
                            const int k = 6 * (j >> 1) + 3 * (j & 1) + u;
                            mma16816(acc[u], kr[12 * s + k][0], kr[12 * s + k][1], kr[12 * s + k][2], kr[12 * s + k][3], pb[j][0], pb[j][1]);
                        }
                    }
                }
#pragma unroll 1
                for (int i = 4; i < 10; i++) {
                    const int sl = i == 5 ? 0 : (i == 6 || i == 8 ? 1 : 2);
                    const uint32_t tile = sl ? ring + (sl - 1) * TILE : xtile, tb = sl ? rb + (sl - 1) * 8 : xb;
                    if (i == 8) head_ld(lane);
                    if (i == 9) head_factor(lane);
                    P_FRAGS(i - 2)
                    mbar_wait(tb, (0x310 >> i) & 1);
#pragma unroll
                    for (int k = 0; k < 6; k++) {
                        const uint32_t a = tile + V_OFF(k);
                        lds128(a, kr[24 + k][0], kr[24 + k][1], kr[24 + k][2], kr[24 + k][3]);
                        lds128(a + 3072, kr[24 + 6 + k][0], kr[24 + 6 + k][1], kr[24 + 6 + k][2], kr[24 + 6 + k][3]);
                    }
#pragma unroll
                    for (int j = 0; j < 4; j++) {
#pragma unroll
                        for (int u = 0; u < 3; u++) {
                            const int k = 6 * (j >> 1) + 3 * (j & 1) + u;
                            mma16816(acc[u], kr[24 + k][0], kr[24 + k][1], kr[24 + k][2], kr[24 + k][3], pb[j][0], pb[j][1]);
                        }
                    }
                    __syncwarp();
                    if (wu < L1R && i == 6 - 2 * (wu & 1)) tile_load_l1(tile, maps.vp, row0 + (6 - (wu & 1)) * TS, tb, lane);
                    else if (i == 4 || i == 6 || i == 7) tile_load(tile, &maps.v, row0 + (i == 4 ? 5 : i) * TS + AFTER(__float_as_uint(acc[0][0]) | __float_as_uint(acc[1][0]) | __float_as_uint(acc[2][0])), tb);
                    if (i == 7 && role < DN0 + NDN && elect_one()) {
                        uint32_t n;
                        asm volatile("atom.shared.add.u32 %0, [%1], 1;" : "=r"(n) : "r"(SM_MISC + 8) : "memory");
                        if (n == 15) load_wo(maps, SM_Q, h, c, WBAR, 3);
                    }
                }
            }
#undef P_FRAGS
#undef P_CONSTS
#undef LANE_IDS
#undef K_OFF
#undef V_OFF
        }

        uint32_t ticket = 0;
        {
            const int tl = opq(tid), warp = tl >> 5, lane = tl & 31, g = lane >> 2, t = lane & 3, mat = lane >> 3, r8 = lane & 7;
            {
                const uint32_t d = SM_R + 4 * (warp * 196 + 8 * g + 4 * t);
                if (t < 2) {
#pragma unroll
                    for (int u = 0; u < 3; u++) sts128(d + 256 * u, acc[u][0] * sc3, acc[u][1] * sc3, acc[u][2] * sc3, acc[u][3] * sc3);
                }
                if (lane == 0) sts128(d + 768, sc2 * sc3, 0.f, 0.f, 0.f);
            }
            const int tc = min(tl, 48);
            uint4* pc = opq(&maps.scr->cx[h * 4 * 56 + tc]);
            uint4* po = opq(pc + c * 56);
            const uint32_t fa = opq(SM_R + 16 * tc);
            __syncthreads();
            const int kg = warp >> 1, mg = warp & 1;
            const bool wo2 = layer && role < DN0 + NDN;
            const bool wo4 = layer && role < NG;
            uint32_t aw, oa, ob0, dw;
            uint32_t* tk;
            auto addrs = [&]() {
                aw = pin((wo2 ? SM_Q : SM_B) + (48 * kg + (mat >> 1) * 8 + r8) * 64 + (((2 * mg + (mat & 1)) ^ ((r8 >> 1) & 3)) << 4));
                oa = pin(SM_OS + 96 * kg + 8 * t);
                ob0 = pin(oa + 8 * t);
                dw = pin(SM_R + 4 * (4 * (16 * mg + g) + kg));
                tk = opq(maps.scr->ticket + 0);
            };
            uint32_t a[2][3][4];
            auto preload = [&]() {
#pragma unroll
                for (int i = 0; i < 2; i++) {
                    mbar_wait(WBAR + 8 * i, wo2);
#pragma unroll
                    for (int ks = 0; ks < 3; ks++) ldsm4t(aw + i * 12288 + ks * 1024, a[i][ks]);
                }
            };
            if (wu < 2) {
                if (tl < 49) {
                    float4 v[8];
#pragma unroll
                    for (int w = 0; w < 8; w++) v[w] = lds128f(fa + w * 784);
                    st_pktf(po, ((v[0].x + v[1].x) + (v[2].x + v[3].x)) + ((v[4].x + v[5].x) + (v[6].x + v[7].x)),
                            ((v[0].y + v[1].y) + (v[2].y + v[3].y)) + ((v[4].y + v[5].y) + (v[6].y + v[7].y)),
                            ((v[0].z + v[1].z) + (v[2].z + v[3].z)) + ((v[4].z + v[5].z) + (v[6].z + v[7].z)),
                            ((v[0].w + v[1].w) + (v[2].w + v[3].w)) + ((v[4].w + v[5].w) + (v[6].w + v[7].w)), tbit);
                }
                __syncwarp();
                uint4 v[4];
#pragma unroll
                for (int k = 0; k < 4; k++) v[k] = ld_pkt(pc + k * 56);
                asm volatile("bar.arrive 1, 256;" ::: "memory");
                addrs();
                const int w = 2 * tc, k3 = w / 24, r = w - 24 * k3;
                const uint32_t d0 = pin(tl < 48 ? SM_OS + 4 * (24 * k3 + (r < 16 ? 4 * (r & 3) + (r >> 2) : 16 + 2 * (r & 3) + ((r >> 2) & 1))) : SM_MISC);
                const uint32_t d1 = pin(tl < 48 ? d0 + (r < 16 ? 16 : 8) : SM_MISC + 12);
                int it = 0;
                bool more = true;
                while (__any_sync(0xffffffffu, ((v[0].w ^ tbit) | (v[1].w ^ tbit) | (v[2].w ^ tbit) | (v[3].w ^ tbit)) & 1) && more) {
#pragma unroll
                    for (int k = 0; k < 4; k++) v[k] = ld_pkt(pc + k * 56);
                    more = ++it < SPIN_CAP;
                }
                const float o0 = (f_(v[0].x) + f_(v[1].x)) + (f_(v[2].x) + f_(v[3].x));
                const uint32_t w0 = pack2(o0, (f_(v[0].y) + f_(v[1].y)) + (f_(v[2].y) + f_(v[3].y)));
                sts32(d1, pack2((f_(v[0].z) + f_(v[1].z)) + (f_(v[2].z) + f_(v[3].z)), (f_(v[0].w) + f_(v[1].w)) + (f_(v[2].w) + f_(v[3].w))));
                sts32(d0, tl < 48 ? w0 : __float_as_uint(o0));
                asm volatile("bar.arrive 2, 256;" ::: "memory");
                preload();
                asm volatile("bar.sync 3, 64;" ::: "memory");
            } else {
                addrs();
                asm volatile("bar.sync 1, 256;" ::: "memory");
                preload();
                asm volatile("bar.sync 2, 256;" ::: "memory");
            }
            uint32_t ob[6];
            lds128(ob0, ob[0], ob[1], ob[2], ob[3]);
            lds64(oa + 64, ob[4], ob[5]);
            if (tl == 224 && layer == 0)
                asm volatile("atom.relaxed.gpu.global.inc.u32 %0, [%1], 0x7fffffff;" : "=r"(ticket) : "l"(tk) : "memory");
            auto put = [&](int i, const float (&cc)[4]) { if (t == 0) { sts32(dw + 512 * i, cc[0]); sts32(dw + 512 * i + 128, cc[2]); } };
            {
                float c0[4] = {0.f, 0.f, 0.f, 0.f}, c1[4] = {0.f, 0.f, 0.f, 0.f}, c2[4] = {0.f, 0.f, 0.f, 0.f}, c3[4] = {0.f, 0.f, 0.f, 0.f};
                mbar_wait(WBAR + 16, wo2);
#pragma unroll
                for (int ks = 0; ks < 3; ks++) {
                    mma16816v(c0, a[0][ks][0], a[0][ks][1], a[0][ks][2], a[0][ks][3], ob[2 * ks], ob[2 * ks + 1]);
                    mma16816v(c1, a[1][ks][0], a[1][ks][1], a[1][ks][2], a[1][ks][3], ob[2 * ks], ob[2 * ks + 1]);
                    if (ks == 0 && layer == 0) {
                        mbar_wait(WBAR + 24, 0);
#pragma unroll
                        for (int k = 0; k < 3; k++) ldsm4t(aw + 3 * 12288 + k * 1024, wk[k]);
                    }
                    if (ks == 1) mbar_wait(WBAR + 32, wo4);
                    ldsm4t(aw + 2 * 12288 + ks * 1024, a[0][ks]);
                }
                const uint32_t aw4 = aw + (wo2 && !wo4 ? SM_B - SM_Q : 0) + 4 * 12288;
                ldsm4t(aw4 + 1024, a[1][0]);
#pragma unroll
                for (int ks = 0; ks < 3; ks++) {
                    mma16816v(c2, a[0][ks][0], a[0][ks][1], a[0][ks][2], a[0][ks][3], ob[2 * ks], ob[2 * ks + 1]);
                    mma16816v(c3, wk[ks][0], wk[ks][1], wk[ks][2], wk[ks][3], ob[2 * ks], ob[2 * ks + 1]);
                    if (ks == 0) { ldsm4t(aw4, a[0][0]); put(0, c0); put(1, c1); }
                    if (ks == 1) ldsm4t(aw4 + 2048, a[0][1]);
                }
                float c4[4] = {0.f, 0.f, 0.f, 0.f}, c5[4] = {0.f, 0.f, 0.f, 0.f};
                mma16816v(c4, a[0][0][0], a[0][0][1], a[0][0][2], a[0][0][3], ob[0], ob[1]);
                mma16816v(c5, a[1][0][0], a[1][0][1], a[1][0][2], a[1][0][3], ob[2], ob[3]);
                mma16816v(c4, a[0][1][0], a[0][1][1], a[0][1][2], a[0][1][3], ob[4], ob[5]);
                put(2, c2); put(3, c3);
                c4[0] += c5[0]; c4[2] += c5[2];
                put(4, c4);
            }
        }
        {
            const int tl = opq(tid);
            uint4* pr = opq(&maps.scr->acc[layer][54 * c + min(tl, 53)]);
            const uint32_t fa = opq(SM_R + 48 * tl);
            const float il = rcp(f_(lds32(SM_MISC)));
            __syncthreads();
            if (tl < 54) {
                const float4 v0 = lds128f(fa), v1 = lds128f(fa + 16), v2 = lds128f(fa + 32);
                const float y0 = il * ((v0.x + v0.y) + (v0.z + v0.w)), y1 = il * ((v1.x + v1.y) + (v1.z + v1.w)), y2 = il * ((v2.x + v2.y) + (v2.z + v2.w));
                red_pkt(pr, y0, tl == 53 ? 0.f : y1, tl == 53 ? 0.f : y2);
            }
            if (tl == 224 && layer == 0) {
                sts32(SM_MISC + 4, ticket);
                if (ticket < NG) load_ffn(maps, ticket, SM_B, FBAR);
            }
        }
        __syncthreads();
        if (layer == 0) role = __shfl_sync(0xffffffffu, (int)lds32(SM_MISC + 4), 0);
        const uint32_t DONE32 = 0x42000000u;
        if (role < NG) {
            const int tl = opq(tid), warp = tl >> 5, lane = tl & 31, g = lane >> 2, t = lane & 3, mat = lane >> 3, r8 = lane & 7;
            const uint32_t ag = SM_B + (80 * warp + (mat >> 1) * 8 + r8) * 96 + (((mat & 1) ^ (r8 >> 2)) << 4);
            constexpr int GI = 32, GK = 16 * 96;
            const bool on = (g & 1) == (t >> 1), isx = (on && g < 2) || g == 4;
            const uint32_t pm = opq(isx ? SM_XS + 160 * warp + 16 * t : (on || g == 5 ? SM_ONE : SM_ZERO)), pm2 = opq(pm + 128 - (isx ? 8 * t : 0));
            const uint32_t dg = opq(SM_R + 4 * (2 * (warp * 48 + g) + t));
            const uint32_t ho = pin(16u * (role * 8 + 4 * warp + ((lane * 11) >> 5)));
            const uint32_t fa = pin(SM_R + 8 * (24 * warp + 2 * min(lane, 11)));
            uint32_t pre[9][4];
            {
                bool hx = wu == 7;
                int it = 0;
                const uint4* px = opq(&maps.scr->acc[layer][min(tl, 215)]);
                const int cq = tl / 54, r = tl - 54 * cq, k0 = min(160 * cq + 3 * r, DM - 1);
                const uint32_t w0 = SM_XS + 4 * xpos(k0 >> 1), w1 = SM_XS + 4 * xpos(min((k0 >> 1) + 1, DM / 2 - 1));
                const bool two = tl < 216 && r != 53;
                const uint32_t e0 = opq(tl < 216 ? w0 + 2 * (k0 & 1) : SM_MISC + 12);
                const uint32_t e1 = opq(two ? ((k0 & 1) ? w1 : w0 + 2) : SM_MISC + 12), e2 = opq(two ? w1 + 2 * (k0 & 1) : SM_MISC + 12);
                const uint32_t x01 = opq(lds16(e0) | (lds16(e1) << 16)), x2 = lds16(e2);
                auto take_x = [&](const uint4 v) {
                    if (__all_sync(0xffffffffu, v.w == DONE32)) {
                        hx = true;
                        const uint32_t y01 = add2(x01, pack2(f_(v.x), f_(v.y))), y2 = add2(x2, pack2(f_(v.z), 0.f));
                        sts16(e0, y01); sts16(e1, y01 >> 16); sts16(e2, y2);
                    }
                };
                while (!mbar_test(FBAR, 0) && ++it < SPIN_CAP) { if (!hx) take_x(ld_pkt(px)); }
                uint4 v = make_uint4(0u, 0u, 0u, 0u);
                if (!hx) v = ld_pkt(px);
#pragma unroll
                for (int n = 0; n < 9; n++) ldsm4t(ag + (n % 3) * GI + (n / 3) * GK, pre[n]);
                if (layer) {
#pragma unroll
                    for (int n = 9; n < 15; n++) ldsm4t(ag + (n % 3) * GI + (n / 3) * GK, kr[n - 9]);
                }
                if (!hx) {
                    bool more = true;
                    while (!__all_sync(0xffffffffu, v.w == DONE32) && more) { v = ld_pkt(px); more = ++it < SPIN_CAP; }
                    const uint32_t y01 = add2(x01, pack2(f_(v.x), f_(v.y))), y2 = add2(x2, pack2(f_(v.z), 0.f));
                    sts16(e0, y01); sts16(e1, y01 >> 16); sts16(e2, y2);
                }
            }
            __syncthreads();
            {
                float cc[3][4], gr[4];
                if (layer) gemv15r(cc, gr, pre, kr, pm, pm2);
                else gemv15<GK, true>(cc, gr, pre, [&](int i) { return ag + i * GI; }, pm, pm2);
                if (t < 2) {
#pragma unroll
                    for (int i = 0; i < 3; i++) { sts32(dg + 128 * i, cc[i][0] + cc[i][3]); sts32(dg + 128 * i + 64, cc[i][1] + cc[i][2]); }
                }
                if ((lane | 4) == 22) sts32(SM_ST + 8 * warp + (g & 1) * 4, gr[0]);
            }
            uint4* ph = reinterpret_cast<uint4*>(reinterpret_cast<char*>(maps.scr->ah) + ho);
            const bool snd = (0x249 >> lane) & 1;
            __syncthreads();
            if (wu < 2) {
                float mean, inv;
                float4 v[8];
#pragma unroll
                for (int w = 0; w < 8; w++) v[w] = lds128f(fa + w * 384);
                ln_stats(mean, inv);
                const float ga = inv * ((((v[0].x + v[1].x) + (v[2].x + v[3].x)) + ((v[4].x + v[5].x) + (v[6].x + v[7].x))) -
                                        mean * (((v[0].y + v[1].y) + (v[2].y + v[3].y)) + ((v[4].y + v[5].y) + (v[6].y + v[7].y))));
                const float gb = inv * ((((v[0].z + v[1].z) + (v[2].z + v[3].z)) + ((v[4].z + v[5].z) + (v[6].z + v[7].z))) -
                                        mean * (((v[0].w + v[1].w) + (v[2].w + v[3].w)) + ((v[4].w + v[5].w) + (v[6].w + v[7].w))));
                uint32_t wd = pack2(ga, gb);
                if (role < NG / 2) {
                    const float g0 = bf_lo(wd), g1 = bf_hi(wd);
                    wd = pack2(g0 * rcp(1.0f + ex2(-1.4426950408889634f * g0)), g1 * rcp(1.0f + ex2(-1.4426950408889634f * g1)));
                }
                const uint32_t wa = __shfl_down_sync(0xffffffffu, wd, 1), wb = __shfl_down_sync(0xffffffffu, wd, 2);
                if (snd) st_pkt(ph, wd, wa, wb, tag);
            }
            __syncthreads();
        } else if (role < DN0 + NDN) {
            const int j = role - DN0;
            const int tl = opq(tid), warp = tl >> 5, lane = tl & 31, g = lane >> 2, t = lane & 3, mat = lane >> 3, r8 = lane & 7;
            float xr0 = 0.f, xr1 = 0.f;
            if (wu == 0) {
                const int col = 16 * j + (lane & 15), cc = col / 160, r = col - 160 * cc, e = r % 3;
                const uint4* px = &maps.scr->acc[layer][(54 * cc + r / 3)];
                const float x0 = bf_lo(lds16(SM_XS + 4 * xpos(col >> 1) + 2 * (col & 1)));
                uint4 v;
                int it = 0;
                bool ld = layer == 0;
                do {
                    v = ld_pkt(px);
                    if (ld && f_(__shfl_sync(0xffffffffu, v.w, 0)) >= (float)DNTH) { ld = false; if (lane == 0) load_ffn(maps, role, SM_B, FBAR); }
                } while (!__all_sync(0xffffffffu, v.w == DONE32) && ++it < SPIN_CAP);
                if (ld && lane == 0) load_ffn(maps, role, SM_B, FBAR);
                const float xres = bfr(x0 + bfr(f_(e == 0 ? v.x : (e == 1 ? v.y : v.z))));
                xr0 = __shfl_sync(0xffffffffu, xres, 2 * (lane & 7));
                xr1 = __shfl_sync(0xffffffffu, xres, 2 * (lane & 7) + 1);
            }
            const uint32_t ad = SM_B + (192 * warp + (mat >> 1) * 8 + r8) * 32 + (((mat & 1) ^ (r8 >> 2)) << 4);
            const uint32_t hs = SM_R + 384 * warp, hb = opq(hs + 16 * t), dd = opq(SM_R + 3072 + 4 * (warp * 16 + g));
            uint32_t pre[NPRE][4];
            uint32_t pos[3];
#pragma unroll
            for (int i = 0; i < 3; i++) { const int w = 3 * lane + i; pos[i] = opq(hs + 4 * ((w & ~15) + 4 * (w & 3) + ((w >> 2) & 1) + ((w >> 2) & 2))); }
            const uint4* ph = opq(&maps.scr->ah[tl]);
            const uint32_t fa = opq(SM_R + 3072 + 8 * (lane & 7));
            uint2* py = opq(reinterpret_cast<uint2*>(maps.scr->ay) + 8 * j + (lane & 7));
            uint32_t* po = opq(reinterpret_cast<uint32_t*>(out) + 8 * j + (lane & 7));
            mbar_wait(FBAR, 0);
#pragma unroll
            for (int n = 0; n < NPRE; n++) ldsm4t(ad + n * 512, pre[n]);
            {
                uint4 v, u;
                int it = 0;
                bool more;
                do { v = ld_pkt(ph); u = ld_pkt(ph + 256); more = ++it < SPIN_CAP; }
                while (!__all_sync(0xffffffffu, v.w == tag && u.w == tag) && more);
                sts32(pos[0], mul2(v.x, u.x)); sts32(pos[1], mul2(v.y, u.y)); sts32(pos[2], mul2(v.z, u.z));
            }
            __syncwarp();
            {
                float cc[4][4];
                uint32_t hv[3][4];
#pragma unroll
                for (int jj = 0; jj < 3; jj++) lds128(hb + 64 * jj, hv[jj][0], hv[jj][1], hv[jj][2], hv[jj][3]);
#pragma unroll
                for (int n = 0; n < 12; n++) {
                    const int s = n < NPRE ? n : n - NPRE;
                    if (n < 4) cc[n][0] = cc[n][1] = cc[n][2] = cc[n][3] = 0.f;
                    mma16816v(cc[n & 3], pre[s][0], pre[s][1], pre[s][2], pre[s][3], hv[(n >> 1) % 3][2 * (n & 1)], hv[(n >> 1) % 3][2 * (n & 1) + 1]);
                    if (n + NPRE < 12) ldsm4t(ad + (n + NPRE) * 512, pre[n]);
                    if ((n & 1) && n < 6) lds128(hb + 64 * ((n >> 1) + 3), hv[n >> 1][0], hv[n >> 1][1], hv[n >> 1][2], hv[n >> 1][3]);
                }
                if (t == 0) { sts32(dd, (cc[0][0] + cc[1][0]) + (cc[2][0] + cc[3][0])); sts32(dd + 32, (cc[0][2] + cc[1][2]) + (cc[2][2] + cc[3][2])); }
            }
            __syncthreads();
            if (tl < 8) {
                float2 v[8];
#pragma unroll
                for (int w = 0; w < 8; w++) v[w] = lds64f(fa + 64 * w);
                const uint32_t y = pack2(((v[0].x + v[1].x) + (v[2].x + v[3].x)) + ((v[4].x + v[5].x) + (v[6].x + v[7].x)),
                                         ((v[0].y + v[1].y) + (v[2].y + v[3].y)) + ((v[4].y + v[5].y) + (v[6].y + v[7].y)));
                const uint32_t wd = pack2(xr0 + bf_lo(y), xr1 + bf_hi(y));
                if (layer) asm volatile("st.global.u32 [%0], %1;" ::"l"(po), "r"(wd) : "memory");
                st_pkt2(py, wd, tag);
            }
            __syncthreads();
        }
    }
}

typedef CUresult (*EncodeFn)(CUtensorMap*, CUtensorMapDataType, cuuint32_t, void*, const cuuint64_t*, const cuuint64_t*, const cuuint32_t*,
                             const cuuint32_t*, CUtensorMapInterleave, CUtensorMapSwizzle, CUtensorMapL2promotion, CUtensorMapFloatOOBfill);

void make_map(EncodeFn enc, CUtensorMap* m, const void* base, int rank, uint64_t d0, uint64_t d1, uint64_t d2, uint64_t s1, uint64_t s2,
              uint32_t b0, uint32_t b1, uint32_t b2, CUtensorMapSwizzle sw, CUtensorMapL2promotion pr = CU_TENSOR_MAP_L2_PROMOTION_NONE) {
    cuuint64_t dims[3] = {d0, d1, d2};
    cuuint64_t strides[2] = {s1, s2};
    cuuint32_t box[3] = {b0, b1, b2};
    cuuint32_t es[3] = {1, 1, 1};
    enc(m, CU_TENSOR_MAP_DATA_TYPE_BFLOAT16, rank, const_cast<void*>(base), dims, strides, box, es, CU_TENSOR_MAP_INTERLEAVE_NONE, sw,
        pr, CU_TENSOR_MAP_FLOAT_OOB_FILL_NONE);
}

}

extern "C" void kernel_launch(void* const* d_in, const int* in_sizes, int n_in, void* d_out, int out_size) {
    (void)in_sizes; (void)n_in; (void)out_size;
    static EncodeFn enc = nullptr;
    static Scratch* scr = nullptr;
    if (!enc) {
        void* fn = nullptr;
        cudaDriverEntryPointQueryResult qr;
        cudaGetDriverEntryPoint("cuTensorMapEncodeTiled", &fn, cudaEnableDefault, &qr);
        enc = reinterpret_cast<EncodeFn>(fn);
        cudaGetSymbolAddress(reinterpret_cast<void**>(&scr), g_scr);
        cudaFuncSetAttribute(decode_kernel, cudaFuncAttributeMaxDynamicSharedMemorySize, SM_TOTAL);
    }
    Maps maps;
    make_map(enc, &maps.k, d_in[1], 2, 64, (uint64_t)NH * SK * 3, 1, 128, 0, 64, 48, 1, CU_TENSOR_MAP_SWIZZLE_128B);
    make_map(enc, &maps.v, d_in[2], 2, 64, (uint64_t)NH * SK * 3, 1, 128, 0, 64, 48, 1, CU_TENSOR_MAP_SWIZZLE_128B);
    {
        cuuint64_t dims[5] = {64, 16, NH * DH / 64, DM / 80, 5};
        cuuint64_t strides[4] = {NH * DH * 2, 128, 80 * NH * DH * 2, 16 * NH * DH * 2};
        cuuint32_t box[5] = {64, 16, 3, 2, 5};
        cuuint32_t es[5] = {1, 1, 1, 1, 1};
        enc(&maps.wq, CU_TENSOR_MAP_DATA_TYPE_BFLOAT16, 5, d_in[3], dims, strides, box, es, CU_TENSOR_MAP_INTERLEAVE_NONE, CU_TENSOR_MAP_SWIZZLE_128B,
            CU_TENSOR_MAP_L2_PROMOTION_NONE, CU_TENSOR_MAP_FLOAT_OOB_FILL_NONE);
    }
    make_map(enc, &maps.wo, d_in[4], 3, 32, NH * DH, DM / 32, DM * 2, 64, 32, 192, 1, CU_TENSOR_MAP_SWIZZLE_64B);
    constexpr int GW = 48;
    make_map(enc, &maps.w1, d_in[6], 3, FF, 160, 4, FF * 2, 160 * FF * 2, GW, 160, 4, CU_TENSOR_MAP_SWIZZLE_NONE);
    make_map(enc, &maps.w3, d_in[7], 3, FF, 160, 4, FF * 2, 160 * FF * 2, GW, 160, 4, CU_TENSOR_MAP_SWIZZLE_NONE);
    make_map(enc, &maps.w2, d_in[8], 3, DM, 256, 6, DM * 2, 256 * DM * 2, 16, 256, 6, CU_TENSOR_MAP_SWIZZLE_32B);
    make_map(enc, &maps.ks, d_in[1], 2, 64, (uint64_t)NH * SK * 3, 1, 128, 0, 16, 48, 1, CU_TENSOR_MAP_SWIZZLE_NONE);
    make_map(enc, &maps.vs, d_in[2], 2, 64, (uint64_t)NH * SK * 3, 1, 128, 0, 16, 48, 1, CU_TENSOR_MAP_SWIZZLE_NONE);
    make_map(enc, &maps.kh, d_in[1], 2, 64, (uint64_t)NH * SK * 3, 1, 128, 0, 64, 24, 1, CU_TENSOR_MAP_SWIZZLE_128B);
    maps.kp = d_in[1];
    maps.vp = d_in[2];
    maps.scr = scr;
    maps.zero = 0;
    const uint32_t rt[8] = {0x2EE0, 0x35E0, 0x2EE0, 0x35E0, 0x3EE0, 0x35E0, 0x3EE0, 0x35E0};
    for (int i = 0; i < 8; i++) maps.rt[i] = rt[i];
    decode_kernel<<<NCTA, NT, SM_TOTAL, cudaStreamPerThread>>>(maps, (const __nv_bfloat16*)d_in[0], (__nv_bfloat16*)d_out);
}
```

```cpp
#include <cuda_runtime.h>
#include <cuda_bf16.h>
#include <cuda.h>
#include <stdint.h>
#include <math.h>

namespace {

constexpr int DM = 640;
constexpr int NH = 32;
constexpr int DH = 192;
constexpr int SK = 32768;
constexpr int WIN = 4096;
constexpr int FF = 1536;
constexpr int NCTA = 128;
constexpr int NT = 256;
constexpr int TILE = 6144;
constexpr int TS = 48;
constexpr int NG = 64;
constexpr int DN0 = 64;
constexpr int NDN = 40;

constexpr uint32_t SB = 1024;
constexpr uint32_t SM_RING = SB;
constexpr uint32_t SM_B = SM_RING + 8 * 2 * TILE;
constexpr uint32_t SM_Q = SM_B + 61440;
constexpr uint32_t SM_XS = SM_Q + 61440;
constexpr uint32_t SM_R = SM_XS + 1280;
constexpr uint32_t SM_ST = SM_R + 4096;
constexpr uint32_t SM_QS = SM_R + 6272;
constexpr uint32_t SM_OS = SM_QS + 384;
constexpr uint32_t SM_CS = SM_OS + 384;
constexpr uint32_t SM_BAR = SM_CS + 768;
constexpr uint32_t SM_XBAR = SM_BAR + 24 * 8;
constexpr uint32_t SM_MISC = SM_XBAR + 8 * 8;
constexpr uint32_t SM_ONE = SM_MISC + 32;
constexpr uint32_t SM_ZERO = SM_ONE + 160;
constexpr uint32_t SM_KX = SM_ZERO + 160;
constexpr uint32_t SM_TOTAL = SM_KX + 8 * 96 - SB;
constexpr int NEXC = 16;
static_assert(SM_TOTAL <= 232448, "shared memory");
constexpr uint32_t QBAR = SM_BAR + 16 * 8, FBAR = QBAR + 8, WBAR = QBAR + 16, QRDY = QBAR + 56;

constexpr unsigned long long POL_EF = 0x12F0000000000000ull;
constexpr unsigned long long POL_EN = 0x1000000000000000ull;

constexpr int L1R = 3;
constexpr int DNTH = 23;
constexpr int NPRE = 6;
constexpr int SPIN_CAP = 1 << 19;
constexpr uint32_t ONES = 0x3F803F80u;
#define AFTER(x) ((x) & maps.zero)
#define ALL6(a, n) (a[n][0] | a[n + 1][0] | a[n + 2][0] | a[n + 3][0] | a[n + 4][0] | a[n + 5][0])
#define ROW0(w) ((h * SK + (SK - WIN) + c * 1024 + (w) * 128) * 3)

struct Scratch {
    uint4 qx[NCTA * 48];
    uint4 qc[NCTA * 48];
    uint4 cx[NCTA * 56];
    uint4 acc[2][256];
    uint4 ay[256];
    uint4 pad0[256];
    uint4 ah[NG * 8];
    uint2 mx[NH * 32];
    uint32_t ticket[32];
};
__device__ __align__(4096) Scratch g_scr;
struct Maps { CUtensorMap k, v, wq, wo, w1, w3, w2, ks, vs, kh; const void *kp, *vp; Scratch* scr; uint32_t rt[8], zero; };

__device__ __forceinline__ uint32_t smem_u32(const void* p) { return (uint32_t)__cvta_generic_to_shared(p); }
__device__ __forceinline__ void mbar_init(uint32_t bar, uint32_t cnt) {
    asm volatile("mbarrier.init.shared::cta.b64 [%0], %1;" ::"r"(bar), "r"(cnt) : "memory");
}
__device__ __forceinline__ void mbar_expect_tx(uint32_t bar, uint32_t bytes) {
    asm volatile("mbarrier.arrive.expect_tx.shared::cta.b64 _, [%0], %1;" ::"r"(bar), "r"(bytes) : "memory");
}
__device__ __forceinline__ bool mbar_test(uint32_t bar, uint32_t parity) {
    uint32_t done;
    asm volatile("{\n.reg .pred p;\nmbarrier.try_wait.parity.shared::cta.b64 p, [%1], %2;\nselp.u32 %0, 1, 0, p;\n}"
                 : "=r"(done) : "r"(bar), "r"(parity) : "memory");
    return done;
}
__device__ __forceinline__ void mbar_wait(uint32_t bar, uint32_t parity) {
    asm volatile("{\n.reg .pred p;\n.reg .u32 n;\nmov.u32 n, 0;\n"
                 "W: mbarrier.try_wait.parity.shared::cta.b64 p, [%0], %1;\n@p bra D;\n"
                 "add.u32 n, n, 1;\nsetp.lt.u32 p, n, %2;\n@p bra W;\nD:\n}" ::"r"(bar), "r"(parity), "n"(SPIN_CAP) : "memory");
}
__device__ __forceinline__ void tma2d(uint32_t dst, const CUtensorMap* map, int c0, int c1, uint32_t bar, unsigned long long pol) {
    asm volatile("cp.async.bulk.tensor.2d.shared::cluster.global.mbarrier::complete_tx::bytes.L2::cache_hint [%0], [%1, {%3, %4}], [%2], %5;"
                 ::"r"(dst), "l"(map), "r"(bar), "r"(c0), "r"(c1), "l"(pol) : "memory");
}
__device__ __forceinline__ void tma3d(uint32_t dst, const CUtensorMap* map, int c0, int c1, int c2, uint32_t bar, unsigned long long pol) {
    asm volatile("cp.async.bulk.tensor.3d.shared::cluster.global.mbarrier::complete_tx::bytes.L2::cache_hint [%0], [%1, {%3, %4, %5}], [%2], %6;"
                 ::"r"(dst), "l"(map), "r"(bar), "r"(c0), "r"(c1), "r"(c2), "l"(pol) : "memory");
}
__device__ __forceinline__ void tma5d(uint32_t dst, const CUtensorMap* map, int c2, int c3, uint32_t bar, unsigned long long pol) {
    asm volatile("cp.async.bulk.tensor.5d.shared::cluster.global.mbarrier::complete_tx::bytes.L2::cache_hint [%0], [%1, {0, 0, %3, %4, 0}], [%2], %5;"
                 ::"r"(dst), "l"(map), "r"(bar), "r"(c2), "r"(c3), "l"(pol) : "memory");
}
__device__ __forceinline__ void tile_load(uint32_t dst, const CUtensorMap* map, int row, uint32_t bar) {
    asm volatile("{\n.reg .pred p;\nelect.sync _|p, 0xffffffff;\n"
                 "@p mbarrier.arrive.expect_tx.shared::cta.b64 _, [%2], 6144;\n"
                 "@p cp.async.bulk.tensor.2d.shared::cluster.global.mbarrier::complete_tx::bytes.L2::cache_hint [%0], [%1, {0, %3}], [%2], %4;\n}"
                 ::"r"(dst), "l"(map), "r"(bar), "r"(row), "l"(POL_EF) : "memory");
}
__device__ __forceinline__ void half_load(uint32_t dst, const CUtensorMap* map, int row, uint32_t bar, bool first) {
    if (first) asm volatile("{\n.reg .pred p;\nelect.sync _|p, 0xffffffff;\n@p mbarrier.arrive.expect_tx.shared::cta.b64 _, [%0], 6144;\n}" ::"r"(bar) : "memory");
    asm volatile("{\n.reg .pred p;\nelect.sync _|p, 0xffffffff;\n"
                 "@p cp.async.bulk.tensor.2d.shared::cluster.global.mbarrier::complete_tx::bytes.L2::cache_hint [%0], [%1, {0, %3}], [%2], %4;\n}"
                 ::"r"(dst), "l"(map), "r"(bar), "r"(row), "l"(POL_EF) : "memory");
}
__device__ __forceinline__ void tile_keep(const CUtensorMap* map, int row) {
    asm volatile("{\n.reg .pred p;\nelect.sync _|p, 0xffffffff;\n"
                 "@p cp.async.bulk.prefetch.tensor.2d.L2.global.L2::cache_hint [%0, {0, %1}], %2;\n}"
                 ::"l"(map), "r"(row), "l"(POL_EN) : "memory");
}
__device__ __forceinline__ void tile_load_l1(uint32_t dst, const void* base, int row, uint32_t bar, int lane) {
    const char* g = static_cast<const char*>(base) + (size_t)row * 128 + lane * 16;
    const uint32_t s0 = dst + (lane >> 3) * 128 + (((lane & 7) ^ (lane >> 3)) << 4), s1 = s0 ^ 64;
#pragma unroll
    for (int k = 0; k < 12; k++)
        asm volatile("cp.async.ca.shared.global.L2::cache_hint [%0], [%1], 16, %2;" ::"r"(((k & 1) ? s1 : s0) + k * 512), "l"(g + k * 512), "l"(POL_EF) : "memory");
    asm volatile("cp.async.mbarrier.arrive.shared::cta.b64 [%0];" ::"r"(bar) : "memory");
    __syncwarp();
    if (lane == 0) asm volatile("mbarrier.arrive.shared::cta.b64 _, [%0];" ::"r"(bar) : "memory");
}
__device__ __forceinline__ bool elect_one() {
    uint32_t p;
    asm volatile("{\n.reg .pred p;\nelect.sync _|p, 0xffffffff;\nselp.u32 %0, 1, 0, p;\n}" : "=r"(p));
    return p;
}
__device__ __forceinline__ void delay(uint32_t clocks) {
    uint32_t t0, t1;
    asm volatile("mov.u32 %0, %%clock;" : "=r"(t0));
    do asm volatile("mov.u32 %0, %%clock;" : "=r"(t1)); while (t1 - t0 < clocks);
}
__device__ __forceinline__ void lds128(uint32_t addr, uint32_t& a, uint32_t& b, uint32_t& c, uint32_t& d) {
    asm volatile("ld.shared.v4.u32 {%0,%1,%2,%3}, [%4];" : "=r"(a), "=r"(b), "=r"(c), "=r"(d) : "r"(addr) : "memory");
}
__device__ __forceinline__ void lds64(uint32_t addr, uint32_t& a, uint32_t& b) {
    asm volatile("ld.shared.v2.u32 {%0,%1}, [%2];" : "=r"(a), "=r"(b) : "r"(addr) : "memory");
}
__device__ __forceinline__ void ldsm4t(uint32_t addr, uint32_t (&a)[4]) {
    asm volatile("ldmatrix.sync.aligned.m8n8.x4.trans.shared.b16 {%0,%1,%2,%3}, [%4];" : "=r"(a[0]), "=r"(a[1]), "=r"(a[2]), "=r"(a[3]) : "r"(addr) : "memory");
}
__device__ __forceinline__ void mma16816(float (&c)[4], uint32_t a0, uint32_t a1, uint32_t a2, uint32_t a3, uint32_t b0, uint32_t b1) {
    asm("mma.sync.aligned.m16n8k16.row.col.f32.bf16.bf16.f32 {%0,%1,%2,%3}, {%4,%5,%6,%7}, {%8,%9}, {%0,%1,%2,%3};"
        : "+f"(c[0]), "+f"(c[1]), "+f"(c[2]), "+f"(c[3]) : "r"(a0), "r"(a1), "r"(a2), "r"(a3), "r"(b0), "r"(b1));
}
__device__ __forceinline__ void mma16816v(float (&c)[4], uint32_t a0, uint32_t a1, uint32_t a2, uint32_t a3, uint32_t b0, uint32_t b1) {
    asm volatile("mma.sync.aligned.m16n8k16.row.col.f32.bf16.bf16.f32 {%0,%1,%2,%3}, {%4,%5,%6,%7}, {%8,%9}, {%0,%1,%2,%3};"
        : "+f"(c[0]), "+f"(c[1]), "+f"(c[2]), "+f"(c[3]) : "r"(a0), "r"(a1), "r"(a2), "r"(a3), "r"(b0), "r"(b1));
}
__device__ __forceinline__ int xpos(int w) {
    const int seg = w / 40, r = w - 40 * seg;
    return 40 * seg + (r < 32 ? (r & 16) + 4 * (r & 3) + ((r >> 2) & 3) : 32 + 2 * (r & 3) + ((r >> 2) & 1));
}
__device__ __forceinline__ void st_pkt(uint4* p, uint32_t a, uint32_t b, uint32_t c, uint32_t d) {
    asm volatile("{\n.reg .b128 t;\n.reg .b64 lo, hi;\nmov.b64 lo, {%1,%2};\nmov.b64 hi, {%3,%4};\nmov.b128 t, {lo,hi};\nst.relaxed.gpu.global.b128 [%0], t;\n}"
                 ::"l"(p), "r"(a), "r"(b), "r"(c), "r"(d) : "memory");
}
__device__ __forceinline__ void st_pktf(uint4* p, float a, float b, float c, float d, uint32_t bit) {
    st_pkt(p, __float_as_uint(a), __float_as_uint(b), __float_as_uint(c), (__float_as_uint(d) & ~1u) | bit);
}
__device__ __forceinline__ void red_pkt(uint4* p, float a, float b, float c) {
    asm volatile("red.relaxed.gpu.global.add.v4.f32 [%0], {%1,%2,%3,%4};" ::"l"(p), "f"(a), "f"(b), "f"(c), "f"(1.0f) : "memory");
}
__device__ __forceinline__ uint4 ld_pkt(const uint4* p) {
    uint4 v;
    asm volatile("{\n.reg .b128 t;\n.reg .b64 lo, hi;\nld.relaxed.gpu.global.b128 t, [%4];\nmov.b128 {lo,hi}, t;\nmov.b64 {%0,%1}, lo;\nmov.b64 {%2,%3}, hi;\n}"
                 : "=r"(v.x), "=r"(v.y), "=r"(v.z), "=r"(v.w) : "l"(p) : "memory");
    return v;
}
__device__ __forceinline__ uint2 ld_pkt2(const uint2* p) {
    unsigned long long v;
    asm volatile("ld.relaxed.gpu.global.b64 %0, [%1];" : "=l"(v) : "l"(p) : "memory");
    return make_uint2((uint32_t)v, (uint32_t)(v >> 32));
}
__device__ __forceinline__ void st_pkt2(uint2* p, uint32_t a, uint32_t b) {
    asm volatile("st.relaxed.gpu.global.b64 [%0], %1;" ::"l"(p), "l"((unsigned long long)a | ((unsigned long long)b << 32)) : "memory");
}
__device__ __forceinline__ float ex2(float x) { float y; asm("ex2.approx.ftz.f32 %0, %1;" : "=f"(y) : "f"(x)); return y; }
__device__ __forceinline__ float rcp(float x) { float y; asm("rcp.approx.ftz.f32 %0, %1;" : "=f"(y) : "f"(x)); return y; }
__device__ __forceinline__ uint32_t pack2(float lo, float hi) {
    uint32_t r; asm("cvt.rn.bf16x2.f32 %0, %1, %2;" : "=r"(r) : "f"(hi), "f"(lo)); return r;
}
__device__ __forceinline__ float bf_lo(uint32_t w) { return __uint_as_float(w << 16); }
__device__ __forceinline__ float bf_hi(uint32_t w) { return __uint_as_float(w & 0xffff0000u); }
__device__ __forceinline__ float bfr(float x) { return bf_lo(pack2(x, 0.f)); }
__device__ __forceinline__ float f_(uint32_t u) { return __uint_as_float(u); }

__device__ __forceinline__ uint32_t add2(uint32_t a, uint32_t b) { uint32_t r; asm("add.rn.bf16x2 %0, %1, %2;" : "=r"(r) : "r"(a), "r"(b)); return r; }
__device__ __forceinline__ uint32_t mul2(uint32_t a, uint32_t b) { uint32_t r; asm("mul.rn.bf16x2 %0, %1, %2;" : "=r"(r) : "r"(a), "r"(b)); return r; }
__device__ __forceinline__ uint32_t f2key(float f) { const uint32_t u = __float_as_uint(f); return u ^ ((uint32_t)((int)u >> 31) | 0x80000000u); }
__device__ __forceinline__ float key2f(uint32_t k) { return __uint_as_float(k ^ ((uint32_t)((int)~k >> 31) | 0x80000000u)); }
__device__ __forceinline__ float4 lds128f(uint32_t a) {
    float4 v; asm volatile("ld.shared.v4.f32 {%0,%1,%2,%3}, [%4];" : "=f"(v.x), "=f"(v.y), "=f"(v.z), "=f"(v.w) : "r"(a) : "memory"); return v;
}
__device__ __forceinline__ float2 lds64f(uint32_t a) { float2 v; asm volatile("ld.shared.v2.f32 {%0,%1}, [%2];" : "=f"(v.x), "=f"(v.y) : "r"(a) : "memory"); return v; }
__device__ __forceinline__ uint32_t lds32(uint32_t a) { uint32_t v; asm volatile("ld.shared.u32 %0, [%1];" : "=r"(v) : "r"(a) : "memory"); return v; }
__device__ __forceinline__ uint32_t lds16(uint32_t a) { uint32_t v; asm volatile("ld.shared.u16 %0, [%1];" : "=r"(v) : "r"(a) : "memory"); return v; }
__device__ __forceinline__ void sts16(uint32_t a, uint32_t v) { asm volatile("st.shared.u16 [%0], %1;" ::"r"(a), "r"(v) : "memory"); }
__device__ __forceinline__ void sts32(uint32_t a, uint32_t v) { asm volatile("st.shared.u32 [%0], %1;" ::"r"(a), "r"(v) : "memory"); }
__device__ __forceinline__ void sts32(uint32_t a, float v) { asm volatile("st.shared.f32 [%0], %1;" ::"r"(a), "f"(v) : "memory"); }
__device__ __forceinline__ void sts128(uint32_t a, float x, float y, float z, float w) {
    asm volatile("st.shared.v4.f32 [%0], {%1,%2,%3,%4};" ::"r"(a), "f"(x), "f"(y), "f"(z), "f"(w) : "memory");
}
template <int N> struct IC { static constexpr int value = N; };
__device__ __forceinline__ int opq(int x) { asm volatile("" : "+r"(x)); return x; }
__device__ __forceinline__ uint32_t opq(uint32_t x) { asm volatile("" : "+r"(x)); return x; }
__device__ __forceinline__ uint32_t pin(uint32_t x) { x = opq(x); sts32(SM_MISC + 12, x); return x; }
__device__ __forceinline__ float pin(float x) { sts32(SM_MISC + 12, x); return x; }
template <typename T> __device__ __forceinline__ T* pin(T* p) {
    asm volatile("{\n.reg .b32 lo, hi;\nmov.b64 {lo, hi}, %0;\nst.shared.v2.b32 [%1], {lo, hi};\n}" : "+l"(p) : "r"(SM_MISC + 16) : "memory");
    return p;
}
template <typename T> __device__ __forceinline__ T* opq(T* p) { asm volatile("" : "+l"(p)); return p; }

__device__ __forceinline__ void ln_finish(float s1, float s2, float& mean, float& inv) {
    const float md = s1 * (1.0f / DM);
    const float var = fmaxf(s2 * (1.0f / DM) - md * md, 0.f);
    mean = bfr(md);
    asm("rsqrt.approx.ftz.f32 %0, %1;" : "=f"(inv) : "f"(var + 1e-5f));
}
__device__ __forceinline__ void ln_stats(float& mean, float& inv) {
    const float4 a = lds128f(SM_ST), b = lds128f(SM_ST + 16), c = lds128f(SM_ST + 32), d = lds128f(SM_ST + 48);
    ln_finish(((a.y + a.w) + (b.y + b.w)) + ((c.y + c.w) + (d.y + d.w)), ((a.x + a.z) + (b.x + b.z)) + ((c.x + c.z) + (d.x + d.z)), mean, inv);
}
template <int SK, bool GRAM, typename AddrF>
__device__ __forceinline__ void gemv15(float (&cc)[3][4], float (&gr)[4], uint32_t (&pre)[9][4], AddrF ad, uint32_t px, uint32_t px2) {
    uint32_t x0[4], x1[4];
    lds128(px, x0[0], x0[1], x0[2], x0[3]);
    lds128(px + 64, x1[0], x1[1], x1[2], x1[3]);
    gr[0] = gr[1] = gr[2] = gr[3] = 0.f;
#pragma unroll
    for (int i = 0; i < 3; i++) {
        cc[i][0] = cc[i][1] = cc[i][2] = cc[i][3] = 0.f;
        mma16816v(cc[i], pre[i][0], pre[i][1], pre[i][2], pre[i][3], x0[0], x0[1]);
    }
#pragma unroll
    for (int i = 0; i < 3; i++) ldsm4t(ad(i) + 3 * SK, pre[i]);
    if (GRAM) mma16816v(gr, x0[0], 0u, x0[1], 0u, x0[0], x0[1]);
#pragma unroll
    for (int i = 0; i < 3; i++) mma16816v(cc[i], pre[3 + i][0], pre[3 + i][1], pre[3 + i][2], pre[3 + i][3], x0[2], x0[3]);
#pragma unroll
    for (int i = 0; i < 3; i++) ldsm4t(ad(i) + 4 * SK, pre[3 + i]);
    lds64(px2, x0[0], x0[1]);
    if (GRAM) mma16816v(gr, x0[2], 0u, x0[3], 0u, x0[2], x0[3]);
#pragma unroll
    for (int i = 0; i < 3; i++) mma16816v(cc[i], pre[6 + i][0], pre[6 + i][1], pre[6 + i][2], pre[6 + i][3], x1[0], x1[1]);
    if (GRAM) mma16816v(gr, x1[0], 0u, x1[1], 0u, x1[0], x1[1]);
#pragma unroll
    for (int i = 0; i < 3; i++) mma16816v(cc[i], pre[i][0], pre[i][1], pre[i][2], pre[i][3], x1[2], x1[3]);
    if (GRAM) mma16816v(gr, x1[2], 0u, x1[3], 0u, x1[2], x1[3]);
    if (GRAM) mma16816v(gr, x0[0], 0u, x0[1], 0u, x0[0], x0[1]);
#pragma unroll
    for (int i = 0; i < 3; i++) mma16816v(cc[i], pre[3 + i][0], pre[3 + i][1], pre[3 + i][2], pre[3 + i][3], x0[0], x0[1]);
}
__device__ __forceinline__ void gemv15r(float (&cc)[3][4], float (&gr)[4], const uint32_t (&pre)[9][4], const uint32_t (&ext)[45][4], uint32_t px, uint32_t px2) {
    uint32_t x0[4], x1[4], x2[2];
    lds128(px, x0[0], x0[1], x0[2], x0[3]);
    lds128(px + 64, x1[0], x1[1], x1[2], x1[3]);
    lds64(px2, x2[0], x2[1]);
    gr[0] = gr[1] = gr[2] = gr[3] = 0.f;
#pragma unroll
    for (int ks = 0; ks < 5; ks++) {
        const uint32_t b0 = ks < 2 ? x0[2 * (ks & 1)] : ks < 4 ? x1[2 * (ks & 1)] : x2[0], b1 = ks < 2 ? x0[2 * (ks & 1) + 1] : ks < 4 ? x1[2 * (ks & 1) + 1] : x2[1];
        mma16816v(gr, b0, 0u, b1, 0u, b0, b1);
#pragma unroll
        for (int i = 0; i < 3; i++) {
            if (ks == 0) cc[i][0] = cc[i][1] = cc[i][2] = cc[i][3] = 0.f;
            const uint32_t (&f)[4] = ks < 3 ? pre[ks < 3 ? 3 * ks + i : 0] : ext[ks < 3 ? 0 : 3 * (ks - 3) + i];
            mma16816v(cc[i], f[0], f[1], f[2], f[3], b0, b1);
        }
    }
}

__device__ __forceinline__ void load_ffn(const Maps& maps, int b, uint32_t dst, uint32_t bar) {
    const bool gu = b < NG;
    mbar_expect_tx(bar, gu ? 61440 : 49152);
    tma3d(dst, gu ? (b < NG / 2 ? &maps.w1 : &maps.w3) : &maps.w2, gu ? 48 * (b & (NG / 2 - 1)) : 16 * (b - DN0), 0, 0, bar, POL_EF);
}

__device__ __forceinline__ void load_wo(const Maps& maps, uint32_t dst, int h, int c, uint32_t bar, int nbox) {
#pragma unroll 1
    for (int i = 0; i < nbox; i++) {
        mbar_expect_tx(bar + 8 * i, 12288);
        tma3d(dst + i * 12288, &maps.wo, 0, h * DH, 5 * c + i, bar + 8 * i, POL_EF);
    }
}

__global__ void __launch_bounds__(NT, 1)
decode_kernel(const __grid_constant__ Maps maps, const __nv_bfloat16* __restrict__ x_in, __nv_bfloat16* __restrict__ out) {
    extern __shared__ __align__(1024) unsigned char smem[];
    const int tid = threadIdx.x;
    const int wu = __shfl_sync(0xffffffffu, tid >> 5, 0);
    const int b = blockIdx.x, h = b >> 2, c = b & 3;
    if (smem_u32(smem) != SB) return;

    {
        const int warp = tid >> 5, lane = tid & 31;
        const uint32_t rbar = SM_BAR + warp * 16;
        if (lane == 0) {
            if (warp == 0) {
                mbar_init(QBAR, 1);
                asm volatile("fence.mbarrier_init.release.cluster;" ::: "memory");
                mbar_expect_tx(QBAR, 61440);
                tma5d(SM_Q, &maps.wq, 3 * h, 2 * c, QBAR, POL_EF);
            }
            mbar_init(rbar, 1); mbar_init(rbar + 8, 1); mbar_init(SM_XBAR + warp * 8, 1);
            mbar_init(FBAR + 8 * max(warp - 1, 0), warp == 7 ? 2 : 1);
            asm volatile("fence.mbarrier_init.release.cluster;" ::: "memory");
            if (warp >= 1 && warp < 7) {
                const CUtensorMap* mp = warp == 1 ? &maps.k : warp == 2 ? &maps.v : warp == 3 ? &maps.wo : warp == 4 ? &maps.w1 : warp == 5 ? &maps.w3 : &maps.w2;
                asm volatile("prefetch.tensormap [%0];" ::"l"(mp) : "memory");
            }
        }
        if (tid == 96) sts32(SM_MISC + 8, 0u);
        if (lane < 2) sts32(SM_KX + warp * 96 + 4 * lane, 0u);
        if (tid >= 128 && tid < 148) {
            const float v = f_(tid < 138 ? ONES : 0u);
            sts128(SM_ONE + 16 * (tid - 128), v, v, v, v);
        }
        if (b == 0 && tid == 255) asm volatile("st.relaxed.gpu.global.u32 [%0], %1;" ::"l"(maps.scr->ticket), "r"(0) : "memory");
        if (tid < 4) st_pkt(reinterpret_cast<uint4*>(&maps.scr->mx[h * 32 + c * 8]) + tid, 0, 0, 0, 0);
        if (tid >= 64 && tid < 66 && b < 108) st_pkt(&maps.scr->acc[1][(2 * b + tid - 64)], 0, 0, 0, 0);
        __syncthreads();
        if (lane == 0) {
            const int row = ROW0(warp);
            mbar_expect_tx(rbar, TILE);
            tma2d(SM_RING + warp * 2 * TILE, &maps.k, 0, row, rbar, POL_EF);
            mbar_expect_tx(rbar + 8, TILE);
            tma2d(SM_RING + (warp * 2 + 1) * TILE, &maps.k, 0, row + TS, rbar + 8, POL_EF);
        }
    }

    uint32_t kr[45][4];
#define KR(n) kr[(n) >> 2][(n) & 3]
    const float SC = 0.07216878364870322f * 1.4426950408889634f;
    int role = 0;
    uint32_t wk[3][4];

#pragma unroll 1
    for (int layer = 0; layer < 2; layer++) {
        const uint32_t tag = layer + 1, tbit = layer ^ 1;
        uint2 xv = make_uint2(0u, 0u);
        uint32_t qo;
        {
            const int tl = opq(tid), warp = tl >> 5, lane = tl & 31, g = lane >> 2, t = lane & 3, mat = lane >> 3, r8 = lane & 7;
            const int kh = warp >> 2, mg = warp & 3;
            const uint32_t aq = SM_Q + kh * TILE + ((mat >> 1) * 8 + r8) * 128 + (((2 * mg + (mat & 1)) ^ r8) << 4);
            if (layer == 0 && tl < 160) xv = reinterpret_cast<const uint2*>(x_in)[tl];
            mbar_wait(QBAR, 0);
            uint32_t pre[9][4];
#pragma unroll
            for (int n = 0; n < 9; n++) ldsm4t(aq + (n % 3) * 2048 + (n / 3) * 2 * TILE, pre[n]);
            if (layer == 1) {
                pin(ALL6(pre, 0) | ALL6(pre, 3));
                __syncthreads();
                delay(role >= DN0 + NDN ? 1500 : 0);
                if (role >= DN0 && role < DN0 + NDN) {
                    if (wu < 6) tile_load(SM_Q + wu * TILE, &maps.k, ROW0(wu) + 5 * TS, SM_XBAR + wu * 8);
                } else if (wu == 7) {
#pragma unroll 1
                    for (int w = 0; w < 6; w++) tile_load(SM_Q + w * TILE, &maps.k, ROW0(w) + 5 * TS, SM_XBAR + w * 8);
                }
            }
            const uint32_t pm = opq(g == 1 ? SM_ONE : SM_XS + 160 * (2 * c + kh) + 16 * t);
            const uint32_t pm2 = opq(pm + 128 - (g == 1 ? 0 : 8 * t));
            const uint32_t dq = opq(SM_R + 768 * kh + 4 * (16 * mg + g));
            qo = pin(16u * (b * 48 + (tl & 63) + (tl >= 64 ? NCTA * 48 : 0)));
            if (tl < 160) {
                const uint32_t xa0 = opq(SM_XS + 4 * xpos(2 * tl));
                const bool xl = tl % 20 < 16;
                if (layer == 1) {
                    const uint4* px = opq(&maps.scr->ay[tl]);
                    uint4 v;
                    int it = 0;
                    bool more;
                    do { v = ld_pkt(px); more = ++it < SPIN_CAP; } while (!__all_sync(0xffffffffu, (v.y & v.w) == 1) && more);
                    xv = make_uint2(v.x, v.z);
                }
                sts32(xa0, xv.x);
                if (xl) sts32(xa0 + 16, xv.y); else sts32(xa0 + 8, xv.y);
            }
            __syncthreads();
            float cc[3][4], gr[4];
            gemv15<2 * TILE, false>(cc, gr, pre, [&](int i) { return aq + i * 2048; }, pm, pm2);
            if (t == 0) {
#pragma unroll
                for (int i = 0; i < 3; i++) { sts32(dq + 256 * i, cc[i][0]); sts32(dq + 256 * i + 32, cc[i][2]); }
                if (layer == 0) {
#pragma unroll
                    for (int i = 0; i < 3; i++) { sts32(dq + 256 * i + 1536, cc[i][1]); sts32(dq + 256 * i + 1568, cc[i][3]); }
                }
            }
        }
        {
            const int tl = opq(tid), j = tl & 63;
            const bool snd = j < 48 && (tl < 64 || (tl < 128 && layer == 0));
            const uint32_t fa = opq(SM_R + 16 * tl + (tl >= 64 ? 512 : 0));
            uint4* pq = reinterpret_cast<uint4*>(reinterpret_cast<char*>(maps.scr->qx) + qo);
            __syncthreads();
            if (snd) {
                const float4 u = lds128f(fa), v = lds128f(fa + 768);
                st_pktf(pq, u.x + v.x, u.y + v.y, u.z + v.z, u.w + v.w, tbit);
            }
            if (layer == 1 && wu >= 5) {
                delay(300);
                if (wu >= 6) tile_load(SM_Q + wu * TILE, &maps.k, ROW0(wu) + 5 * TS, SM_XBAR + wu * 8);
                else if (role < NG && elect_one()) {
                    mbar_expect_tx(WBAR + 32, 12288);
                    tma3d(SM_Q + 4 * 12288, &maps.wo, 0, h * DH, 5 * c + 4, WBAR + 32, POL_EF);
                }
            }
            if (layer == 1 && tl >= 192 && tl < 194 && b < 108) st_pkt(&maps.scr->acc[0][(2 * b + tl - 192)], 0, 0, 0, 0);
        }

        float sc0 = -INFINITY, sc1 = -INFINITY, sc2 = 0.f, sc3 = 0.f, mw;
        uint32_t pk0, pk1;
        float acc[3][4];
        {
            const uint32_t ring = SM_RING + wu * 2 * TILE, rb = SM_BAR + wu * 16;
            const uint32_t xtile = SM_Q + wu * TILE, xb = SM_XBAR + wu * 8;
            const int row0 = ROW0(wu);
            const uint32_t bt = SM_B + wu * TILE;
            auto issue1 = [&](int n, uint32_t dep, bool vph) {
                const CUtensorMap* mp = n < 8 ? &maps.k : &maps.v;
                const int row = row0 + ((n + (n >= 8 ? 2 : 0)) & 7) * TS;
                if (vph && wu < L1R && n == 12 - (wu & 1)) {
                    tile_load_l1(ring + (n & 1) * TILE, maps.vp, row, rb + (n & 1) * 8, opq(tid) & 31);
                    return;
                }
                const int k = vph || n >= 6 ? n & 1 : n >= 3 ? n - 3 : n;
                tile_load(k == 2 ? bt : ring + k * TILE, mp, row + dep, k == 2 ? xb : rb + k * 8);
                if ((maps.rt[wu] >> n) & 1) tile_keep(n < 8 ? &maps.ks : &maps.vs, row);
            };
            auto refill1 = [&](int s, uint32_t dep, bool vph = false) { issue1(s + 2, dep, vph); };
#define K_OFF(i) ((uint32_t)((3 * ((g >> 1) + 4 * (g & 1)) + ((i) >> 1)) * 128 + ((t ^ ((3 * ((g >> 1) + 4 * (g & 1)) + ((i) >> 1)) & 7) ^ (((i) & 1) << 2)) << 4)))
#define V_OFF(i) ((uint32_t)((6 * t + (i)) * 128 + ((g ^ ((6 * t + (i)) & 7)) << 4)))
#define LANE_IDS const int tl = opq(tid), lane = tl & 31, g = lane >> 2, t = lane & 3; (void)tl; (void)lane; (void)g; (void)t;
            const uint32_t kx = SM_KX + wu * 96;
#pragma unroll 1
            for (int s = layer ? 5 : 0; s < 5 + layer; s++) {
                if (s < 5) {
                    LANE_IDS
                    const int k = s >= 3 ? s - 3 : s;
                    mbar_wait(k == 2 ? xb : rb + k * 8, s >= 3);
                    refill1(s, 0);
                    const uint32_t tile = k == 2 ? bt : ring + k * TILE;
                    uint32_t mx = 0u, mn = 0xffffffffu, mn2 = 0xffffffffu;
#pragma unroll
                    for (int q = 0; q < 12; q++) {
                        uint32_t a0, a1, a2, a3;
                        lds128(tile + K_OFF(q % 6) + (q / 6) * 3072, a0, a1, a2, a3);
                        a0 &= 0x7fff7fffu; a1 &= 0x7fff7fffu; a2 &= 0x7fff7fffu; a3 &= 0x7fff7fffu;
                        mx = __vimax3_u16x2(__vimax3_u16x2(mx, a0, a1), a2, a3);
                        mn = __viaddmin_u16x2(a0, 0xffffffffu, __viaddmin_u16x2(a1, 0xffffffffu, mn));
                        mn2 = __viaddmin_u16x2(a2, 0xffffffffu, __viaddmin_u16x2(a3, 0xffffffffu, mn2));
                    }
                    mn = __vminu2(mn, mn2);
                    const uint32_t emax = __reduce_max_sync(0xffffffffu, max(mx & 0xffffu, mx >> 16)) >> 7;
                    const uint32_t base = (max(emax, 16u) - 15u) << 7, lim = base + 0x7fu;
                    bool raw = emax < 80u || emax > 190u;
                    uint32_t fl = __ballot_sync(0xffffffffu, min(mn & 0xffffu, mn >> 16) < lim);
                    if (!raw && fl) {
                        const uint32_t n0 = lds32(kx);
                        __syncwarp();
#pragma unroll 1
                        for (; fl; fl &= fl - 1) {
                            const int g = (__ffs(fl) - 1) >> 2, t = (__ffs(fl) - 1) & 3, q = min(lane, 23) >> 1, i = q >= 6 ? q - 6 : q;
                            const uint32_t a = tile + K_OFF(i) + (q >= 6 ? 3072 : 0) + 8 * (lane & 1);
                            uint32_t w0, w1;
                            lds64(a, w0, w1);
#pragma unroll 1
                            for (int e = 0; e < 4; e++) {
                                const uint32_t x = __funnelshift_r(w0, w1, 16 * e) & 0xffffu;
                                if (e == 1) w0 = w1;
                                if ((x & 0x7fffu) - 1u < lim && lane < 24) {
                                    uint32_t n;
                                    asm volatile("atom.shared.add.u32 %0, [%1], 1;" : "=r"(n) : "r"(kx) : "memory");
                                    if (n < NEXC) sts32(kx + 32 + 4 * n, x | (2 * ((2 * t + (e >> 1)) * 12 + 2 * i + (lane & 1)) + (e & 1)) << 16 | (16 * (s & 4) + (q >= 6 ? 32 : 0) + 4 * g + (s & 3)) << 24);
                                    sts16(a + 2 * e, 0u);
                                }
                            }
                        }
                        __syncwarp();
                        raw = lds32(kx) > NEXC;
                        __syncwarp();
                        if (raw && lane == 0) sts32(kx, n0);
                    }
                    if (lane == 0) {
                        sts32(kx + 8 + 4 * s, (base + (31u << 7)) << 16);
                        if (raw) sts32(kx + 4, lds32(kx + 4) | 1u << s);
                    }
                    const uint32_t b2 = (0x10000u - base) * 0x10001u;
                    auto pack = [&](auto S) {
                        constexpr int n0 = 36 * decltype(S)::value;
#pragma unroll
                        for (int q = 0; q < 12; q++) {
                            uint32_t a0, a1, a2, a3;
                            lds128(tile + K_OFF(q % 6) + (q / 6) * 3072, a0, a1, a2, a3);
                            a0 = __viaddmax_s16x2(a0 & 0x7fff7fffu, b2, 0u) | (a0 & 0x80008000u); a1 = __viaddmax_s16x2(a1 & 0x7fff7fffu, b2, 0u) | (a1 & 0x80008000u);
                            a2 = __viaddmax_s16x2(a2 & 0x7fff7fffu, b2, 0u) | (a2 & 0x80008000u); a3 = __viaddmax_s16x2(a3 & 0x7fff7fffu, b2, 0u) | (a3 & 0x80008000u);
                            KR(n0 + 3 * q) = __byte_perm(a0, a1, 0x6420);
                            KR(n0 + 3 * q + 1) = __byte_perm(a2, a3, 0x6420);
                            const uint32_t ho = __byte_perm(a2, a3, 0x7531);
                            KR(n0 + 3 * q + 2) = __byte_perm(a0, a1, 0x7531) | __funnelshift_r(ho, ho, 4);
                        }
                    };
                    switch (s) {
                        case 0: pack(IC<0>()); break;
                        case 1: pack(IC<1>()); break;
                        case 2: pack(IC<2>()); break;
                        case 3: pack(IC<3>()); break;
                        default: pack(IC<4>()); break;
                    }
                    __syncwarp();
                }
                if (wu < 2 && (s == 3 || layer)) {
                    const int tc = min(opq(tid), 47);
                    const uint4* pq = opq(&maps.scr->qx[h * 4 * 48 + tc]);
                    uint4 v[4];
                    int it = 0;
                    bool more = true;
#pragma unroll
                    for (int k = 0; k < 4; k++) v[k] = ld_pkt(pq + 48 * k);
                    if (layer == 0) {
                        uint4 u[4];
                        do {
#pragma unroll
                            for (int k = 0; k < 4; k++) u[k] = ld_pkt(pq + NCTA * 48 + 48 * k);
                            more = ++it < SPIN_CAP;
                        } while (!__all_sync(0xffffffffu, u[0].w & u[1].w & u[2].w & u[3].w & 1) && more);
                        sts128(SM_CS + 16 * tc, (f_(u[0].x) + f_(u[1].x)) + (f_(u[2].x) + f_(u[3].x)), (f_(u[0].y) + f_(u[1].y)) + (f_(u[2].y) + f_(u[3].y)),
                               (f_(u[0].z) + f_(u[1].z)) + (f_(u[2].z) + f_(u[3].z)), (f_(u[0].w) + f_(u[1].w)) + (f_(u[2].w) + f_(u[3].w)));
                    }
                    float mean, inv;
                    {
                        const int lane = opq(tid) & 31;
                        uint32_t xw[10];
                        lds128(SM_XS + 16 * lane, xw[0], xw[1], xw[2], xw[3]);
                        lds128(SM_XS + 512 + 16 * lane, xw[4], xw[5], xw[6], xw[7]);
                        lds64(SM_XS + 1024 + 8 * lane, xw[8], xw[9]);
                        float s1 = 0.f, s2 = 0.f, s3 = 0.f, s4 = 0.f;
#pragma unroll
                        for (int i = 0; i < 10; i++) { const float e0 = bf_lo(xw[i]), e1 = bf_hi(xw[i]); s1 += e0; s3 += e1; s2 = fmaf(e0, e0, s2); s4 = fmaf(e1, e1, s4); }
                        s1 += s3; s2 += s4;
                        const bool lo = lane < 16;
                        float sv = (lo ? s1 : s2) + __shfl_xor_sync(0xffffffffu, lo ? s2 : s1, 16);
#pragma unroll
                        for (int o = 8; o > 0; o >>= 1) sv += __shfl_xor_sync(0xffffffffu, sv, o);
                        const float so = __shfl_xor_sync(0xffffffffu, sv, 16);
                        ln_finish(lo ? sv : so, lo ? so : sv, mean, inv);
                    }
                    const float4 cs = lds128f(SM_CS + 16 * tc);
                    mean *= -inv;
                    const float m0 = pin(mean * cs.x), m1 = pin(mean * cs.y), m2 = pin(mean * cs.z), m3 = pin(mean * cs.w);
                    const int w = 2 * tc;
                    const uint32_t qd = pin(SM_QS + 4 * (((w >> 2) & 3) * 24 + 2 * (w >> 4) + ((w >> 1) & 1)));
                    while (__any_sync(0xffffffffu, ((v[0].w ^ tbit) | (v[1].w ^ tbit) | (v[2].w ^ tbit) | (v[3].w ^ tbit)) & 1) && more) {
#pragma unroll
                        for (int k = 0; k < 4; k++) v[k] = ld_pkt(pq + 48 * k);
                        more = ++it < SPIN_CAP;
                    }
                    const float q0 = fmaf(inv, (f_(v[0].x) + f_(v[1].x)) + (f_(v[2].x) + f_(v[3].x)), m0), q1 = fmaf(inv, (f_(v[0].y) + f_(v[1].y)) + (f_(v[2].y) + f_(v[3].y)), m1);
                    const float q2 = fmaf(inv, (f_(v[0].z) + f_(v[1].z)) + (f_(v[2].z) + f_(v[3].z)), m2), q3 = fmaf(inv, (f_(v[0].w) + f_(v[1].w)) + (f_(v[2].w) + f_(v[3].w)), m3);
                    sts32(qd, pack2(q0, q1));
                    sts32(qd + 48, pack2(q2, q3));
                    __syncwarp();
                    if (elect_one()) asm volatile("mbarrier.arrive.shared::cta.b64 _, [%0];" ::"r"(QRDY) : "memory");
                }
            }
            uint32_t qa, ka[3];
            {
                LANE_IDS
                qa = opq(SM_QS + (2 * t + (g & 1)) * 48);
#pragma unroll
                for (int i = 0; i < 3; i++) ka[i] = opq(xtile + K_OFF(2 * i));
            }
            uint32_t f[6][4];
            if (layer == 1) {
                if (wu >= 2 && wu < 5) delay(300);
                mbar_wait(xb, 0);
            }
#pragma unroll
            for (int i = 0; i < 6; i++) lds128(ka[i >> 1] ^ ((i & 1) << 6), f[i][0], f[i][1], f[i][2], f[i][3]);
            if (layer == 1) {
                __syncwarp();
                half_load(xtile, &maps.kh, row0 + 6 * TS + AFTER(ALL6(f, 0)), xb, true);
            }
            mbar_wait(QRDY, layer);
            {
                uint32_t qf[12];
#pragma unroll
                for (int i = 0; i < 3; i++) lds128(qa + 16 * i, qf[4 * i], qf[4 * i + 1], qf[4 * i + 2], qf[4 * i + 3]);
                const int t = opq(tid) & 3;
                auto kr_scores = [&](auto TAU, float& sa, float& sb) {
                    constexpr int tau = decltype(TAU)::value;
                    float cc[2][4] = {{0.f, 0.f, 0.f, 0.f}, {0.f, 0.f, 0.f, 0.f}};
#pragma unroll
                    for (int n = 0; n < 12; n++) {
                        const int q = (n & 1) * 6 + (n >> 1), i = n >> 1;
                        const uint32_t l0 = KR(36 * tau + 3 * q), l1 = KR(36 * tau + 3 * q + 1), hh = KR(36 * tau + 3 * q + 2);
                        const uint32_t h0 = hh & 0x87878787u, h1 = __funnelshift_l(hh, hh, 4) & 0x87878787u;
                        mma16816(cc[n & 1], __byte_perm(l0, h0, 0x5140), __byte_perm(l0, h0, 0x7362), __byte_perm(l1, h1, 0x5140), __byte_perm(l1, h1, 0x7362), qf[2 * i], qf[2 * i + 1]);
                    }
                    if (t == (tau & 3)) { sa = cc[0][0] + cc[0][3]; sb = cc[1][0] + cc[1][3]; }
                };
                auto stage_v = [&](auto S) {
                    constexpr int s = decltype(S)::value;
                    const int lane = opq(tid) & 31, g = lane >> 2, t = lane & 3;
#pragma unroll
                    for (int i = 0; i < 6; i++) {
                        const uint32_t a = ring + s * TILE + V_OFF(i);
                        lds128(a, kr[12 * s + i][0], kr[12 * s + i][1], kr[12 * s + i][2], kr[12 * s + i][3]);
                        lds128(a + 3072, kr[12 * s + 6 + i][0], kr[12 * s + 6 + i][1], kr[12 * s + 6 + i][2], kr[12 * s + 6 + i][3]);
                    }
                    __syncwarp();
                    tile_load(ring + s * TILE, s ? &maps.v : &maps.k, row0 + (s ? 2 : 7) * TS + AFTER(ALL6(kr, 12 * s) | ALL6(kr, 12 * s + 6)), rb + s * 8);
                };
                if (layer == 1) {
                    float cA[4] = {0.f, 0.f, 0.f, 0.f}, cB[4] = {0.f, 0.f, 0.f, 0.f};
#pragma unroll
                    for (int i = 0; i < 6; i++) {
                        mma16816v(cA, f[i][0], f[i][1], f[i][2], f[i][3], qf[2 * i], qf[2 * i + 1]);
                        lds128((opq(ka[i >> 1]) ^ ((i & 1) << 6)) + 3072, f[i][0], f[i][1], f[i][2], f[i][3]);
                    }
                    __syncwarp();
                    half_load(xtile + 3072, &maps.kh, row0 + 6 * TS + 24 + AFTER(ALL6(f, 0)), xb, false);
#pragma unroll
                    for (int i = 0; i < 6; i++) mma16816v(cB, f[i][0], f[i][1], f[i][2], f[i][3], qf[2 * i], qf[2 * i + 1]);
                    sc2 = cA[0] + cA[3]; sc3 = cB[0] + cB[3];
                }
#pragma unroll
                for (int i = 0; i < 12; i++) qf[i] = mul2(qf[i], 0x6f806f80u);
                kr_scores(IC<0>(), sc0, sc1);
                kr_scores(IC<1>(), sc0, sc1);
                if (layer == 1) stage_v(IC<0>());
                kr_scores(IC<2>(), sc0, sc1);
                if (layer == 1) stage_v(IC<1>());
                kr_scores(IC<3>(), sc0, sc1);
                kr_scores(IC<4>(), sc2, sc3);
                {
                    LANE_IDS
                    const float sa = f_(lds32(kx + 8 + 4 * t)), sb = t == 0 ? f_(lds32(kx + 24)) : 1.0f;
                    const int nx = (int)lds32(kx);
                    uint32_t rm = lds32(kx + 4), qm = 0u;
#pragma unroll
                    for (int i = 0; i < 6; i++) qm = __vimax3_u16x2(qm, qf[2 * i] & 0x7fff7fffu, qf[2 * i + 1] & 0x7fff7fffu);
#pragma unroll
                    for (int i = 0; i < 3; i++) lds128(SM_QS + (2 * t + (g & 1)) * 48 + 16 * i, qf[4 * i], qf[4 * i + 1], qf[4 * i + 2], qf[4 * i + 3]);
                    if (__any_sync(0xffffffffu, max(qm & 0xffffu, qm >> 16) >= 0x7f80u)) rm = 31;
                    sc0 *= sa; sc1 *= sa; sc2 *= sb; sc3 *= sb;
                    if (nx) {
                        const uint32_t w = lds32(kx + 32 + 4 * (lane & 15));
                        const float d = bf_lo(lds16(SM_QS + ((w >> 15) & 0x1fe))) * bf_lo(w);
#pragma unroll 1
                        for (int n = 0; n < nx; n++) {
                            const uint32_t k = (__shfl_sync(0xffffffffu, w, n) >> 24) ^ lane;
                            const float dn = __shfl_sync(0xffffffffu, d, n);
                            if (k == 0) sc0 += dn;
                            if (k == 32) sc1 += dn;
                            if (k == 64) sc2 += dn;
                            if (k == 96) sc3 += dn;
                        }
                    }
#pragma unroll 1
                    for (; rm; rm &= rm - 1) {
                        const int tau = __ffs(rm) - 1;
#pragma unroll 1
                        for (int hf = 0; hf < 2; hf++) {
                            const char* gp = static_cast<const char*>(maps.kp) + (size_t)(row0 + tau * TS) * 128 + (8 * hf + (g >> 1) + 4 * (g & 1)) * 384 + 16 * t;
                            float cA[4] = {0.f, 0.f, 0.f, 0.f};
#pragma unroll
                            for (int i = 0; i < 6; i++) {
                                const uint4 a = __ldcg(reinterpret_cast<const uint4*>(gp + 64 * i));
                                mma16816(cA, a.x, a.y, a.z, a.w, qf[2 * i], qf[2 * i + 1]);
                            }
                            if ((tau & 3) == t) {
                                const int k = hf + (tau >> 2) * 2;
                                const float d = cA[0] + cA[3];
                                if (k == 0) sc0 = d; else if (k == 1) sc1 = d; else if (k == 2) sc2 = d; else sc3 = d;
                            }
                        }
                    }
                }
                if (layer == 0) {
                    LANE_IDS
#pragma unroll 1
                    for (int s = 5; s < 8; s++) {
                        mbar_wait(s == 5 ? xb : rb + (s & 1) * 8, s == 5);
                        const uint32_t tile = s == 5 ? bt : ring + (s & 1) * TILE;
                        float cA[4] = {0.f, 0.f, 0.f, 0.f}, cB[4] = {0.f, 0.f, 0.f, 0.f};
#pragma unroll
                        for (int i = 0; i < 6; i++) {
                            uint32_t a0, a1, a2, a3;
                            lds128(tile + K_OFF(i), a0, a1, a2, a3);
                            mma16816(cA, a0, a1, a2, a3, qf[2 * i], qf[2 * i + 1]);
                            lds128(tile + K_OFF(i) + 3072, a0, a1, a2, a3);
                            mma16816(cB, a0, a1, a2, a3, qf[2 * i], qf[2 * i + 1]);
                        }
                        if (t == (s & 3)) { sc2 = cA[0] + cA[3]; sc3 = cB[0] + cB[3]; }
                        __syncwarp();
                        refill1(s, AFTER(__float_as_uint(cA[0]) | __float_as_uint(cB[0])));
                    }
                } else {
                    LANE_IDS
#pragma unroll 1
                    for (int i = 2; i < 4; i++) {
                        const uint32_t tile = i == 3 ? ring : xtile, tb = i == 3 ? rb : xb;
                        mbar_wait(tb, 1);
#pragma unroll
                        for (int k = 0; k < 6; k++) {
                            const uint32_t a = tile + K_OFF(k);
                            lds128(a, kr[24 + k][0], kr[24 + k][1], kr[24 + k][2], kr[24 + k][3]);
                            lds128(a + 3072, kr[24 + 6 + k][0], kr[24 + 6 + k][1], kr[24 + 6 + k][2], kr[24 + 6 + k][3]);
                        }
                        float cA[4] = {0.f, 0.f, 0.f, 0.f}, cB[4] = {0.f, 0.f, 0.f, 0.f}, cC[4] = {0.f, 0.f, 0.f, 0.f}, cD[4] = {0.f, 0.f, 0.f, 0.f};
#pragma unroll
                        for (int k = 0; k < 3; k++) {
                            mma16816(cA, kr[24 + k][0], kr[24 + k][1], kr[24 + k][2], kr[24 + k][3], qf[2 * k], qf[2 * k + 1]);
                            mma16816(cB, kr[24 + 6 + k][0], kr[24 + 6 + k][1], kr[24 + 6 + k][2], kr[24 + 6 + k][3], qf[2 * k], qf[2 * k + 1]);
                            mma16816(cC, kr[24 + 3 + k][0], kr[24 + 3 + k][1], kr[24 + 3 + k][2], kr[24 + 3 + k][3], qf[6 + 2 * k], qf[7 + 2 * k]);
                            mma16816(cD, kr[24 + 9 + k][0], kr[24 + 9 + k][1], kr[24 + 9 + k][2], kr[24 + 9 + k][3], qf[6 + 2 * k], qf[7 + 2 * k]);
                        }
                        __syncwarp();
                        tile_load(tile, &maps.v, row0 + (i + 1) * TS + AFTER(__float_as_uint(cA[0]) | __float_as_uint(cB[0]) | __float_as_uint(cC[0]) | __float_as_uint(cD[0])), tb);
                        if (t == i) { sc2 = (cA[0] + cC[0]) + (cA[3] + cC[3]); sc3 = (cB[0] + cD[0]) + (cB[3] + cD[3]); }
                    }
                }
            }
            {
                const uint32_t mk = __reduce_max_sync(0xffffffffu, f2key(fmaxf(fmaxf(sc0, sc1), fmaxf(sc2, sc3))));
                if ((opq(tid) & 31) == 0) st_pkt2(&maps.scr->mx[h * 32 + c * 8 + wu], mk, tag);
                mw = key2f(mk);
            }
            pk0 = pack2(ex2((sc0 - mw) * SC), ex2((sc1 - mw) * SC));
            pk1 = pack2(ex2((sc2 - mw) * SC), ex2((sc3 - mw) * SC));
            sc2 = (bf_lo(pk0) + bf_hi(pk0)) + (bf_lo(pk1) + bf_hi(pk1));
#pragma unroll
            for (int o = 16; o > 0; o >>= 1) sc2 += __shfl_xor_sync(0xffffffffu, sc2, o);
#pragma unroll
            for (int s = 0; s < 3; s++) { acc[s][0] = acc[s][1] = acc[s][2] = acc[s][3] = 0.f; }
            auto head_ld = [&](int lane) { const uint2 mv = ld_pkt2(&maps.scr->mx[h * 32 + lane]); sc0 = f_(mv.x); sc1 = f_(mv.y); };
            auto head_factor = [&](int lane) {
                int it = 0;
                while (!__all_sync(0xffffffffu, __float_as_uint(sc1) == tag) && ++it < SPIN_CAP) head_ld(lane);
                sc3 = ex2((mw - key2f(__reduce_max_sync(0xffffffffu, __float_as_uint(sc0)))) * SC);
            };
#define P_CONSTS \
                const uint32_t sel0 = g == 0 ? 0x4410u : (g == 1 ? 0x1044u : 0x4444u); \
                const uint32_t sel1 = g == 2 ? 0x4410u : (g == 3 ? 0x1044u : 0x4444u); \
                const int src00 = 4 * (t < 2 ? 4 * t : 4 * (t - 2) + 1);
#define P_FRAGS(tau) \
                const uint32_t pk = ((tau) & 4) ? pk1 : pk0; \
                const uint32_t w0 = __shfl_sync(0xffffffffu, pk, src00 + ((tau) & 3)); \
                const uint32_t w1 = __shfl_sync(0xffffffffu, pk, src00 + ((tau) & 3) + 8); \
                uint32_t pb[4][2]; \
                _Pragma("unroll") for (int j = 0; j < 4; j++) { \
                    const uint32_t src = ((j & 1) ? w1 : w0) >> ((j >> 1) * 16); \
                    pb[j][0] = __byte_perm(src, 0, sel0); pb[j][1] = __byte_perm(src, 0, sel1); \
                }
            if (layer == 0) {
#pragma unroll 1
                for (int s = 8; s < 16; s++) {
                    LANE_IDS
                    P_CONSTS
                    if (s == 14) {
                        uint4* p = nullptr;
                        if (tl < 48) p = &maps.scr->qx[b * 48 + tl];
                        else if (tl < 98) p = &maps.scr->cx[b * 56 + tl - 48];
                        else if (tl < 145) {}
                        else if (tl >= 160) { if (tl < 208) p = &maps.scr->qc[b * 48 + tl - 160]; }
                        else if (b < NG) { if (tl < 153) p = &maps.scr->ah[b * 8 + tl - 145]; }
                        else if (b < DN0 + NDN && tl < 149) p = &maps.scr->ay[(b - DN0) * 4 + tl - 145];
                        if (p) st_pkt(p, 0, 0, 0, tl < 48);
                    }
                    if (s == 13) head_ld(lane);
                    P_FRAGS((s + 2) & 7)
                    mbar_wait(rb + (s & 1) * 8, ((s >> 1) + 1) & 1);
                    const uint32_t tile = ring + (s & 1) * TILE;
#pragma unroll
                    for (int j = 0; j < 4; j++) {
#pragma unroll
                        for (int u = 0; u < 3; u++) {
                            uint32_t a0, a1, a2, a3;
                            lds128(tile + (j >> 1) * 3072 + V_OFF(3 * (j & 1) + u), a0, a1, a2, a3);
                            mma16816(acc[u], a0, a1, a2, a3, pb[j][0], pb[j][1]);
                        }
                    }
                    __syncwarp();
                    if (s < 14) refill1(s, AFTER(__float_as_uint(acc[0][0]) | __float_as_uint(acc[1][0]) | __float_as_uint(acc[2][0])), true);
                    if (s == 13) head_factor(lane);
                    if (s == 15 && elect_one()) {
                        uint32_t n;
                        asm volatile("atom.shared.add.u32 %0, [%1], 1;" : "=r"(n) : "r"(SM_MISC + 8) : "memory");
                        if (n == 7) load_wo(maps, SM_B, h, c, WBAR, 5);
                    }
                }
            } else {
                LANE_IDS
                P_CONSTS
#pragma unroll
                for (int s = 0; s < 2; s++) {
                    P_FRAGS(s)
#pragma unroll
                    for (int j = 0; j < 4; j++) {
#pragma unroll
                        for (int u = 0; u < 3; u++) {
                            const int k = 6 * (j >> 1) + 3 * (j & 1) + u;
                            mma16816(acc[u], kr[12 * s + k][0], kr[12 * s + k][1], kr[12 * s + k][2], kr[12 * s + k][3], pb[j][0], pb[j][1]);
                        }
                    }
                }
#pragma unroll 1
                for (int i = 4; i < 10; i++) {
                    const int sl = i == 5 ? 0 : (i == 6 || i == 8 ? 1 : 2);
                    const uint32_t tile = sl ? ring + (sl - 1) * TILE : xtile, tb = sl ? rb + (sl - 1) * 8 : xb;
                    if (i == 8) head_ld(lane);
                    if (i == 9) head_factor(lane);
                    P_FRAGS(i - 2)
                    mbar_wait(tb, (0x310 >> i) & 1);
#pragma unroll
                    for (int k = 0; k < 6; k++) {
                        const uint32_t a = tile + V_OFF(k);
                        lds128(a, kr[24 + k][0], kr[24 + k][1], kr[24 + k][2], kr[24 + k][3]);
                        lds128(a + 3072, kr[24 + 6 + k][0], kr[24 + 6 + k][1], kr[24 + 6 + k][2], kr[24 + 6 + k][3]);
                    }
#pragma unroll
                    for (int j = 0; j < 4; j++) {
#pragma unroll
                        for (int u = 0; u < 3; u++) {
                            const int k = 6 * (j >> 1) + 3 * (j & 1) + u;
                            mma16816(acc[u], kr[24 + k][0], kr[24 + k][1], kr[24 + k][2], kr[24 + k][3], pb[j][0], pb[j][1]);
                        }
                    }
                    __syncwarp();
                    if (wu < L1R && i == 6 - 2 * (wu & 1)) tile_load_l1(tile, maps.vp, row0 + (6 - (wu & 1)) * TS, tb, lane);
                    else if (i == 4 || i == 6 || i == 7) tile_load(tile, &maps.v, row0 + (i == 4 ? 5 : i) * TS + AFTER(__float_as_uint(acc[0][0]) | __float_as_uint(acc[1][0]) | __float_as_uint(acc[2][0])), tb);
                    if (i == 7 && role < DN0 + NDN && elect_one()) {
                        uint32_t n;
                        asm volatile("atom.shared.add.u32 %0, [%1], 1;" : "=r"(n) : "r"(SM_MISC + 8) : "memory");
                        if (n == 15) load_wo(maps, SM_Q, h, c, WBAR, 3);
                    }
                }
            }
#undef P_FRAGS
#undef P_CONSTS
#undef LANE_IDS
#undef K_OFF
#undef V_OFF
        }

        uint32_t ticket = 0;
        {
            const int tl = opq(tid), warp = tl >> 5, lane = tl & 31, g = lane >> 2, t = lane & 3, mat = lane >> 3, r8 = lane & 7;
            {
                const uint32_t d = SM_R + 4 * (warp * 196 + 8 * g + 4 * t);
                if (t < 2) {
#pragma unroll
                    for (int u = 0; u < 3; u++) sts128(d + 256 * u, acc[u][0] * sc3, acc[u][1] * sc3, acc[u][2] * sc3, acc[u][3] * sc3);
                }
                if (lane == 0) sts128(d + 768, sc2 * sc3, 0.f, 0.f, 0.f);
            }
            const int tc = min(tl, 48);
            uint4* pc = opq(&maps.scr->cx[h * 4 * 56 + tc]);
            uint4* po = opq(pc + c * 56);
            const uint32_t fa = opq(SM_R + 16 * tc);
            __syncthreads();
            const int kg = warp >> 1, mg = warp & 1;
            const bool wo2 = layer && role < DN0 + NDN;
            const bool wo4 = layer && role < NG;
            uint32_t aw, oa, ob0, dw;
            uint32_t* tk;
            auto addrs = [&]() {
                aw = pin((wo2 ? SM_Q : SM_B) + (48 * kg + (mat >> 1) * 8 + r8) * 64 + (((2 * mg + (mat & 1)) ^ ((r8 >> 1) & 3)) << 4));
                oa = pin(SM_OS + 96 * kg + 8 * t);
                ob0 = pin(oa + 8 * t);
                dw = pin(SM_R + 4 * (4 * (16 * mg + g) + kg));
                tk = opq(maps.scr->ticket + 0);
            };
            uint32_t a[2][3][4];
            auto preload = [&]() {
#pragma unroll
                for (int i = 0; i < 2; i++) {
                    mbar_wait(WBAR + 8 * i, wo2);
#pragma unroll
                    for (int ks = 0; ks < 3; ks++) ldsm4t(aw + i * 12288 + ks * 1024, a[i][ks]);
                }
            };
            if (wu < 2) {
                if (tl < 49) {
                    float4 v[8];
#pragma unroll
                    for (int w = 0; w < 8; w++) v[w] = lds128f(fa + w * 784);
                    st_pktf(po, ((v[0].x + v[1].x) + (v[2].x + v[3].x)) + ((v[4].x + v[5].x) + (v[6].x + v[7].x)),
                            ((v[0].y + v[1].y) + (v[2].y + v[3].y)) + ((v[4].y + v[5].y) + (v[6].y + v[7].y)),
                            ((v[0].z + v[1].z) + (v[2].z + v[3].z)) + ((v[4].z + v[5].z) + (v[6].z + v[7].z)),
                            ((v[0].w + v[1].w) + (v[2].w + v[3].w)) + ((v[4].w + v[5].w) + (v[6].w + v[7].w)), tbit);
                }
                __syncwarp();
                uint4 v[4];
#pragma unroll
                for (int k = 0; k < 4; k++) v[k] = ld_pkt(pc + k * 56);
                asm volatile("bar.arrive 1, 256;" ::: "memory");
                addrs();
                const int w = 2 * tc, k3 = w / 24, r = w - 24 * k3;
                const uint32_t d0 = pin(tl < 48 ? SM_OS + 4 * (24 * k3 + (r < 16 ? 4 * (r & 3) + (r >> 2) : 16 + 2 * (r & 3) + ((r >> 2) & 1))) : SM_MISC);
                const uint32_t d1 = pin(tl < 48 ? d0 + (r < 16 ? 16 : 8) : SM_MISC + 12);
                int it = 0;
                bool more = true;
                while (__any_sync(0xffffffffu, ((v[0].w ^ tbit) | (v[1].w ^ tbit) | (v[2].w ^ tbit) | (v[3].w ^ tbit)) & 1) && more) {
#pragma unroll
                    for (int k = 0; k < 4; k++) v[k] = ld_pkt(pc + k * 56);
                    more = ++it < SPIN_CAP;
                }
                const float o0 = (f_(v[0].x) + f_(v[1].x)) + (f_(v[2].x) + f_(v[3].x));
                const uint32_t w0 = pack2(o0, (f_(v[0].y) + f_(v[1].y)) + (f_(v[2].y) + f_(v[3].y)));
                sts32(d1, pack2((f_(v[0].z) + f_(v[1].z)) + (f_(v[2].z) + f_(v[3].z)), (f_(v[0].w) + f_(v[1].w)) + (f_(v[2].w) + f_(v[3].w))));
                sts32(d0, tl < 48 ? w0 : __float_as_uint(o0));
                asm volatile("bar.arrive 2, 256;" ::: "memory");
                preload();
                asm volatile("bar.sync 3, 64;" ::: "memory");
            } else {
                addrs();
                asm volatile("bar.sync 1, 256;" ::: "memory");
                preload();
                asm volatile("bar.sync 2, 256;" ::: "memory");
            }
            uint32_t ob[6];
            lds128(ob0, ob[0], ob[1], ob[2], ob[3]);
            lds64(oa + 64, ob[4], ob[5]);
            if (tl == 224 && layer == 0)
                asm volatile("atom.relaxed.gpu.global.inc.u32 %0, [%1], 0x7fffffff;" : "=r"(ticket) : "l"(tk) : "memory");
            auto put = [&](int i, const float (&cc)[4]) { if (t == 0) { sts32(dw + 512 * i, cc[0]); sts32(dw + 512 * i + 128, cc[2]); } };
            {
                float c0[4] = {0.f, 0.f, 0.f, 0.f}, c1[4] = {0.f, 0.f, 0.f, 0.f}, c2[4] = {0.f, 0.f, 0.f, 0.f}, c3[4] = {0.f, 0.f, 0.f, 0.f};
                mbar_wait(WBAR + 16, wo2);
#pragma unroll
                for (int ks = 0; ks < 3; ks++) {
                    mma16816v(c0, a[0][ks][0], a[0][ks][1], a[0][ks][2], a[0][ks][3], ob[2 * ks], ob[2 * ks + 1]);
                    mma16816v(c1, a[1][ks][0], a[1][ks][1], a[1][ks][2], a[1][ks][3], ob[2 * ks], ob[2 * ks + 1]);
                    if (ks == 0 && layer == 0) {
                        mbar_wait(WBAR + 24, 0);
#pragma unroll
                        for (int k = 0; k < 3; k++) ldsm4t(aw + 3 * 12288 + k * 1024, wk[k]);
                    }
                    if (ks == 1) mbar_wait(WBAR + 32, wo4);
                    ldsm4t(aw + 2 * 12288 + ks * 1024, a[0][ks]);
                }
                const uint32_t aw4 = aw + (wo2 && !wo4 ? SM_B - SM_Q : 0) + 4 * 12288;
                ldsm4t(aw4 + 1024, a[1][0]);
#pragma unroll
                for (int ks = 0; ks < 3; ks++) {
                    mma16816v(c2, a[0][ks][0], a[0][ks][1], a[0][ks][2], a[0][ks][3], ob[2 * ks], ob[2 * ks + 1]);
                    mma16816v(c3, wk[ks][0], wk[ks][1], wk[ks][2], wk[ks][3], ob[2 * ks], ob[2 * ks + 1]);
                    if (ks == 0) { ldsm4t(aw4, a[0][0]); put(0, c0); put(1, c1); }
                    if (ks == 1) ldsm4t(aw4 + 2048, a[0][1]);
                }
                float c4[4] = {0.f, 0.f, 0.f, 0.f}, c5[4] = {0.f, 0.f, 0.f, 0.f};
                mma16816v(c4, a[0][0][0], a[0][0][1], a[0][0][2], a[0][0][3], ob[0], ob[1]);
                mma16816v(c5, a[1][0][0], a[1][0][1], a[1][0][2], a[1][0][3], ob[2], ob[3]);
                mma16816v(c4, a[0][1][0], a[0][1][1], a[0][1][2], a[0][1][3], ob[4], ob[5]);
                put(2, c2); put(3, c3);
                c4[0] += c5[0]; c4[2] += c5[2];
                put(4, c4);
            }
        }
        {
            const int tl = opq(tid);
            uint4* pr = opq(&maps.scr->acc[layer][54 * c + min(tl, 53)]);
            const uint32_t fa = opq(SM_R + 48 * tl);
            const float il = rcp(f_(lds32(SM_MISC)));
            __syncthreads();
            if (tl < 54) {
                const float4 v0 = lds128f(fa), v1 = lds128f(fa + 16), v2 = lds128f(fa + 32);
                const float y0 = il * ((v0.x + v0.y) + (v0.z + v0.w)), y1 = il * ((v1.x + v1.y) + (v1.z + v1.w)), y2 = il * ((v2.x + v2.y) + (v2.z + v2.w));
                red_pkt(pr, y0, tl == 53 ? 0.f : y1, tl == 53 ? 0.f : y2);
            }
            if (tl == 224 && layer == 0) {
                sts32(SM_MISC + 4, ticket);
                if (ticket < NG) load_ffn(maps, ticket, SM_B, FBAR);
            }
        }
        __syncthreads();
        if (layer == 0) role = __shfl_sync(0xffffffffu, (int)lds32(SM_MISC + 4), 0);
        const uint32_t DONE32 = 0x42000000u;
        if (role < NG) {
            const int tl = opq(tid), warp = tl >> 5, lane = tl & 31, g = lane >> 2, t = lane & 3, mat = lane >> 3, r8 = lane & 7;
            const uint32_t ag = SM_B + (80 * warp + (mat >> 1) * 8 + r8) * 96 + (((mat & 1) ^ (r8 >> 2)) << 4);
            constexpr int GI = 32, GK = 16 * 96;
            const bool on = (g & 1) == (t >> 1), isx = (on && g < 2) || g == 4;
            const uint32_t pm = opq(isx ? SM_XS + 160 * warp + 16 * t : (on || g == 5 ? SM_ONE : SM_ZERO)), pm2 = opq(pm + 128 - (isx ? 8 * t : 0));
            const uint32_t dg = opq(SM_R + 4 * (2 * (warp * 48 + g) + t));
            const uint32_t ho = pin(16u * (role * 8 + 4 * warp + ((lane * 11) >> 5)));
            const uint32_t fa = pin(SM_R + 8 * (24 * warp + 2 * min(lane, 11)));
            uint32_t pre[9][4];
            {
                bool hx = wu == 7;
                int it = 0;
                const uint4* px = opq(&maps.scr->acc[layer][min(tl, 215)]);
                const int cq = tl / 54, r = tl - 54 * cq, k0 = min(160 * cq + 3 * r, DM - 1);
                const uint32_t w0 = SM_XS + 4 * xpos(k0 >> 1), w1 = SM_XS + 4 * xpos(min((k0 >> 1) + 1, DM / 2 - 1));
                const bool two = tl < 216 && r != 53;
                const uint32_t e0 = opq(tl < 216 ? w0 + 2 * (k0 & 1) : SM_MISC + 12);
                const uint32_t e1 = opq(two ? ((k0 & 1) ? w1 : w0 + 2) : SM_MISC + 12), e2 = opq(two ? w1 + 2 * (k0 & 1) : SM_MISC + 12);
                const uint32_t x01 = opq(lds16(e0) | (lds16(e1) << 16)), x2 = lds16(e2);
                auto take_x = [&](const uint4 v) {
                    if (__all_sync(0xffffffffu, v.w == DONE32)) {
                        hx = true;
                        const uint32_t y01 = add2(x01, pack2(f_(v.x), f_(v.y))), y2 = add2(x2, pack2(f_(v.z), 0.f));
                        sts16(e0, y01); sts16(e1, y01 >> 16); sts16(e2, y2);
                    }
                };
                while (!mbar_test(FBAR, 0) && ++it < SPIN_CAP) { if (!hx) take_x(ld_pkt(px)); }
                uint4 v = make_uint4(0u, 0u, 0u, 0u);
                if (!hx) v = ld_pkt(px);
#pragma unroll
                for (int n = 0; n < 9; n++) ldsm4t(ag + (n % 3) * GI + (n / 3) * GK, pre[n]);
                if (layer) {
#pragma unroll
                    for (int n = 9; n < 15; n++) ldsm4t(ag + (n % 3) * GI + (n / 3) * GK, kr[n - 9]);
                }
                if (!hx) {
                    bool more = true;
                    while (!__all_sync(0xffffffffu, v.w == DONE32) && more) { v = ld_pkt(px); more = ++it < SPIN_CAP; }
                    const uint32_t y01 = add2(x01, pack2(f_(v.x), f_(v.y))), y2 = add2(x2, pack2(f_(v.z), 0.f));
                    sts16(e0, y01); sts16(e1, y01 >> 16); sts16(e2, y2);
                }
            }
            __syncthreads();
            {
                float cc[3][4], gr[4];
                if (layer) gemv15r(cc, gr, pre, kr, pm, pm2);
                else gemv15<GK, true>(cc, gr, pre, [&](int i) { return ag + i * GI; }, pm, pm2);
                if (t < 2) {
#pragma unroll
                    for (int i = 0; i < 3; i++) { sts32(dg + 128 * i, cc[i][0] + cc[i][3]); sts32(dg + 128 * i + 64, cc[i][1] + cc[i][2]); }
                }
                if ((lane | 4) == 22) sts32(SM_ST + 8 * warp + (g & 1) * 4, gr[0]);
            }
            uint4* ph = reinterpret_cast<uint4*>(reinterpret_cast<char*>(maps.scr->ah) + ho);
            const bool snd = (0x249 >> lane) & 1;
            __syncthreads();
            if (wu < 2) {
                float mean, inv;
                float4 v[8];
#pragma unroll
                for (int w = 0; w < 8; w++) v[w] = lds128f(fa + w * 384);
                ln_stats(mean, inv);
                const float ga = inv * ((((v[0].x + v[1].x) + (v[2].x + v[3].x)) + ((v[4].x + v[5].x) + (v[6].x + v[7].x))) -
                                        mean * (((v[0].y + v[1].y) + (v[2].y + v[3].y)) + ((v[4].y + v[5].y) + (v[6].y + v[7].y))));
                const float gb = inv * ((((v[0].z + v[1].z) + (v[2].z + v[3].z)) + ((v[4].z + v[5].z) + (v[6].z + v[7].z))) -
                                        mean * (((v[0].w + v[1].w) + (v[2].w + v[3].w)) + ((v[4].w + v[5].w) + (v[6].w + v[7].w))));
                uint32_t wd = pack2(ga, gb);
                if (role < NG / 2) {
                    const float g0 = bf_lo(wd), g1 = bf_hi(wd);
                    wd = pack2(g0 * rcp(1.0f + ex2(-1.4426950408889634f * g0)), g1 * rcp(1.0f + ex2(-1.4426950408889634f * g1)));
                }
                const uint32_t wa = __shfl_down_sync(0xffffffffu, wd, 1), wb = __shfl_down_sync(0xffffffffu, wd, 2);
                if (snd) st_pkt(ph, wd, wa, wb, tag);
            }
            __syncthreads();
        } else if (role < DN0 + NDN) {
            const int j = role - DN0;
            const int tl = opq(tid), warp = tl >> 5, lane = tl & 31, g = lane >> 2, t = lane & 3, mat = lane >> 3, r8 = lane & 7;
            float xr0 = 0.f, xr1 = 0.f;
            if (wu == 0) {
                const int col = 16 * j + (lane & 15), cc = col / 160, r = col - 160 * cc, e = r % 3;
                const uint4* px = &maps.scr->acc[layer][(54 * cc + r / 3)];
                const float x0 = bf_lo(lds16(SM_XS + 4 * xpos(col >> 1) + 2 * (col & 1)));
                uint4 v;
                int it = 0;
                bool ld = layer == 0;
                do {
                    v = ld_pkt(px);
                    if (ld && f_(__shfl_sync(0xffffffffu, v.w, 0)) >= (float)DNTH) { ld = false; if (lane == 0) load_ffn(maps, role, SM_B, FBAR); }
                } while (!__all_sync(0xffffffffu, v.w == DONE32) && ++it < SPIN_CAP);
                if (ld && lane == 0) load_ffn(maps, role, SM_B, FBAR);
                const float xres = bfr(x0 + bfr(f_(e == 0 ? v.x : (e == 1 ? v.y : v.z))));
                xr0 = __shfl_sync(0xffffffffu, xres, 2 * (lane & 7));
                xr1 = __shfl_sync(0xffffffffu, xres, 2 * (lane & 7) + 1);
            }
            const uint32_t ad = SM_B + (192 * warp + (mat >> 1) * 8 + r8) * 32 + (((mat & 1) ^ (r8 >> 2)) << 4);
            const uint32_t hs = SM_R + 384 * warp, hb = opq(hs + 16 * t), dd = opq(SM_R + 3072 + 4 * (warp * 16 + g));
            uint32_t pre[NPRE][4];
            uint32_t pos[3];
#pragma unroll
            for (int i = 0; i < 3; i++) { const int w = 3 * lane + i; pos[i] = opq(hs + 4 * ((w & ~15) + 4 * (w & 3) + ((w >> 2) & 1) + ((w >> 2) & 2))); }
            const uint4* ph = opq(&maps.scr->ah[tl]);
            const uint32_t fa = opq(SM_R + 3072 + 8 * (lane & 7));
            uint2* py = opq(reinterpret_cast<uint2*>(maps.scr->ay) + 8 * j + (lane & 7));
            uint32_t* po = opq(reinterpret_cast<uint32_t*>(out) + 8 * j + (lane & 7));
            mbar_wait(FBAR, 0);
#pragma unroll
            for (int n = 0; n < NPRE; n++) ldsm4t(ad + n * 512, pre[n]);
            {
                uint4 v, u;
                int it = 0;
                bool more;
                do { v = ld_pkt(ph); u = ld_pkt(ph + 256); more = ++it < SPIN_CAP; }
                while (!__all_sync(0xffffffffu, v.w == tag && u.w == tag) && more);
                sts32(pos[0], mul2(v.x, u.x)); sts32(pos[1], mul2(v.y, u.y)); sts32(pos[2], mul2(v.z, u.z));
            }
            __syncwarp();
            {
                float cc[4][4];
                uint32_t hv[3][4];
#pragma unroll
                for (int jj = 0; jj < 3; jj++) lds128(hb + 64 * jj, hv[jj][0], hv[jj][1], hv[jj][2], hv[jj][3]);
#pragma unroll
                for (int n = 0; n < 12; n++) {
                    const int s = n < NPRE ? n : n - NPRE;
                    if (n < 4) cc[n][0] = cc[n][1] = cc[n][2] = cc[n][3] = 0.f;
                    mma16816v(cc[n & 3], pre[s][0], pre[s][1], pre[s][2], pre[s][3], hv[(n >> 1) % 3][2 * (n & 1)], hv[(n >> 1) % 3][2 * (n & 1) + 1]);
                    if (n + NPRE < 12) ldsm4t(ad + (n + NPRE) * 512, pre[n]);
                    if ((n & 1) && n < 6) lds128(hb + 64 * ((n >> 1) + 3), hv[n >> 1][0], hv[n >> 1][1], hv[n >> 1][2], hv[n >> 1][3]);
                }
                if (t == 0) { sts32(dd, (cc[0][0] + cc[1][0]) + (cc[2][0] + cc[3][0])); sts32(dd + 32, (cc[0][2] + cc[1][2]) + (cc[2][2] + cc[3][2])); }
            }
            __syncthreads();
            if (tl < 8) {
                float2 v[8];
#pragma unroll
                for (int w = 0; w < 8; w++) v[w] = lds64f(fa + 64 * w);
                const uint32_t y = pack2(((v[0].x + v[1].x) + (v[2].x + v[3].x)) + ((v[4].x + v[5].x) + (v[6].x + v[7].x)),
                                         ((v[0].y + v[1].y) + (v[2].y + v[3].y)) + ((v[4].y + v[5].y) + (v[6].y + v[7].y)));
                const uint32_t wd = pack2(xr0 + bf_lo(y), xr1 + bf_hi(y));
                if (layer) asm volatile("st.global.u32 [%0], %1;" ::"l"(po), "r"(wd) : "memory");
                st_pkt2(py, wd, tag);
            }
            __syncthreads();
        }
    }
}

typedef CUresult (*EncodeFn)(CUtensorMap*, CUtensorMapDataType, cuuint32_t, void*, const cuuint64_t*, const cuuint64_t*, const cuuint32_t*,
                             const cuuint32_t*, CUtensorMapInterleave, CUtensorMapSwizzle, CUtensorMapL2promotion, CUtensorMapFloatOOBfill);

void make_map(EncodeFn enc, CUtensorMap* m, const void* base, int rank, uint64_t d0, uint64_t d1, uint64_t d2, uint64_t s1, uint64_t s2,
              uint32_t b0, uint32_t b1, uint32_t b2, CUtensorMapSwizzle sw, CUtensorMapL2promotion pr = CU_TENSOR_MAP_L2_PROMOTION_NONE) {
    cuuint64_t dims[3] = {d0, d1, d2};
    cuuint64_t strides[2] = {s1, s2};
    cuuint32_t box[3] = {b0, b1, b2};
    cuuint32_t es[3] = {1, 1, 1};
    enc(m, CU_TENSOR_MAP_DATA_TYPE_BFLOAT16, rank, const_cast<void*>(base), dims, strides, box, es, CU_TENSOR_MAP_INTERLEAVE_NONE, sw,
        pr, CU_TENSOR_MAP_FLOAT_OOB_FILL_NONE);
}

}

extern "C" void kernel_launch(void* const* d_in, const int* in_sizes, int n_in, void* d_out, int out_size) {
    (void)in_sizes; (void)n_in; (void)out_size;
    static EncodeFn enc = nullptr;
    static Scratch* scr = nullptr;
    if (!enc) {
        void* fn = nullptr;
        cudaDriverEntryPointQueryResult qr;
        cudaGetDriverEntryPoint("cuTensorMapEncodeTiled", &fn, cudaEnableDefault, &qr);
        enc = reinterpret_cast<EncodeFn>(fn);
        cudaGetSymbolAddress(reinterpret_cast<void**>(&scr), g_scr);
        cudaFuncSetAttribute(decode_kernel, cudaFuncAttributeMaxDynamicSharedMemorySize, SM_TOTAL);
    }
    Maps maps;
    make_map(enc, &maps.k, d_in[1], 2, 64, (uint64_t)NH * SK * 3, 1, 128, 0, 64, 48, 1, CU_TENSOR_MAP_SWIZZLE_128B);
    make_map(enc, &maps.v, d_in[2], 2, 64, (uint64_t)NH * SK * 3, 1, 128, 0, 64, 48, 1, CU_TENSOR_MAP_SWIZZLE_128B);
    {
        cuuint64_t dims[5] = {64, 16, NH * DH / 64, DM / 80, 5};
        cuuint64_t strides[4] = {NH * DH * 2, 128, 80 * NH * DH * 2, 16 * NH * DH * 2};
        cuuint32_t box[5] = {64, 16, 3, 2, 5};
        cuuint32_t es[5] = {1, 1, 1, 1, 1};
        enc(&maps.wq, CU_TENSOR_MAP_DATA_TYPE_BFLOAT16, 5, d_in[3], dims, strides, box, es, CU_TENSOR_MAP_INTERLEAVE_NONE, CU_TENSOR_MAP_SWIZZLE_128B,
            CU_TENSOR_MAP_L2_PROMOTION_NONE, CU_TENSOR_MAP_FLOAT_OOB_FILL_NONE);
    }
    make_map(enc, &maps.wo, d_in[4], 3, 32, NH * DH, DM / 32, DM * 2, 64, 32, 192, 1, CU_TENSOR_MAP_SWIZZLE_64B);
    constexpr int GW = 48;
    make_map(enc, &maps.w1, d_in[6], 3, FF, 160, 4, FF * 2, 160 * FF * 2, GW, 160, 4, CU_TENSOR_MAP_SWIZZLE_NONE);
    make_map(enc, &maps.w3, d_in[7], 3, FF, 160, 4, FF * 2, 160 * FF * 2, GW, 160, 4, CU_TENSOR_MAP_SWIZZLE_NONE);
    make_map(enc, &maps.w2, d_in[8], 3, DM, 256, 6, DM * 2, 256 * DM * 2, 16, 256, 6, CU_TENSOR_MAP_SWIZZLE_32B);
    make_map(enc, &maps.ks, d_in[1], 2, 64, (uint64_t)NH * SK * 3, 1, 128, 0, 16, 48, 1, CU_TENSOR_MAP_SWIZZLE_NONE);
    make_map(enc, &maps.vs, d_in[2], 2, 64, (uint64_t)NH * SK * 3, 1, 128, 0, 16, 48, 1, CU_TENSOR_MAP_SWIZZLE_NONE);
    make_map(enc, &maps.kh, d_in[1], 2, 64, (uint64_t)NH * SK * 3, 1, 128, 0, 64, 24, 1, CU_TENSOR_MAP_SWIZZLE_128B);
    maps.kp = d_in[1];
    maps.vp = d_in[2];
    maps.scr = scr;
    maps.zero = 0;
    const uint32_t rt[8] = {0x2EE0, 0x35E0, 0x2EE0, 0x35E0, 0x3EE0, 0x35E0, 0x3EE0, 0x35E0};
    for (int i = 0; i < 8; i++) maps.rt[i] = rt[i];
    decode_kernel<<<NCTA, NT, SM_TOTAL, cudaStreamPerThread>>>(maps, (const __nv_bfloat16*)d_in[0], (__nv_bfloat16*)d_out);
}
```

```cpp
#include <cuda_runtime.h>
#include <cuda_bf16.h>
#include <cuda.h>
#include <stdint.h>
#include <math.h>

namespace {

constexpr int DM = 640;
constexpr int NH = 32;
constexpr int DH = 192;
constexpr int SK = 32768;
constexpr int WIN = 4096;
constexpr int FF = 1536;
constexpr int NCTA = 128;
constexpr int NT = 256;
constexpr int TILE = 6144;
constexpr int TS = 48;
constexpr int NG = 64;
constexpr int DN0 = 64;
constexpr int NDN = 40;

constexpr uint32_t SB = 1024;
constexpr uint32_t SM_RING = SB;
constexpr uint32_t SM_B = SM_RING + 8 * 2 * TILE;
constexpr uint32_t SM_Q = SM_B + 61440;
constexpr uint32_t SM_XS = SM_Q + 61440;
constexpr uint32_t SM_R = SM_XS + 1280;
constexpr uint32_t SM_ST = SM_R + 4096;
constexpr uint32_t SM_QS = SM_R + 6272;
constexpr uint32_t SM_OS = SM_QS + 384;
constexpr uint32_t SM_CS = SM_OS + 384;
constexpr uint32_t SM_BAR = SM_CS + 768;
constexpr uint32_t SM_XBAR = SM_BAR + 24 * 8;
constexpr uint32_t SM_MISC = SM_XBAR + 8 * 8;
constexpr uint32_t SM_ONE = SM_MISC + 32;
constexpr uint32_t SM_ZERO = SM_ONE + 160;
constexpr uint32_t SM_KX = SM_ZERO + 160;
constexpr uint32_t SM_TOTAL = SM_KX + 8 * 96 - SB;
constexpr int NEXC = 16;
static_assert(SM_TOTAL <= 232448, "shared memory");
constexpr uint32_t QBAR = SM_BAR + 16 * 8, FBAR = QBAR + 8, WBAR = QBAR + 16, QRDY = QBAR + 56;

constexpr unsigned long long POL_EF = 0x12F0000000000000ull;
constexpr unsigned long long POL_EN = 0x1000000000000000ull;

constexpr int L1R = 3;
constexpr int DNTH = 21;
constexpr int NPRE = 8;
constexpr int SPIN_CAP = 1 << 19;
constexpr uint32_t ONES = 0x3F803F80u;
#define AFTER(x) ((x) & maps.zero)
#define ALL6(a, n) (a[n][0] | a[n + 1][0] | a[n + 2][0] | a[n + 3][0] | a[n + 4][0] | a[n + 5][0])
#define ROW0(w) ((h * SK + (SK - WIN) + c * 1024 + (w) * 128) * 3)

struct Scratch {
    uint4 qx[NCTA * 48];
    uint4 qc[NCTA * 48];
    uint4 cx[NCTA * 56];
    uint4 acc[2][256];
    uint4 ay[256];
    uint4 pad0[256];
    uint4 ah[NG * 8];
    uint2 mx[NH * 32];
    uint32_t ticket[32];
};
__device__ __align__(4096) Scratch g_scr;
struct Maps { CUtensorMap k, v, wq, wo, w1, w3, w2, ks, vs, kh; const void *kp, *vp; Scratch* scr; uint32_t rt[8], zero; };

__device__ __forceinline__ uint32_t smem_u32(const void* p) { return (uint32_t)__cvta_generic_to_shared(p); }
__device__ __forceinline__ void mbar_init(uint32_t bar, uint32_t cnt) {
    asm volatile("mbarrier.init.shared::cta.b64 [%0], %1;" ::"r"(bar), "r"(cnt) : "memory");
}
__device__ __forceinline__ void mbar_expect_tx(uint32_t bar, uint32_t bytes) {
    asm volatile("mbarrier.arrive.expect_tx.shared::cta.b64 _, [%0], %1;" ::"r"(bar), "r"(bytes) : "memory");
}
__device__ __forceinline__ bool mbar_test(uint32_t bar, uint32_t parity) {
    uint32_t done;
    asm volatile("{\n.reg .pred p;\nmbarrier.try_wait.parity.shared::cta.b64 p, [%1], %2;\nselp.u32 %0, 1, 0, p;\n}"
                 : "=r"(done) : "r"(bar), "r"(parity) : "memory");
    return done;
}
__device__ __forceinline__ void mbar_wait(uint32_t bar, uint32_t parity) {
    asm volatile("{\n.reg .pred p;\n.reg .u32 n;\nmov.u32 n, 0;\n"
                 "W: mbarrier.try_wait.parity.shared::cta.b64 p, [%0], %1;\n@p bra D;\n"
                 "add.u32 n, n, 1;\nsetp.lt.u32 p, n, %2;\n@p bra W;\nD:\n}" ::"r"(bar), "r"(parity), "n"(SPIN_CAP) : "memory");
}
__device__ __forceinline__ void tma2d(uint32_t dst, const CUtensorMap* map, int c0, int c1, uint32_t bar, unsigned long long pol) {
    asm volatile("cp.async.bulk.tensor.2d.shared::cluster.global.mbarrier::complete_tx::bytes.L2::cache_hint [%0], [%1, {%3, %4}], [%2], %5;"
                 ::"r"(dst), "l"(map), "r"(bar), "r"(c0), "r"(c1), "l"(pol) : "memory");
}
__device__ __forceinline__ void tma3d(uint32_t dst, const CUtensorMap* map, int c0, int c1, int c2, uint32_t bar, unsigned long long pol) {
    asm volatile("cp.async.bulk.tensor.3d.shared::cluster.global.mbarrier::complete_tx::bytes.L2::cache_hint [%0], [%1, {%3, %4, %5}], [%2], %6;"
                 ::"r"(dst), "l"(map), "r"(bar), "r"(c0), "r"(c1), "r"(c2), "l"(pol) : "memory");
}
__device__ __forceinline__ void tma5d(uint32_t dst, const CUtensorMap* map, int c2, int c3, uint32_t bar, unsigned long long pol) {
    asm volatile("cp.async.bulk.tensor.5d.shared::cluster.global.mbarrier::complete_tx::bytes.L2::cache_hint [%0], [%1, {0, 0, %3, %4, 0}], [%2], %5;"
                 ::"r"(dst), "l"(map), "r"(bar), "r"(c2), "r"(c3), "l"(pol) : "memory");
}
__device__ __forceinline__ void tile_load(uint32_t dst, const CUtensorMap* map, int row, uint32_t bar) {
    asm volatile("{\n.reg .pred p;\nelect.sync _|p, 0xffffffff;\n"
                 "@p mbarrier.arrive.expect_tx.shared::cta.b64 _, [%2], 6144;\n"
                 "@p cp.async.bulk.tensor.2d.shared::cluster.global.mbarrier::complete_tx::bytes.L2::cache_hint [%0], [%1, {0, %3}], [%2], %4;\n}"
                 ::"r"(dst), "l"(map), "r"(bar), "r"(row), "l"(POL_EF) : "memory");
}
__device__ __forceinline__ void half_load(uint32_t dst, const CUtensorMap* map, int row, uint32_t bar, bool first) {
    if (first) asm volatile("{\n.reg .pred p;\nelect.sync _|p, 0xffffffff;\n@p mbarrier.arrive.expect_tx.shared::cta.b64 _, [%0], 6144;\n}" ::"r"(bar) : "memory");
    asm volatile("{\n.reg .pred p;\nelect.sync _|p, 0xffffffff;\n"
                 "@p cp.async.bulk.tensor.2d.shared::cluster.global.mbarrier::complete_tx::bytes.L2::cache_hint [%0], [%1, {0, %3}], [%2], %4;\n}"
                 ::"r"(dst), "l"(map), "r"(bar), "r"(row), "l"(POL_EF) : "memory");
}
__device__ __forceinline__ void tile_keep(const CUtensorMap* map, int row) {
    asm volatile("{\n.reg .pred p;\nelect.sync _|p, 0xffffffff;\n"
                 "@p cp.async.bulk.prefetch.tensor.2d.L2.global.L2::cache_hint [%0, {0, %1}], %2;\n}"
                 ::"l"(map), "r"(row), "l"(POL_EN) : "memory");
}
__device__ __forceinline__ void tile_load_l1(uint32_t dst, const void* base, int row, uint32_t bar, int lane) {
    const char* g = static_cast<const char*>(base) + (size_t)row * 128 + lane * 16;
    const uint32_t s0 = dst + (lane >> 3) * 128 + (((lane & 7) ^ (lane >> 3)) << 4), s1 = s0 ^ 64;
#pragma unroll
    for (int k = 0; k < 12; k++)
        asm volatile("cp.async.ca.shared.global.L2::cache_hint [%0], [%1], 16, %2;" ::"r"(((k & 1) ? s1 : s0) + k * 512), "l"(g + k * 512), "l"(POL_EF) : "memory");
    asm volatile("cp.async.mbarrier.arrive.shared::cta.b64 [%0];" ::"r"(bar) : "memory");
    __syncwarp();
    if (lane == 0) asm volatile("mbarrier.arrive.shared::cta.b64 _, [%0];" ::"r"(bar) : "memory");
}
__device__ __forceinline__ bool elect_one() {
    uint32_t p;
    asm volatile("{\n.reg .pred p;\nelect.sync _|p, 0xffffffff;\nselp.u32 %0, 1, 0, p;\n}" : "=r"(p));
    return p;
}
__device__ __forceinline__ void delay(uint32_t clocks) {
    uint32_t t0, t1;
    asm volatile("mov.u32 %0, %%clock;" : "=r"(t0));
    do asm volatile("mov.u32 %0, %%clock;" : "=r"(t1)); while (t1 - t0 < clocks);
}
__device__ __forceinline__ void lds128(uint32_t addr, uint32_t& a, uint32_t& b, uint32_t& c, uint32_t& d) {
    asm volatile("ld.shared.v4.u32 {%0,%1,%2,%3}, [%4];" : "=r"(a), "=r"(b), "=r"(c), "=r"(d) : "r"(addr) : "memory");
}
__device__ __forceinline__ void lds64(uint32_t addr, uint32_t& a, uint32_t& b) {
    asm volatile("ld.shared.v2.u32 {%0,%1}, [%2];" : "=r"(a), "=r"(b) : "r"(addr) : "memory");
}
__device__ __forceinline__ void ldsm4t(uint32_t addr, uint32_t (&a)[4]) {
    asm volatile("ldmatrix.sync.aligned.m8n8.x4.trans.shared.b16 {%0,%1,%2,%3}, [%4];" : "=r"(a[0]), "=r"(a[1]), "=r"(a[2]), "=r"(a[3]) : "r"(addr) : "memory");
}
__device__ __forceinline__ void mma16816(float (&c)[4], uint32_t a0, uint32_t a1, uint32_t a2, uint32_t a3, uint32_t b0, uint32_t b1) {
    asm("mma.sync.aligned.m16n8k16.row.col.f32.bf16.bf16.f32 {%0,%1,%2,%3}, {%4,%5,%6,%7}, {%8,%9}, {%0,%1,%2,%3};"
        : "+f"(c[0]), "+f"(c[1]), "+f"(c[2]), "+f"(c[3]) : "r"(a0), "r"(a1), "r"(a2), "r"(a3), "r"(b0), "r"(b1));
}
__device__ __forceinline__ void mma16816v(float (&c)[4], uint32_t a0, uint32_t a1, uint32_t a2, uint32_t a3, uint32_t b0, uint32_t b1) {
    asm volatile("mma.sync.aligned.m16n8k16.row.col.f32.bf16.bf16.f32 {%0,%1,%2,%3}, {%4,%5,%6,%7}, {%8,%9}, {%0,%1,%2,%3};"
        : "+f"(c[0]), "+f"(c[1]), "+f"(c[2]), "+f"(c[3]) : "r"(a0), "r"(a1), "r"(a2), "r"(a3), "r"(b0), "r"(b1));
}
__device__ __forceinline__ int xpos(int w) {
    const int seg = w / 40, r = w - 40 * seg;
    return 40 * seg + (r < 32 ? (r & 16) + 4 * (r & 3) + ((r >> 2) & 3) : 32 + 2 * (r & 3) + ((r >> 2) & 1));
}
__device__ __forceinline__ void st_pkt(uint4* p, uint32_t a, uint32_t b, uint32_t c, uint32_t d) {
    asm volatile("{\n.reg .b128 t;\n.reg .b64 lo, hi;\nmov.b64 lo, {%1,%2};\nmov.b64 hi, {%3,%4};\nmov.b128 t, {lo,hi};\nst.relaxed.gpu.global.b128 [%0], t;\n}"
                 ::"l"(p), "r"(a), "r"(b), "r"(c), "r"(d) : "memory");
}
__device__ __forceinline__ void st_pktf(uint4* p, float a, float b, float c, float d, uint32_t bit) {
    st_pkt(p, __float_as_uint(a), __float_as_uint(b), __float_as_uint(c), (__float_as_uint(d) & ~1u) | bit);
}
__device__ __forceinline__ void red_pkt(uint4* p, float a, float b, float c) {
    asm volatile("red.relaxed.gpu.global.add.v4.f32 [%0], {%1,%2,%3,%4};" ::"l"(p), "f"(a), "f"(b), "f"(c), "f"(1.0f) : "memory");
}
__device__ __forceinline__ uint4 ld_pkt(const uint4* p) {
    uint4 v;
    asm volatile("{\n.reg .b128 t;\n.reg .b64 lo, hi;\nld.relaxed.gpu.global.b128 t, [%4];\nmov.b128 {lo,hi}, t;\nmov.b64 {%0,%1}, lo;\nmov.b64 {%2,%3}, hi;\n}"
                 : "=r"(v.x), "=r"(v.y), "=r"(v.z), "=r"(v.w) : "l"(p) : "memory");
    return v;
}
__device__ __forceinline__ uint2 ld_pkt2(const uint2* p) {
    unsigned long long v;
    asm volatile("ld.relaxed.gpu.global.b64 %0, [%1];" : "=l"(v) : "l"(p) : "memory");
    return make_uint2((uint32_t)v, (uint32_t)(v >> 32));
}
__device__ __forceinline__ void st_pkt2(uint2* p, uint32_t a, uint32_t b) {
    asm volatile("st.relaxed.gpu.global.b64 [%0], %1;" ::"l"(p), "l"((unsigned long long)a | ((unsigned long long)b << 32)) : "memory");
}
__device__ __forceinline__ float ex2(float x) { float y; asm("ex2.approx.ftz.f32 %0, %1;" : "=f"(y) : "f"(x)); return y; }
__device__ __forceinline__ float rcp(float x) { float y; asm("rcp.approx.ftz.f32 %0, %1;" : "=f"(y) : "f"(x)); return y; }
__device__ __forceinline__ uint32_t pack2(float lo, float hi) {
    uint32_t r; asm("cvt.rn.bf16x2.f32 %0, %1, %2;" : "=r"(r) : "f"(hi), "f"(lo)); return r;
}
__device__ __forceinline__ float bf_lo(uint32_t w) { return __uint_as_float(w << 16); }
__device__ __forceinline__ float bf_hi(uint32_t w) { return __uint_as_float(w & 0xffff0000u); }
__device__ __forceinline__ float bfr(float x) { return bf_lo(pack2(x, 0.f)); }
__device__ __forceinline__ float f_(uint32_t u) { return __uint_as_float(u); }

__device__ __forceinline__ uint32_t add2(uint32_t a, uint32_t b) { uint32_t r; asm("add.rn.bf16x2 %0, %1, %2;" : "=r"(r) : "r"(a), "r"(b)); return r; }
__device__ __forceinline__ uint32_t mul2(uint32_t a, uint32_t b) { uint32_t r; asm("mul.rn.bf16x2 %0, %1, %2;" : "=r"(r) : "r"(a), "r"(b)); return r; }
__device__ __forceinline__ uint32_t f2key(float f) { const uint32_t u = __float_as_uint(f); return u ^ ((uint32_t)((int)u >> 31) | 0x80000000u); }
__device__ __forceinline__ float key2f(uint32_t k) { return __uint_as_float(k ^ ((uint32_t)((int)~k >> 31) | 0x80000000u)); }
__device__ __forceinline__ float4 lds128f(uint32_t a) {
    float4 v; asm volatile("ld.shared.v4.f32 {%0,%1,%2,%3}, [%4];" : "=f"(v.x), "=f"(v.y), "=f"(v.z), "=f"(v.w) : "r"(a) : "memory"); return v;
}
__device__ __forceinline__ float2 lds64f(uint32_t a) { float2 v; asm volatile("ld.shared.v2.f32 {%0,%1}, [%2];" : "=f"(v.x), "=f"(v.y) : "r"(a) : "memory"); return v; }
__device__ __forceinline__ uint32_t lds32(uint32_t a) { uint32_t v; asm volatile("ld.shared.u32 %0, [%1];" : "=r"(v) : "r"(a) : "memory"); return v; }
__device__ __forceinline__ uint32_t lds16(uint32_t a) { uint32_t v; asm volatile("ld.shared.u16 %0, [%1];" : "=r"(v) : "r"(a) : "memory"); return v; }
__device__ __forceinline__ void sts16(uint32_t a, uint32_t v) { asm volatile("st.shared.u16 [%0], %1;" ::"r"(a), "r"(v) : "memory"); }
__device__ __forceinline__ void sts32(uint32_t a, uint32_t v) { asm volatile("st.shared.u32 [%0], %1;" ::"r"(a), "r"(v) : "memory"); }
__device__ __forceinline__ void sts32(uint32_t a, float v) { asm volatile("st.shared.f32 [%0], %1;" ::"r"(a), "f"(v) : "memory"); }
__device__ __forceinline__ void sts128(uint32_t a, float x, float y, float z, float w) {
    asm volatile("st.shared.v4.f32 [%0], {%1,%2,%3,%4};" ::"r"(a), "f"(x), "f"(y), "f"(z), "f"(w) : "memory");
}
template <int N> struct IC { static constexpr int value = N; };
__device__ __forceinline__ int opq(int x) { asm volatile("" : "+r"(x)); return x; }
__device__ __forceinline__ uint32_t opq(uint32_t x) { asm volatile("" : "+r"(x)); return x; }
template <typename T> __device__ __forceinline__ T* opq(T* p) { asm volatile("" : "+l"(p)); return p; }

__device__ __forceinline__ void ln_finish(float s1, float s2, float& mean, float& inv) {
    const float md = s1 * (1.0f / DM);
    const float var = fmaxf(s2 * (1.0f / DM) - md * md, 0.f);
    mean = bfr(md);
    asm("rsqrt.approx.ftz.f32 %0, %1;" : "=f"(inv) : "f"(var + 1e-5f));
}
__device__ __forceinline__ void ln_stats(float& mean, float& inv) {
    const float4 a = lds128f(SM_ST), b = lds128f(SM_ST + 16), c = lds128f(SM_ST + 32), d = lds128f(SM_ST + 48);
    ln_finish(((a.y + a.w) + (b.y + b.w)) + ((c.y + c.w) + (d.y + d.w)), ((a.x + a.z) + (b.x + b.z)) + ((c.x + c.z) + (d.x + d.z)), mean, inv);
}
template <int SK, bool GRAM, typename AddrF>
__device__ __forceinline__ void gemv15(float (&cc)[3][4], float (&gr)[4], uint32_t (&pre)[9][4], AddrF ad, uint32_t px, uint32_t px2) {
    uint32_t x0[4], x1[4];
    lds128(px, x0[0], x0[1], x0[2], x0[3]);
    lds128(px + 64, x1[0], x1[1], x1[2], x1[3]);
    gr[0] = gr[1] = gr[2] = gr[3] = 0.f;
#pragma unroll
    for (int i = 0; i < 3; i++) {
        cc[i][0] = cc[i][1] = cc[i][2] = cc[i][3] = 0.f;
        mma16816v(cc[i], pre[i][0], pre[i][1], pre[i][2], pre[i][3], x0[0], x0[1]);
    }
#pragma unroll
    for (int i = 0; i < 3; i++) ldsm4t(ad(i) + 3 * SK, pre[i]);
    if (GRAM) mma16816v(gr, x0[0], 0u, x0[1], 0u, x0[0], x0[1]);
#pragma unroll
    for (int i = 0; i < 3; i++) mma16816v(cc[i], pre[3 + i][0], pre[3 + i][1], pre[3 + i][2], pre[3 + i][3], x0[2], x0[3]);
#pragma unroll
    for (int i = 0; i < 3; i++) ldsm4t(ad(i) + 4 * SK, pre[3 + i]);
    lds64(px2, x0[0], x0[1]);
    if (GRAM) mma16816v(gr, x0[2], 0u, x0[3], 0u, x0[2], x0[3]);
#pragma unroll
    for (int i = 0; i < 3; i++) mma16816v(cc[i], pre[6 + i][0], pre[6 + i][1], pre[6 + i][2], pre[6 + i][3], x1[0], x1[1]);
    if (GRAM) mma16816v(gr, x1[0], 0u, x1[1], 0u, x1[0], x1[1]);
#pragma unroll
    for (int i = 0; i < 3; i++) mma16816v(cc[i], pre[i][0], pre[i][1], pre[i][2], pre[i][3], x1[2], x1[3]);
    if (GRAM) mma16816v(gr, x1[2], 0u, x1[3], 0u, x1[2], x1[3]);
    if (GRAM) mma16816v(gr, x0[0], 0u, x0[1], 0u, x0[0], x0[1]);
#pragma unroll
    for (int i = 0; i < 3; i++) mma16816v(cc[i], pre[3 + i][0], pre[3 + i][1], pre[3 + i][2], pre[3 + i][3], x0[0], x0[1]);
}
__device__ __forceinline__ void gemv15r(float (&cc)[3][4], float (&gr)[4], const uint32_t (&pre)[9][4], const uint32_t (&ext)[45][4], uint32_t px, uint32_t px2) {
    uint32_t x0[4], x1[4], x2[2];
    lds128(px, x0[0], x0[1], x0[2], x0[3]);
    lds128(px + 64, x1[0], x1[1], x1[2], x1[3]);
    lds64(px2, x2[0], x2[1]);
    gr[0] = gr[1] = gr[2] = gr[3] = 0.f;
#pragma unroll
    for (int ks = 0; ks < 5; ks++) {
        const uint32_t b0 = ks < 2 ? x0[2 * (ks & 1)] : ks < 4 ? x1[2 * (ks & 1)] : x2[0], b1 = ks < 2 ? x0[2 * (ks & 1) + 1] : ks < 4 ? x1[2 * (ks & 1) + 1] : x2[1];
        mma16816v(gr, b0, 0u, b1, 0u, b0, b1);
#pragma unroll
        for (int i = 0; i < 3; i++) {
            if (ks == 0) cc[i][0] = cc[i][1] = cc[i][2] = cc[i][3] = 0.f;
            const uint32_t (&f)[4] = ks < 3 ? pre[ks < 3 ? 3 * ks + i : 0] : ext[ks < 3 ? 0 : 3 * (ks - 3) + i];
            mma16816v(cc[i], f[0], f[1], f[2], f[3], b0, b1);
        }
    }
}

__device__ __forceinline__ void load_ffn(const Maps& maps, int b, uint32_t dst, uint32_t bar) {
    const bool gu = b < NG;
    mbar_expect_tx(bar, gu ? 61440 : 49152);
    tma3d(dst, gu ? (b < NG / 2 ? &maps.w1 : &maps.w3) : &maps.w2, gu ? 48 * (b & (NG / 2 - 1)) : 16 * (b - DN0), 0, 0, bar, POL_EF);
}

__device__ __forceinline__ void load_wo(const Maps& maps, uint32_t dst, int h, int c, uint32_t bar, int nbox) {
#pragma unroll 1
    for (int i = 0; i < nbox; i++) {
        mbar_expect_tx(bar + 8 * i, 12288);
        tma3d(dst + i * 12288, &maps.wo, 0, h * DH, 5 * c + i, bar + 8 * i, POL_EF);
    }
}

__global__ void __launch_bounds__(NT, 1)
decode_kernel(const __grid_constant__ Maps maps, const __nv_bfloat16* __restrict__ x_in, __nv_bfloat16* __restrict__ out) {
    extern __shared__ __align__(1024) unsigned char smem[];
    const int tid = threadIdx.x;
    const int wu = __shfl_sync(0xffffffffu, tid >> 5, 0);
    const int b = blockIdx.x, h = b >> 2, c = b & 3;
    if (smem_u32(smem) != SB) return;

    {
        const int warp = tid >> 5, lane = tid & 31;
        const uint32_t rbar = SM_BAR + warp * 16;
        if (lane == 0) {
            if (warp == 0) {
                mbar_init(QBAR, 1);
                asm volatile("fence.mbarrier_init.release.cluster;" ::: "memory");
                mbar_expect_tx(QBAR, 61440);
                tma5d(SM_Q, &maps.wq, 3 * h, 2 * c, QBAR, POL_EF);
            }
            mbar_init(rbar, 1); mbar_init(rbar + 8, 1); mbar_init(SM_XBAR + warp * 8, 1);
            mbar_init(FBAR + 8 * max(warp - 1, 0), warp == 7 ? 2 : 1);
            asm volatile("fence.mbarrier_init.release.cluster;" ::: "memory");
            if (warp >= 1 && warp < 7) {
                const CUtensorMap* mp = warp == 1 ? &maps.k : warp == 2 ? &maps.v : warp == 3 ? &maps.wo : warp == 4 ? &maps.w1 : warp == 5 ? &maps.w3 : &maps.w2;
                asm volatile("prefetch.tensormap [%0];" ::"l"(mp) : "memory");
            }
        }
        if (tid == 96) sts32(SM_MISC + 8, 0u);
        if (lane < 2) sts32(SM_KX + warp * 96 + 4 * lane, 0u);
        if (tid >= 128 && tid < 148) {
            const float v = f_(tid < 138 ? ONES : 0u);
            sts128(SM_ONE + 16 * (tid - 128), v, v, v, v);
        }
        if (b == 0 && tid == 255) asm volatile("st.relaxed.gpu.global.u32 [%0], %1;" ::"l"(maps.scr->ticket), "r"(0) : "memory");
        if (tid < 4) st_pkt(reinterpret_cast<uint4*>(&maps.scr->mx[h * 32 + c * 8]) + tid, 0, 0, 0, 0);
        if (tid >= 64 && tid < 66 && b < 108) st_pkt(&maps.scr->acc[1][(2 * b + tid - 64)], 0, 0, 0, 0);
        __syncthreads();
        if (lane == 0) {
            const int row = ROW0(warp);
            mbar_expect_tx(rbar, TILE);
            tma2d(SM_RING + warp * 2 * TILE, &maps.k, 0, row, rbar, POL_EF);
            mbar_expect_tx(rbar + 8, TILE);
            tma2d(SM_RING + (warp * 2 + 1) * TILE, &maps.k, 0, row + TS, rbar + 8, POL_EF);
        }
    }

    uint32_t kr[45][4];
#define KR(n) kr[(n) >> 2][(n) & 3]
    const float SC = 0.07216878364870322f * 1.4426950408889634f;
    int role = 0;
    uint32_t wk[3][4];

#pragma unroll 1
    for (int layer = 0; layer < 2; layer++) {
        const uint32_t tag = layer + 1, tbit = layer ^ 1;
        uint2 xv = make_uint2(0u, 0u);
        uint32_t qo;
        {
            const int tl = opq(tid), warp = tl >> 5, lane = tl & 31, g = lane >> 2, t = lane & 3, mat = lane >> 3, r8 = lane & 7;
            const int kh = warp >> 2, mg = warp & 3;
            const uint32_t aq = SM_Q + kh * TILE + ((mat >> 1) * 8 + r8) * 128 + (((2 * mg + (mat & 1)) ^ r8) << 4);
            if (layer == 0 && tl < 160) xv = reinterpret_cast<const uint2*>(x_in)[tl];
            mbar_wait(QBAR, 0);
            uint32_t pre[9][4];
#pragma unroll
            for (int n = 0; n < 9; n++) ldsm4t(aq + (n % 3) * 2048 + (n / 3) * 2 * TILE, pre[n]);
            if (layer == 1) {
                sts32(SM_MISC + 12, ALL6(pre, 0) | ALL6(pre, 3));
                __syncthreads();
                delay(role >= DN0 + NDN ? 1000 : 0);
                if (role >= DN0 && role < DN0 + NDN) {
                    if (wu < 6) tile_load(SM_Q + wu * TILE, &maps.k, ROW0(wu) + 5 * TS, SM_XBAR + wu * 8);
                } else if (wu == 7) {
#pragma unroll 1
                    for (int w = 0; w < 6; w++) tile_load(SM_Q + w * TILE, &maps.k, ROW0(w) + 5 * TS, SM_XBAR + w * 8);
                }
            }
            const uint32_t pm = opq(g == 1 ? SM_ONE : SM_XS + 160 * (2 * c + kh) + 16 * t);
            const uint32_t pm2 = opq(pm + 128 - (g == 1 ? 0 : 8 * t));
            const uint32_t dq = opq(SM_R + 768 * kh + 4 * (16 * mg + g));
            qo = opq(16u * (b * 48 + (tl & 63) + (tl >= 64 ? NCTA * 48 : 0)));
            if (tl < 160) {
                const uint32_t xa0 = opq(SM_XS + 4 * xpos(2 * tl));
                const bool xl = tl % 20 < 16;
                if (layer == 1) {
                    const uint4* px = opq(&maps.scr->ay[tl]);
                    uint4 v;
                    int it = 0;
                    bool more;
                    do { v = ld_pkt(px); more = ++it < SPIN_CAP; } while (!__all_sync(0xffffffffu, (v.y & v.w) == 1) && more);
                    xv = make_uint2(v.x, v.z);
                }
                sts32(xa0, xv.x);
                if (xl) sts32(xa0 + 16, xv.y); else sts32(xa0 + 8, xv.y);
            }
            __syncthreads();
            float cc[3][4], gr[4];
            gemv15<2 * TILE, false>(cc, gr, pre, [&](int i) { return aq + i * 2048; }, pm, pm2);
            if (t == 0) {
#pragma unroll
                for (int i = 0; i < 3; i++) { sts32(dq + 256 * i, cc[i][0]); sts32(dq + 256 * i + 32, cc[i][2]); }
                if (layer == 0) {
#pragma unroll
                    for (int i = 0; i < 3; i++) { sts32(dq + 256 * i + 1536, cc[i][1]); sts32(dq + 256 * i + 1568, cc[i][3]); }
                }
            }
        }
        {
            const int tl = opq(tid), j = tl & 63;
            const bool snd = j < 48 && (tl < 64 || (tl < 128 && layer == 0));
            const uint32_t fa = opq(SM_R + 16 * tl + (tl >= 64 ? 512 : 0));
            uint4* pq = reinterpret_cast<uint4*>(reinterpret_cast<char*>(maps.scr->qx) + qo);
            __syncthreads();
            if (snd) {
                const float4 u = lds128f(fa), v = lds128f(fa + 768);
                st_pktf(pq, u.x + v.x, u.y + v.y, u.z + v.z, u.w + v.w, tbit);
            }
            if (layer == 1 && wu >= 5) {
                delay(300);
                if (wu >= 6) tile_load(SM_Q + wu * TILE, &maps.k, ROW0(wu) + 5 * TS, SM_XBAR + wu * 8);
                else if (role < NG && elect_one()) {
                    mbar_expect_tx(WBAR + 32, 12288);
                    tma3d(SM_Q + 4 * 12288, &maps.wo, 0, h * DH, 5 * c + 4, WBAR + 32, POL_EF);
                }
            }
            if (layer == 1 && tl >= 192 && tl < 194 && b < 108) st_pkt(&maps.scr->acc[0][(2 * b + tl - 192)], 0, 0, 0, 0);
        }

        float sc0 = -INFINITY, sc1 = -INFINITY, sc2 = 0.f, sc3 = 0.f, mw;
        uint32_t pk0, pk1;
        float acc[3][4];
        {
            const uint32_t ring = SM_RING + wu * 2 * TILE, rb = SM_BAR + wu * 16;
            const uint32_t xtile = SM_Q + wu * TILE, xb = SM_XBAR + wu * 8;
            const int row0 = ROW0(wu);
            const uint32_t bt = SM_B + wu * TILE;
            auto issue1 = [&](int n, uint32_t dep, bool vph) {
                const CUtensorMap* mp = n < 8 ? &maps.k : &maps.v;
                const int row = row0 + ((n + (n >= 8 ? 2 : 0)) & 7) * TS;
                if (vph && wu < L1R && n == 12 - (wu & 1)) {
                    tile_load_l1(ring + (n & 1) * TILE, maps.vp, row, rb + (n & 1) * 8, opq(tid) & 31);
                    return;
                }
                const int k = vph || n >= 6 ? n & 1 : n >= 3 ? n - 3 : n;
                tile_load(k == 2 ? bt : ring + k * TILE, mp, row + dep, k == 2 ? xb : rb + k * 8);
                if ((maps.rt[wu] >> n) & 1) tile_keep(n < 8 ? &maps.ks : &maps.vs, row);
            };
            auto refill1 = [&](int s, uint32_t dep, bool vph = false) { issue1(s + 2, dep, vph); };
#define K_OFF(i) ((uint32_t)((3 * ((g >> 1) + 4 * (g & 1)) + ((i) >> 1)) * 128 + ((t ^ ((3 * ((g >> 1) + 4 * (g & 1)) + ((i) >> 1)) & 7) ^ (((i) & 1) << 2)) << 4)))
#define V_OFF(i) ((uint32_t)((6 * t + (i)) * 128 + ((g ^ ((6 * t + (i)) & 7)) << 4)))
#define LANE_IDS const int tl = opq(tid), lane = tl & 31, g = lane >> 2, t = lane & 3; (void)tl; (void)lane; (void)g; (void)t;
            const uint32_t kx = SM_KX + wu * 96;
#pragma unroll 1
            for (int s = layer ? 5 : 0; s < 5 + layer; s++) {
                if (s < 5) {
                    LANE_IDS
                    const int k = s >= 3 ? s - 3 : s;
                    mbar_wait(k == 2 ? xb : rb + k * 8, s >= 3);
                    refill1(s, 0);
                    const uint32_t tile = k == 2 ? bt : ring + k * TILE;
                    uint32_t mx = 0u, mn = 0xffffffffu, mn2 = 0xffffffffu;
#pragma unroll
                    for (int q = 0; q < 12; q++) {
                        uint32_t a0, a1, a2, a3;
                        lds128(tile + K_OFF(q % 6) + (q / 6) * 3072, a0, a1, a2, a3);
                        a0 &= 0x7fff7fffu; a1 &= 0x7fff7fffu; a2 &= 0x7fff7fffu; a3 &= 0x7fff7fffu;
                        mx = __vimax3_u16x2(__vimax3_u16x2(mx, a0, a1), a2, a3);
                        mn = __viaddmin_u16x2(a0, 0xffffffffu, __viaddmin_u16x2(a1, 0xffffffffu, mn));
                        mn2 = __viaddmin_u16x2(a2, 0xffffffffu, __viaddmin_u16x2(a3, 0xffffffffu, mn2));
                    }
                    mn = __vminu2(mn, mn2);
                    const uint32_t emax = __reduce_max_sync(0xffffffffu, max(mx & 0xffffu, mx >> 16)) >> 7;
                    const uint32_t base = (max(emax, 16u) - 15u) << 7, lim = base + 0x7fu;
                    bool raw = emax < 80u || emax > 190u;
                    uint32_t fl = __ballot_sync(0xffffffffu, min(mn & 0xffffu, mn >> 16) < lim);
                    if (!raw && fl) {
                        const uint32_t n0 = lds32(kx);
                        __syncwarp();
#pragma unroll 1
                        for (; fl; fl &= fl - 1) {
                            const int g = (__ffs(fl) - 1) >> 2, t = (__ffs(fl) - 1) & 3, q = min(lane, 23) >> 1, i = q >= 6 ? q - 6 : q;
                            const uint32_t a = tile + K_OFF(i) + (q >= 6 ? 3072 : 0) + 8 * (lane & 1);
                            uint32_t w0, w1;
                            lds64(a, w0, w1);
#pragma unroll 1
                            for (int e = 0; e < 4; e++) {
                                const uint32_t x = __funnelshift_r(w0, w1, 16 * e) & 0xffffu;
                                if (e == 1) w0 = w1;
                                if ((x & 0x7fffu) - 1u < lim && lane < 24) {
                                    uint32_t n;
                                    asm volatile("atom.shared.add.u32 %0, [%1], 1;" : "=r"(n) : "r"(kx) : "memory");
                                    if (n < NEXC) sts32(kx + 32 + 4 * n, x | (2 * ((2 * t + (e >> 1)) * 12 + 2 * i + (lane & 1)) + (e & 1)) << 16 | (16 * (s & 4) + (q >= 6 ? 32 : 0) + 4 * g + (s & 3)) << 24);
                                    sts16(a + 2 * e, 0u);
                                }
                            }
                        }
                        __syncwarp();
                        raw = lds32(kx) > NEXC;
                        __syncwarp();
                        if (raw && lane == 0) sts32(kx, n0);
                    }
                    if (lane == 0) {
                        sts32(kx + 8 + 4 * s, (base + (31u << 7)) << 16);
                        if (raw) sts32(kx + 4, lds32(kx + 4) | 1u << s);
                    }
                    const uint32_t b2 = (0x10000u - base) * 0x10001u;
                    auto pack = [&](auto S) {
                        constexpr int n0 = 36 * decltype(S)::value;
#pragma unroll
                        for (int q = 0; q < 12; q++) {
                            uint32_t a0, a1, a2, a3;
                            lds128(tile + K_OFF(q % 6) + (q / 6) * 3072, a0, a1, a2, a3);
                            a0 = __viaddmax_s16x2(a0 & 0x7fff7fffu, b2, 0u) | (a0 & 0x80008000u); a1 = __viaddmax_s16x2(a1 & 0x7fff7fffu, b2, 0u) | (a1 & 0x80008000u);
                            a2 = __viaddmax_s16x2(a2 & 0x7fff7fffu, b2, 0u) | (a2 & 0x80008000u); a3 = __viaddmax_s16x2(a3 & 0x7fff7fffu, b2, 0u) | (a3 & 0x80008000u);
                            KR(n0 + 3 * q) = __byte_perm(a0, a1, 0x6420);
                            KR(n0 + 3 * q + 1) = __byte_perm(a2, a3, 0x6420);
                            const uint32_t ho = __byte_perm(a2, a3, 0x7531);
                            KR(n0 + 3 * q + 2) = __byte_perm(a0, a1, 0x7531) | __funnelshift_r(ho, ho, 4);
                        }
                    };
                    switch (s) {
                        case 0: pack(IC<0>()); break;
                        case 1: pack(IC<1>()); break;
                        case 2: pack(IC<2>()); break;
                        case 3: pack(IC<3>()); break;
                        default: pack(IC<4>()); break;
                    }
                    __syncwarp();
                }
                if (wu < 2 && (s == 3 || layer)) {
                    const int tc = min(opq(tid), 47);
                    const uint4* pq = opq(&maps.scr->qx[h * 4 * 48 + tc]);
                    uint4 v[4];
                    int it = 0;
                    bool more = true;
#pragma unroll
                    for (int k = 0; k < 4; k++) v[k] = ld_pkt(pq + 48 * k);
                    if (layer == 0) {
                        uint4 u[4];
                        do {
#pragma unroll
                            for (int k = 0; k < 4; k++) u[k] = ld_pkt(pq + NCTA * 48 + 48 * k);
                            more = ++it < SPIN_CAP;
                        } while (!__all_sync(0xffffffffu, u[0].w & u[1].w & u[2].w & u[3].w & 1) && more);
                        sts128(SM_CS + 16 * tc, (f_(u[0].x) + f_(u[1].x)) + (f_(u[2].x) + f_(u[3].x)), (f_(u[0].y) + f_(u[1].y)) + (f_(u[2].y) + f_(u[3].y)),
                               (f_(u[0].z) + f_(u[1].z)) + (f_(u[2].z) + f_(u[3].z)), (f_(u[0].w) + f_(u[1].w)) + (f_(u[2].w) + f_(u[3].w)));
                    }
                    float mean, inv;
                    {
                        const int lane = opq(tid) & 31;
                        uint32_t xw[10];
                        lds128(SM_XS + 16 * lane, xw[0], xw[1], xw[2], xw[3]);
                        lds128(SM_XS + 512 + 16 * lane, xw[4], xw[5], xw[6], xw[7]);
                        lds64(SM_XS + 1024 + 8 * lane, xw[8], xw[9]);
                        float s1 = 0.f, s2 = 0.f, s3 = 0.f, s4 = 0.f;
#pragma unroll
                        for (int i = 0; i < 10; i++) { const float e0 = bf_lo(xw[i]), e1 = bf_hi(xw[i]); s1 += e0; s3 += e1; s2 = fmaf(e0, e0, s2); s4 = fmaf(e1, e1, s4); }
                        s1 += s3; s2 += s4;
                        const bool lo = lane < 16;
                        float sv = (lo ? s1 : s2) + __shfl_xor_sync(0xffffffffu, lo ? s2 : s1, 16);
#pragma unroll
                        for (int o = 8; o > 0; o >>= 1) sv += __shfl_xor_sync(0xffffffffu, sv, o);
                        const float so = __shfl_xor_sync(0xffffffffu, sv, 16);
                        ln_finish(lo ? sv : so, lo ? so : sv, mean, inv);
                    }
                    const float4 cs = lds128f(SM_CS + 16 * tc);
                    mean *= -inv;
                    const float m0 = mean * cs.x, m1 = mean * cs.y, m2 = mean * cs.z, m3 = mean * cs.w;
                    const int w = 2 * tc;
                    const uint32_t qd = opq(SM_QS + 4 * (((w >> 2) & 3) * 24 + 2 * (w >> 4) + ((w >> 1) & 1)));
                    while (__any_sync(0xffffffffu, ((v[0].w ^ tbit) | (v[1].w ^ tbit) | (v[2].w ^ tbit) | (v[3].w ^ tbit)) & 1) && more) {
#pragma unroll
                        for (int k = 0; k < 4; k++) v[k] = ld_pkt(pq + 48 * k);
                        more = ++it < SPIN_CAP;
                    }
                    const float q0 = fmaf(inv, (f_(v[0].x) + f_(v[1].x)) + (f_(v[2].x) + f_(v[3].x)), m0), q1 = fmaf(inv, (f_(v[0].y) + f_(v[1].y)) + (f_(v[2].y) + f_(v[3].y)), m1);
                    const float q2 = fmaf(inv, (f_(v[0].z) + f_(v[1].z)) + (f_(v[2].z) + f_(v[3].z)), m2), q3 = fmaf(inv, (f_(v[0].w) + f_(v[1].w)) + (f_(v[2].w) + f_(v[3].w)), m3);
                    sts32(qd, pack2(q0, q1));
                    sts32(qd + 48, pack2(q2, q3));
                    __syncwarp();
                    if (elect_one()) asm volatile("mbarrier.arrive.shared::cta.b64 _, [%0];" ::"r"(QRDY) : "memory");
                }
            }
            uint32_t qa, ka[3];
            {
                LANE_IDS
                qa = opq(SM_QS + (2 * t + (g & 1)) * 48);
#pragma unroll
                for (int i = 0; i < 3; i++) ka[i] = opq(xtile + K_OFF(2 * i));
            }
            uint32_t f[6][4];
            if (layer == 1) {
                if (wu >= 2 && wu < 5) delay(150);
                mbar_wait(xb, 0);
            }
#pragma unroll
            for (int i = 0; i < 6; i++) lds128(ka[i >> 1] ^ ((i & 1) << 6), f[i][0], f[i][1], f[i][2], f[i][3]);
            if (layer == 1) {
                __syncwarp();
                half_load(xtile, &maps.kh, row0 + 6 * TS + AFTER(ALL6(f, 0)), xb, true);
            }
            mbar_wait(QRDY, layer);
            {
                uint32_t qf[12];
#pragma unroll
                for (int i = 0; i < 3; i++) lds128(qa + 16 * i, qf[4 * i], qf[4 * i + 1], qf[4 * i + 2], qf[4 * i + 3]);
                const int t = opq(tid) & 3;
                auto kr_scores = [&](auto TAU, float& sa, float& sb) {
                    constexpr int tau = decltype(TAU)::value;
                    float cc[2][4] = {{0.f, 0.f, 0.f, 0.f}, {0.f, 0.f, 0.f, 0.f}};
#pragma unroll
                    for (int n = 0; n < 12; n++) {
                        const int q = (n & 1) * 6 + (n >> 1), i = n >> 1;
                        const uint32_t l0 = KR(36 * tau + 3 * q), l1 = KR(36 * tau + 3 * q + 1), hh = KR(36 * tau + 3 * q + 2);
                        const uint32_t h0 = hh & 0x87878787u, h1 = __funnelshift_l(hh, hh, 4) & 0x87878787u;
                        mma16816v(cc[n & 1], __byte_perm(l0, h0, 0x5140), __byte_perm(l0, h0, 0x7362), __byte_perm(l1, h1, 0x5140), __byte_perm(l1, h1, 0x7362), qf[2 * i], qf[2 * i + 1]);
                    }
                    if (t == (tau & 3)) { sa = cc[0][0] + cc[0][3]; sb = cc[1][0] + cc[1][3]; }
                };
                auto stage_v = [&](auto S) {
                    constexpr int s = decltype(S)::value;
                    const int lane = opq(tid) & 31, g = lane >> 2, t = lane & 3;
#pragma unroll
                    for (int i = 0; i < 6; i++) {
                        const uint32_t a = ring + s * TILE + V_OFF(i);
                        lds128(a, kr[12 * s + i][0], kr[12 * s + i][1], kr[12 * s + i][2], kr[12 * s + i][3]);
                        lds128(a + 3072, kr[12 * s + 6 + i][0], kr[12 * s + 6 + i][1], kr[12 * s + 6 + i][2], kr[12 * s + 6 + i][3]);
                    }
                    __syncwarp();
                    tile_load(ring + s * TILE, s ? &maps.v : &maps.k, row0 + (s ? 2 : 7) * TS + AFTER(ALL6(kr, 12 * s) | ALL6(kr, 12 * s + 6)), rb + s * 8);
                };
                if (layer == 1) {
                    float cA[4] = {0.f, 0.f, 0.f, 0.f}, cB[4] = {0.f, 0.f, 0.f, 0.f};
#pragma unroll
                    for (int i = 0; i < 6; i++) {
                        mma16816v(cA, f[i][0], f[i][1], f[i][2], f[i][3], qf[2 * i], qf[2 * i + 1]);
                        lds128((opq(ka[i >> 1]) ^ ((i & 1) << 6)) + 3072, f[i][0], f[i][1], f[i][2], f[i][3]);
                    }
                    __syncwarp();
                    half_load(xtile + 3072, &maps.kh, row0 + 6 * TS + 24 + AFTER(ALL6(f, 0)), xb, false);
#pragma unroll
                    for (int i = 0; i < 6; i++) mma16816v(cB, f[i][0], f[i][1], f[i][2], f[i][3], qf[2 * i], qf[2 * i + 1]);
                    sc2 = cA[0] + cA[3]; sc3 = cB[0] + cB[3];
                }
#pragma unroll
                for (int i = 0; i < 12; i++) qf[i] = mul2(qf[i], 0x6f806f80u);
                kr_scores(IC<0>(), sc0, sc1);
                kr_scores(IC<1>(), sc0, sc1);
                if (layer == 1) stage_v(IC<0>());
                kr_scores(IC<2>(), sc0, sc1);
                if (layer == 1) stage_v(IC<1>());
                kr_scores(IC<3>(), sc0, sc1);
                kr_scores(IC<4>(), sc2, sc3);
                {
                    LANE_IDS
                    const float sa = f_(lds32(kx + 8 + 4 * t)), sb = t == 0 ? f_(lds32(kx + 24)) : 1.0f;
                    const int nx = (int)lds32(kx);
                    uint32_t rm = lds32(kx + 4), qm = 0u;
#pragma unroll
                    for (int i = 0; i < 6; i++) qm = __vimax3_u16x2(qm, qf[2 * i] & 0x7fff7fffu, qf[2 * i + 1] & 0x7fff7fffu);
#pragma unroll
                    for (int i = 0; i < 3; i++) lds128(SM_QS + (2 * t + (g & 1)) * 48 + 16 * i, qf[4 * i], qf[4 * i + 1], qf[4 * i + 2], qf[4 * i + 3]);
                    if (__any_sync(0xffffffffu, max(qm & 0xffffu, qm >> 16) >= 0x7f80u)) rm = 31;
                    sc0 *= sa; sc1 *= sa; sc2 *= sb; sc3 *= sb;
                    if (nx) {
                        const uint32_t w = lds32(kx + 32 + 4 * (lane & 15));
                        const float d = bf_lo(lds16(SM_QS + ((w >> 15) & 0x1fe))) * bf_lo(w);
#pragma unroll 1
                        for (int n = 0; n < nx; n++) {
                            const uint32_t k = (__shfl_sync(0xffffffffu, w, n) >> 24) ^ lane;
                            const float dn = __shfl_sync(0xffffffffu, d, n);
                            if (k == 0) sc0 += dn;
                            if (k == 32) sc1 += dn;
                            if (k == 64) sc2 += dn;
                            if (k == 96) sc3 += dn;
                        }
                    }
#pragma unroll 1
                    for (; rm; rm &= rm - 1) {
                        const int tau = __ffs(rm) - 1;
#pragma unroll 1
                        for (int hf = 0; hf < 2; hf++) {
                            const char* gp = static_cast<const char*>(maps.kp) + (size_t)(row0 + tau * TS) * 128 + (8 * hf + (g >> 1) + 4 * (g & 1)) * 384 + 16 * t;
                            float cA[4] = {0.f, 0.f, 0.f, 0.f};
#pragma unroll
                            for (int i = 0; i < 6; i++) {
                                const uint4 a = __ldcg(reinterpret_cast<const uint4*>(gp + 64 * i));
                                mma16816(cA, a.x, a.y, a.z, a.w, qf[2 * i], qf[2 * i + 1]);
                            }
                            if ((tau & 3) == t) {
                                const int k = hf + (tau >> 2) * 2;
                                const float d = cA[0] + cA[3];
                                if (k == 0) sc0 = d; else if (k == 1) sc1 = d; else if (k == 2) sc2 = d; else sc3 = d;
                            }
                        }
                    }
                }
                if (layer == 0) {
                    LANE_IDS
#pragma unroll 1
                    for (int s = 5; s < 8; s++) {
                        mbar_wait(s == 5 ? xb : rb + (s & 1) * 8, s == 5);
                        const uint32_t tile = s == 5 ? bt : ring + (s & 1) * TILE;
                        float cA[4] = {0.f, 0.f, 0.f, 0.f}, cB[4] = {0.f, 0.f, 0.f, 0.f};
#pragma unroll
                        for (int i = 0; i < 6; i++) {
                            uint32_t a0, a1, a2, a3;
                            lds128(tile + K_OFF(i), a0, a1, a2, a3);
                            mma16816(cA, a0, a1, a2, a3, qf[2 * i], qf[2 * i + 1]);
                            lds128(tile + K_OFF(i) + 3072, a0, a1, a2, a3);
                            mma16816(cB, a0, a1, a2, a3, qf[2 * i], qf[2 * i + 1]);
                        }
                        if (t == (s & 3)) { sc2 = cA[0] + cA[3]; sc3 = cB[0] + cB[3]; }
                        __syncwarp();
                        refill1(s, AFTER(__float_as_uint(cA[0]) | __float_as_uint(cB[0])));
                    }
                } else {
                    LANE_IDS
#pragma unroll 1
                    for (int i = 2; i < 4; i++) {
                        const uint32_t tile = i == 3 ? ring : xtile, tb = i == 3 ? rb : xb;
                        mbar_wait(tb, 1);
#pragma unroll
                        for (int k = 0; k < 6; k++) {
                            const uint32_t a = tile + K_OFF(k);
                            lds128(a, kr[24 + k][0], kr[24 + k][1], kr[24 + k][2], kr[24 + k][3]);
                            lds128(a + 3072, kr[24 + 6 + k][0], kr[24 + 6 + k][1], kr[24 + 6 + k][2], kr[24 + 6 + k][3]);
                        }
                        float cA[4] = {0.f, 0.f, 0.f, 0.f}, cB[4] = {0.f, 0.f, 0.f, 0.f}, cC[4] = {0.f, 0.f, 0.f, 0.f}, cD[4] = {0.f, 0.f, 0.f, 0.f};
#pragma unroll
                        for (int k = 0; k < 3; k++) {
                            mma16816(cA, kr[24 + k][0], kr[24 + k][1], kr[24 + k][2], kr[24 + k][3], qf[2 * k], qf[2 * k + 1]);
                            mma16816(cB, kr[24 + 6 + k][0], kr[24 + 6 + k][1], kr[24 + 6 + k][2], kr[24 + 6 + k][3], qf[2 * k], qf[2 * k + 1]);
                            mma16816(cC, kr[24 + 3 + k][0], kr[24 + 3 + k][1], kr[24 + 3 + k][2], kr[24 + 3 + k][3], qf[6 + 2 * k], qf[7 + 2 * k]);
                            mma16816(cD, kr[24 + 9 + k][0], kr[24 + 9 + k][1], kr[24 + 9 + k][2], kr[24 + 9 + k][3], qf[6 + 2 * k], qf[7 + 2 * k]);
                        }
                        __syncwarp();
                        tile_load(tile, &maps.v, row0 + (i + 1) * TS + AFTER(__float_as_uint(cA[0]) | __float_as_uint(cB[0]) | __float_as_uint(cC[0]) | __float_as_uint(cD[0])), tb);
                        if (t == i) { sc2 = (cA[0] + cC[0]) + (cA[3] + cC[3]); sc3 = (cB[0] + cD[0]) + (cB[3] + cD[3]); }
                    }
                }
            }
            {
                const uint32_t mk = __reduce_max_sync(0xffffffffu, f2key(fmaxf(fmaxf(sc0, sc1), fmaxf(sc2, sc3))));
                if ((opq(tid) & 31) == 0) st_pkt2(&maps.scr->mx[h * 32 + c * 8 + wu], mk, tag);
                mw = key2f(mk);
            }
            pk0 = pack2(ex2((sc0 - mw) * SC), ex2((sc1 - mw) * SC));
            pk1 = pack2(ex2((sc2 - mw) * SC), ex2((sc3 - mw) * SC));
            sc2 = (bf_lo(pk0) + bf_hi(pk0)) + (bf_lo(pk1) + bf_hi(pk1));
#pragma unroll
            for (int o = 16; o > 0; o >>= 1) sc2 += __shfl_xor_sync(0xffffffffu, sc2, o);
#pragma unroll
            for (int s = 0; s < 3; s++) { acc[s][0] = acc[s][1] = acc[s][2] = acc[s][3] = 0.f; }
            auto head_ld = [&](int lane) { const uint2 mv = ld_pkt2(&maps.scr->mx[h * 32 + lane]); sc0 = f_(mv.x); sc1 = f_(mv.y); };
            auto head_factor = [&](int lane) {
                int it = 0;
                while (!__all_sync(0xffffffffu, __float_as_uint(sc1) == tag) && ++it < SPIN_CAP) head_ld(lane);
                sc3 = ex2((mw - key2f(__reduce_max_sync(0xffffffffu, __float_as_uint(sc0)))) * SC);
            };
#define P_CONSTS \
                const uint32_t sel0 = g == 0 ? 0x4410u : (g == 1 ? 0x1044u : 0x4444u); \
                const uint32_t sel1 = g == 2 ? 0x4410u : (g == 3 ? 0x1044u : 0x4444u); \
                const int src00 = 4 * (t < 2 ? 4 * t : 4 * (t - 2) + 1);
#define P_FRAGS(tau) \
                const uint32_t pk = ((tau) & 4) ? pk1 : pk0; \
                const uint32_t w0 = __shfl_sync(0xffffffffu, pk, src00 + ((tau) & 3)); \
                const uint32_t w1 = __shfl_sync(0xffffffffu, pk, src00 + ((tau) & 3) + 8); \
                uint32_t pb[4][2]; \
                _Pragma("unroll") for (int j = 0; j < 4; j++) { \
                    const uint32_t src = ((j & 1) ? w1 : w0) >> ((j >> 1) * 16); \
                    pb[j][0] = __byte_perm(src, 0, sel0); pb[j][1] = __byte_perm(src, 0, sel1); \
                }
            if (layer == 0) {
#pragma unroll 1
                for (int s = 8; s < 16; s++) {
                    LANE_IDS
                    P_CONSTS
                    if (s == 14) {
                        uint4* p = nullptr;
                        if (tl < 48) p = &maps.scr->qx[b * 48 + tl];
                        else if (tl < 98) p = &maps.scr->cx[b * 56 + tl - 48];
                        else if (tl < 145) {}
                        else if (tl >= 160) { if (tl < 208) p = &maps.scr->qc[b * 48 + tl - 160]; }
                        else if (b < NG) { if (tl < 153) p = &maps.scr->ah[b * 8 + tl - 145]; }
                        else if (b < DN0 + NDN && tl < 149) p = &maps.scr->ay[(b - DN0) * 4 + tl - 145];
                        if (p) st_pkt(p, 0, 0, 0, tl < 48);
                    }
                    if (s == 13) head_ld(lane);
                    P_FRAGS((s + 2) & 7)
                    mbar_wait(rb + (s & 1) * 8, ((s >> 1) + 1) & 1);
                    const uint32_t tile = ring + (s & 1) * TILE;
#pragma unroll
                    for (int j = 0; j < 4; j++) {
#pragma unroll
                        for (int u = 0; u < 3; u++) {
                            uint32_t a0, a1, a2, a3;
                            lds128(tile + (j >> 1) * 3072 + V_OFF(3 * (j & 1) + u), a0, a1, a2, a3);
                            mma16816(acc[u], a0, a1, a2, a3, pb[j][0], pb[j][1]);
                        }
                    }
                    __syncwarp();
                    if (s < 14) refill1(s, AFTER(__float_as_uint(acc[0][0]) | __float_as_uint(acc[1][0]) | __float_as_uint(acc[2][0])), true);
                    if (s == 13) head_factor(lane);
                    if (s == 15 && elect_one()) {
                        uint32_t n;
                        asm volatile("atom.shared.add.u32 %0, [%1], 1;" : "=r"(n) : "r"(SM_MISC + 8) : "memory");
                        if (n == 7) load_wo(maps, SM_B, h, c, WBAR, 5);
                    }
                }
            } else {
                LANE_IDS
                P_CONSTS
#pragma unroll
                for (int s = 0; s < 2; s++) {
                    P_FRAGS(s)
#pragma unroll
                    for (int j = 0; j < 4; j++) {
#pragma unroll
                        for (int u = 0; u < 3; u++) {
                            const int k = 6 * (j >> 1) + 3 * (j & 1) + u;
                            mma16816(acc[u], kr[12 * s + k][0], kr[12 * s + k][1], kr[12 * s + k][2], kr[12 * s + k][3], pb[j][0], pb[j][1]);
                        }
                    }
                }
#pragma unroll 1
                for (int i = 4; i < 10; i++) {
                    const int sl = i == 5 ? 0 : (i == 6 || i == 8 ? 1 : 2);
                    const uint32_t tile = sl ? ring + (sl - 1) * TILE : xtile, tb = sl ? rb + (sl - 1) * 8 : xb;
                    if (i == 8) head_ld(lane);
                    if (i == 9) head_factor(lane);
                    P_FRAGS(i - 2)
                    mbar_wait(tb, (0x310 >> i) & 1);
#pragma unroll
                    for (int k = 0; k < 6; k++) {
                        const uint32_t a = tile + V_OFF(k);
                        lds128(a, kr[24 + k][0], kr[24 + k][1], kr[24 + k][2], kr[24 + k][3]);
                        lds128(a + 3072, kr[24 + 6 + k][0], kr[24 + 6 + k][1], kr[24 + 6 + k][2], kr[24 + 6 + k][3]);
                    }
#pragma unroll
                    for (int j = 0; j < 4; j++) {
#pragma unroll
                        for (int u = 0; u < 3; u++) {
                            const int k = 6 * (j >> 1) + 3 * (j & 1) + u;
                            mma16816(acc[u], kr[24 + k][0], kr[24 + k][1], kr[24 + k][2], kr[24 + k][3], pb[j][0], pb[j][1]);
                        }
                    }
                    __syncwarp();
                    if (wu < L1R && i == 6 - 2 * (wu & 1)) tile_load_l1(tile, maps.vp, row0 + (6 - (wu & 1)) * TS, tb, lane);
                    else if (i == 4 || i == 6 || i == 7) tile_load(tile, &maps.v, row0 + (i == 4 ? 5 : i) * TS + AFTER(__float_as_uint(acc[0][0]) | __float_as_uint(acc[1][0]) | __float_as_uint(acc[2][0])), tb);
                    if (i == 7 && role < DN0 + NDN && elect_one()) {
                        uint32_t n;
                        asm volatile("atom.shared.add.u32 %0, [%1], 1;" : "=r"(n) : "r"(SM_MISC + 8) : "memory");
                        if (n == 15) load_wo(maps, SM_Q, h, c, WBAR, 3);
                    }
                }
            }
#undef P_FRAGS
#undef P_CONSTS
#undef LANE_IDS
#undef K_OFF
#undef V_OFF
        }

        uint32_t ticket = 0;
        {
            const int tl = opq(tid), warp = tl >> 5, lane = tl & 31, g = lane >> 2, t = lane & 3, mat = lane >> 3, r8 = lane & 7;
            {
                const uint32_t d = SM_R + 4 * (warp * 196 + 8 * g + 4 * t);
                if (t < 2) {
#pragma unroll
                    for (int u = 0; u < 3; u++) sts128(d + 256 * u, acc[u][0] * sc3, acc[u][1] * sc3, acc[u][2] * sc3, acc[u][3] * sc3);
                }
                if (lane == 0) sts128(d + 768, sc2 * sc3, 0.f, 0.f, 0.f);
            }
            const int tc = min(tl, 48);
            uint4* pc = opq(&maps.scr->cx[h * 4 * 56 + tc]);
            uint4* po = pc + c * 56;
            const uint32_t fa = opq(SM_R + 16 * tc);
            __syncthreads();
            const int kg = warp >> 1, mg = warp & 1;
            const bool wo2 = layer && role < DN0 + NDN;
            const bool wo4 = layer && role < NG;
            uint32_t aw, oa, ob0, dw;
            uint32_t* tk;
            auto addrs = [&]() {
                aw = opq((wo2 ? SM_Q : SM_B) + (48 * kg + (mat >> 1) * 8 + r8) * 64 + (((2 * mg + (mat & 1)) ^ ((r8 >> 1) & 3)) << 4));
                oa = opq(SM_OS + 96 * kg + 8 * t);
                ob0 = opq(oa + 8 * t);
                dw = opq(SM_R + 4 * (4 * (16 * mg + g) + kg));
                tk = maps.scr->ticket;
            };
            uint32_t a[2][3][4];
            auto preload = [&]() {
#pragma unroll
                for (int i = 0; i < 2; i++) {
                    mbar_wait(WBAR + 8 * i, wo2);
#pragma unroll
                    for (int ks = 0; ks < 3; ks++) ldsm4t(aw + i * 12288 + ks * 1024, a[i][ks]);
                }
            };
            if (wu < 2) {
                if (tl < 49) {
                    float4 v[8];
#pragma unroll
                    for (int w = 0; w < 8; w++) v[w] = lds128f(fa + w * 784);
                    st_pktf(po, ((v[0].x + v[1].x) + (v[2].x + v[3].x)) + ((v[4].x + v[5].x) + (v[6].x + v[7].x)),
                            ((v[0].y + v[1].y) + (v[2].y + v[3].y)) + ((v[4].y + v[5].y) + (v[6].y + v[7].y)),
                            ((v[0].z + v[1].z) + (v[2].z + v[3].z)) + ((v[4].z + v[5].z) + (v[6].z + v[7].z)),
                            ((v[0].w + v[1].w) + (v[2].w + v[3].w)) + ((v[4].w + v[5].w) + (v[6].w + v[7].w)), tbit);
                }
                __syncwarp();
                uint4 v[4];
#pragma unroll
                for (int k = 0; k < 4; k++) v[k] = ld_pkt(pc + k * 56);
                asm volatile("bar.arrive 1, 256;" ::: "memory");
                addrs();
                const int w = 2 * tc, k3 = w / 24, r = w - 24 * k3;
                const uint32_t d0 = opq(tl < 48 ? SM_OS + 4 * (24 * k3 + (r < 16 ? 4 * (r & 3) + (r >> 2) : 16 + 2 * (r & 3) + ((r >> 2) & 1))) : SM_MISC);
                const uint32_t d1 = opq(tl < 48 ? d0 + (r < 16 ? 16 : 8) : SM_MISC + 12);
                int it = 0;
                bool more = true;
                while (__any_sync(0xffffffffu, ((v[0].w ^ tbit) | (v[1].w ^ tbit) | (v[2].w ^ tbit) | (v[3].w ^ tbit)) & 1) && more) {
#pragma unroll
                    for (int k = 0; k < 4; k++) v[k] = ld_pkt(pc + k * 56);
                    more = ++it < SPIN_CAP;
                }
                const float o0 = (f_(v[0].x) + f_(v[1].x)) + (f_(v[2].x) + f_(v[3].x));
                const uint32_t w0 = pack2(o0, (f_(v[0].y) + f_(v[1].y)) + (f_(v[2].y) + f_(v[3].y)));
                sts32(d1, pack2((f_(v[0].z) + f_(v[1].z)) + (f_(v[2].z) + f_(v[3].z)), (f_(v[0].w) + f_(v[1].w)) + (f_(v[2].w) + f_(v[3].w))));
                sts32(d0, tl < 48 ? w0 : __float_as_uint(o0));
                asm volatile("bar.arrive 2, 256;" ::: "memory");
                preload();
                asm volatile("bar.sync 3, 64;" ::: "memory");
            } else {
                addrs();
                asm volatile("bar.sync 1, 256;" ::: "memory");
                preload();
                asm volatile("bar.sync 2, 256;" ::: "memory");
            }
            uint32_t ob[6];
            lds128(ob0, ob[0], ob[1], ob[2], ob[3]);
            lds64(oa + 64, ob[4], ob[5]);
            if (tl == 224 && layer == 0)
                asm volatile("atom.relaxed.gpu.global.inc.u32 %0, [%1], 0x7fffffff;" : "=r"(ticket) : "l"(tk) : "memory");
            auto put = [&](int i, const float (&cc)[4]) { if (t == 0) { sts32(dw + 512 * i, cc[0]); sts32(dw + 512 * i + 128, cc[2]); } };
            {
                float c0[4] = {0.f, 0.f, 0.f, 0.f}, c1[4] = {0.f, 0.f, 0.f, 0.f}, c2[4] = {0.f, 0.f, 0.f, 0.f}, c3[4] = {0.f, 0.f, 0.f, 0.f};
                mbar_wait(WBAR + 16, wo2);
#pragma unroll
                for (int ks = 0; ks < 3; ks++) {
                    mma16816v(c0, a[0][ks][0], a[0][ks][1], a[0][ks][2], a[0][ks][3], ob[2 * ks], ob[2 * ks + 1]);
                    mma16816v(c1, a[1][ks][0], a[1][ks][1], a[1][ks][2], a[1][ks][3], ob[2 * ks], ob[2 * ks + 1]);
                    if (ks == 0 && layer == 0) {
                        mbar_wait(WBAR + 24, 0);
#pragma unroll
                        for (int k = 0; k < 3; k++) ldsm4t(aw + 3 * 12288 + k * 1024, wk[k]);
                    }
                    if (ks == 1) mbar_wait(WBAR + 32, wo4);
                    ldsm4t(aw + 2 * 12288 + ks * 1024, a[0][ks]);
                }
                const uint32_t aw4 = aw + (wo2 && !wo4 ? SM_B - SM_Q : 0) + 4 * 12288;
                ldsm4t(aw4 + 1024, a[1][0]);
#pragma unroll
                for (int ks = 0; ks < 3; ks++) {
                    mma16816v(c2, a[0][ks][0], a[0][ks][1], a[0][ks][2], a[0][ks][3], ob[2 * ks], ob[2 * ks + 1]);
                    mma16816v(c3, wk[ks][0], wk[ks][1], wk[ks][2], wk[ks][3], ob[2 * ks], ob[2 * ks + 1]);
                    if (ks == 0) { ldsm4t(aw4, a[0][0]); put(0, c0); put(1, c1); }
                    if (ks == 1) ldsm4t(aw4 + 2048, a[0][1]);
                }
                float c4[4] = {0.f, 0.f, 0.f, 0.f}, c5[4] = {0.f, 0.f, 0.f, 0.f};
                mma16816v(c4, a[0][0][0], a[0][0][1], a[0][0][2], a[0][0][3], ob[0], ob[1]);
                mma16816v(c5, a[1][0][0], a[1][0][1], a[1][0][2], a[1][0][3], ob[2], ob[3]);
                mma16816v(c4, a[0][1][0], a[0][1][1], a[0][1][2], a[0][1][3], ob[4], ob[5]);
                put(2, c2); put(3, c3);
                c4[0] += c5[0]; c4[2] += c5[2];
                put(4, c4);
            }
        }
        {
            const int tl = opq(tid);
            uint4* pr = opq(&maps.scr->acc[layer][54 * c + min(tl, 53)]);
            const uint32_t fa = opq(SM_R + 48 * tl);
            const float il = rcp(f_(lds32(SM_MISC)));
            __syncthreads();
            if (tl < 54) {
                const float4 v0 = lds128f(fa), v1 = lds128f(fa + 16), v2 = lds128f(fa + 32);
                const float y0 = il * ((v0.x + v0.y) + (v0.z + v0.w)), y1 = il * ((v1.x + v1.y) + (v1.z + v1.w)), y2 = il * ((v2.x + v2.y) + (v2.z + v2.w));
                red_pkt(pr, y0, tl == 53 ? 0.f : y1, tl == 53 ? 0.f : y2);
            }
            if (tl == 224 && layer == 0) {
                sts32(SM_MISC + 4, ticket);
                if (ticket < NG) load_ffn(maps, ticket, SM_B, FBAR);
            }
        }
        __syncthreads();
        if (layer == 0) role = __shfl_sync(0xffffffffu, (int)lds32(SM_MISC + 4), 0);
        const uint32_t DONE32 = 0x42000000u;
        if (role < NG) {
            const int tl = opq(tid), warp = tl >> 5, lane = tl & 31, g = lane >> 2, t = lane & 3, mat = lane >> 3, r8 = lane & 7;
            const uint32_t ag = SM_B + (80 * warp + (mat >> 1) * 8 + r8) * 96 + (((mat & 1) ^ (r8 >> 2)) << 4);
            constexpr int GI = 32, GK = 16 * 96;
            const bool on = (g & 1) == (t >> 1), isx = (on && g < 2) || g == 4;
            const uint32_t pm = opq(isx ? SM_XS + 160 * warp + 16 * t : (on || g == 5 ? SM_ONE : SM_ZERO)), pm2 = opq(pm + 128 - (isx ? 8 * t : 0));
            const uint32_t dg = opq(SM_R + 4 * (2 * (warp * 48 + g) + t));
            const uint32_t ho = opq(16u * (role * 8 + 4 * warp + ((lane * 11) >> 5)));
            const uint32_t fa = opq(SM_R + 8 * (24 * warp + 2 * min(lane, 11)));
            uint32_t pre[9][4];
            {
                bool hx = wu == 7;
                int it = 0;
                const uint4* px = opq(&maps.scr->acc[layer][min(tl, 215)]);
                const int cq = tl / 54, r = tl - 54 * cq, k0 = min(160 * cq + 3 * r, DM - 1);
                const uint32_t w0 = SM_XS + 4 * xpos(k0 >> 1), w1 = SM_XS + 4 * xpos(min((k0 >> 1) + 1, DM / 2 - 1));
                const bool two = tl < 216 && r != 53;
                const uint32_t e0 = opq(tl < 216 ? w0 + 2 * (k0 & 1) : SM_MISC + 12);
                const uint32_t e1 = opq(two ? ((k0 & 1) ? w1 : w0 + 2) : SM_MISC + 12), e2 = opq(two ? w1 + 2 * (k0 & 1) : SM_MISC + 12);
                const uint32_t x01 = opq(lds16(e0) | (lds16(e1) << 16)), x2 = lds16(e2);
                auto take_x = [&](const uint4 v) {
                    if (__all_sync(0xffffffffu, v.w == DONE32)) {
                        hx = true;
                        const uint32_t y01 = add2(x01, pack2(f_(v.x), f_(v.y))), y2 = add2(x2, pack2(f_(v.z), 0.f));
                        sts16(e0, y01); sts16(e1, y01 >> 16); sts16(e2, y2);
                    }
                };
                while (!mbar_test(FBAR, 0) && ++it < SPIN_CAP) { if (!hx) take_x(ld_pkt(px)); }
                uint4 v = make_uint4(0u, 0u, 0u, 0u);
                if (!hx) v = ld_pkt(px);
#pragma unroll
                for (int n = 0; n < 9; n++) ldsm4t(ag + (n % 3) * GI + (n / 3) * GK, pre[n]);
                if (layer) {
#pragma unroll
                    for (int n = 9; n < 15; n++) ldsm4t(ag + (n % 3) * GI + (n / 3) * GK, kr[n - 9]);
                }
                if (!hx) {
                    bool more = true;
                    while (!__all_sync(0xffffffffu, v.w == DONE32) && more) { v = ld_pkt(px); more = ++it < SPIN_CAP; }
                    const uint32_t y01 = add2(x01, pack2(f_(v.x), f_(v.y))), y2 = add2(x2, pack2(f_(v.z), 0.f));
                    sts16(e0, y01); sts16(e1, y01 >> 16); sts16(e2, y2);
                }
            }
            __syncthreads();
            {
                float cc[3][4], gr[4];
                if (layer) gemv15r(cc, gr, pre, kr, pm, pm2);
                else gemv15<GK, true>(cc, gr, pre, [&](int i) { return ag + i * GI; }, pm, pm2);
                if (t < 2) {
#pragma unroll
                    for (int i = 0; i < 3; i++) { sts32(dg + 128 * i, cc[i][0] + cc[i][3]); sts32(dg + 128 * i + 64, cc[i][1] + cc[i][2]); }
                }
                if ((lane | 4) == 22) sts32(SM_ST + 8 * warp + (g & 1) * 4, gr[0]);
            }
            uint4* ph = reinterpret_cast<uint4*>(reinterpret_cast<char*>(maps.scr->ah) + ho);
            const bool snd = (0x249 >> lane) & 1;
            __syncthreads();
            if (wu < 2) {
                float mean, inv;
                float4 v[8];
#pragma unroll
                for (int w = 0; w < 8; w++) v[w] = lds128f(fa + w * 384);
                ln_stats(mean, inv);
                const float ga = inv * ((((v[0].x + v[1].x) + (v[2].x + v[3].x)) + ((v[4].x + v[5].x) + (v[6].x + v[7].x))) -
                                        mean * (((v[0].y + v[1].y) + (v[2].y + v[3].y)) + ((v[4].y + v[5].y) + (v[6].y + v[7].y))));
                const float gb = inv * ((((v[0].z + v[1].z) + (v[2].z + v[3].z)) + ((v[4].z + v[5].z) + (v[6].z + v[7].z))) -
                                        mean * (((v[0].w + v[1].w) + (v[2].w + v[3].w)) + ((v[4].w + v[5].w) + (v[6].w + v[7].w))));
                uint32_t wd = pack2(ga, gb);
                if (role < NG / 2) {
                    const float g0 = bf_lo(wd), g1 = bf_hi(wd);
                    wd = pack2(g0 * rcp(1.0f + ex2(-1.4426950408889634f * g0)), g1 * rcp(1.0f + ex2(-1.4426950408889634f * g1)));
                }
                const uint32_t wa = __shfl_down_sync(0xffffffffu, wd, 1), wb = __shfl_down_sync(0xffffffffu, wd, 2);
                if (snd) st_pkt(ph, wd, wa, wb, tag);
            }
            __syncthreads();
        } else if (role < DN0 + NDN) {
            const int j = role - DN0;
            const int tl = opq(tid), warp = tl >> 5, lane = tl & 31, g = lane >> 2, t = lane & 3, mat = lane >> 3, r8 = lane & 7;
            float xr0 = 0.f, xr1 = 0.f;
            if (wu == 0) {
                const int col = 16 * j + (lane & 15), cc = col / 160, r = col - 160 * cc, e = r % 3;
                const uint4* px = &maps.scr->acc[layer][(54 * cc + r / 3)];
                const float x0 = bf_lo(lds16(SM_XS + 4 * xpos(col >> 1) + 2 * (col & 1)));
                uint4 v;
                int it = 0;
                bool ld = layer == 0;
                do {
                    v = ld_pkt(px);
                    if (ld && f_(__shfl_sync(0xffffffffu, v.w, 0)) >= (float)DNTH) { ld = false; if (lane == 0) load_ffn(maps, role, SM_B, FBAR); }
                } while (!__all_sync(0xffffffffu, v.w == DONE32) && ++it < SPIN_CAP);
                if (ld && lane == 0) load_ffn(maps, role, SM_B, FBAR);
                const float xres = bfr(x0 + bfr(f_(e == 0 ? v.x : (e == 1 ? v.y : v.z))));
                xr0 = __shfl_sync(0xffffffffu, xres, 2 * (lane & 7));
                xr1 = __shfl_sync(0xffffffffu, xres, 2 * (lane & 7) + 1);
            }
            const uint32_t ad = SM_B + (192 * warp + (mat >> 1) * 8 + r8) * 32 + (((mat & 1) ^ (r8 >> 2)) << 4);
            const uint32_t hs = SM_R + 384 * warp, hb = opq(hs + 16 * t), dd = opq(SM_R + 3072 + 4 * (warp * 16 + g));
            uint32_t pre[NPRE][4];
            uint32_t pos[3];
#pragma unroll
            for (int i = 0; i < 3; i++) { const int w = 3 * lane + i; pos[i] = opq(hs + 4 * ((w & ~15) + 4 * (w & 3) + ((w >> 2) & 1) + ((w >> 2) & 2))); }
            const uint4* ph = opq(&maps.scr->ah[tl]);
            const uint32_t fa = opq(SM_R + 3072 + 8 * (lane & 7));
            uint2* py = opq(reinterpret_cast<uint2*>(maps.scr->ay) + 8 * j + (lane & 7));
            uint32_t* po = opq(reinterpret_cast<uint32_t*>(out) + 8 * j + (lane & 7));
            mbar_wait(FBAR, 0);
#pragma unroll
            for (int n = 0; n < NPRE; n++) ldsm4t(ad + n * 512, pre[n]);
            {
                uint4 v, u;
                int it = 0;
                bool more;
                do { v = ld_pkt(ph); u = ld_pkt(ph + 256); more = ++it < SPIN_CAP; }
                while (!__all_sync(0xffffffffu, v.w == tag && u.w == tag) && more);
                sts32(pos[0], mul2(v.x, u.x)); sts32(pos[1], mul2(v.y, u.y)); sts32(pos[2], mul2(v.z, u.z));
            }
            __syncwarp();
            {
                float cc[4][4];
                uint32_t hv[3][4];
#pragma unroll
                for (int jj = 0; jj < 3; jj++) lds128(hb + 64 * jj, hv[jj][0], hv[jj][1], hv[jj][2], hv[jj][3]);
#pragma unroll
                for (int n = 0; n < 12; n++) {
                    const int s = n < NPRE ? n : n - NPRE;
                    if (n < 4) cc[n][0] = cc[n][1] = cc[n][2] = cc[n][3] = 0.f;
                    mma16816v(cc[n & 3], pre[s][0], pre[s][1], pre[s][2], pre[s][3], hv[(n >> 1) % 3][2 * (n & 1)], hv[(n >> 1) % 3][2 * (n & 1) + 1]);
                    if (n + NPRE < 12) ldsm4t(ad + (n + NPRE) * 512, pre[n]);
                    if ((n & 1) && n < 6) lds128(hb + 64 * ((n >> 1) + 3), hv[n >> 1][0], hv[n >> 1][1], hv[n >> 1][2], hv[n >> 1][3]);
                }
                if (t == 0) { sts32(dd, (cc[0][0] + cc[1][0]) + (cc[2][0] + cc[3][0])); sts32(dd + 32, (cc[0][2] + cc[1][2]) + (cc[2][2] + cc[3][2])); }
            }
            __syncthreads();
            if (tl < 8) {
                float2 v[8];
#pragma unroll
                for (int w = 0; w < 8; w++) v[w] = lds64f(fa + 64 * w);
                const uint32_t y = pack2(((v[0].x + v[1].x) + (v[2].x + v[3].x)) + ((v[4].x + v[5].x) + (v[6].x + v[7].x)),
                                         ((v[0].y + v[1].y) + (v[2].y + v[3].y)) + ((v[4].y + v[5].y) + (v[6].y + v[7].y)));
                const uint32_t wd = pack2(xr0 + bf_lo(y), xr1 + bf_hi(y));
                if (layer) asm volatile("st.global.u32 [%0], %1;" ::"l"(po), "r"(wd) : "memory");
                st_pkt2(py, wd, tag);
            }
            __syncthreads();
        }
    }
}

typedef CUresult (*EncodeFn)(CUtensorMap*, CUtensorMapDataType, cuuint32_t, void*, const cuuint64_t*, const cuuint64_t*, const cuuint32_t*,
                             const cuuint32_t*, CUtensorMapInterleave, CUtensorMapSwizzle, CUtensorMapL2promotion, CUtensorMapFloatOOBfill);

void make_map(EncodeFn enc, CUtensorMap* m, const void* base, int rank, uint64_t d0, uint64_t d1, uint64_t d2, uint64_t s1, uint64_t s2,
              uint32_t b0, uint32_t b1, uint32_t b2, CUtensorMapSwizzle sw, CUtensorMapL2promotion pr = CU_TENSOR_MAP_L2_PROMOTION_NONE) {
    cuuint64_t dims[3] = {d0, d1, d2};
    cuuint64_t strides[2] = {s1, s2};
    cuuint32_t box[3] = {b0, b1, b2};
    cuuint32_t es[3] = {1, 1, 1};
    enc(m, CU_TENSOR_MAP_DATA_TYPE_BFLOAT16, rank, const_cast<void*>(base), dims, strides, box, es, CU_TENSOR_MAP_INTERLEAVE_NONE, sw,
        pr, CU_TENSOR_MAP_FLOAT_OOB_FILL_NONE);
}

}

extern "C" void kernel_launch(void* const* d_in, const int* in_sizes, int n_in, void* d_out, int out_size) {
    (void)in_sizes; (void)n_in; (void)out_size;
    static EncodeFn enc = nullptr;
    static Scratch* scr = nullptr;
    if (!enc) {
        void* fn = nullptr;
        cudaDriverEntryPointQueryResult qr;
        cudaGetDriverEntryPoint("cuTensorMapEncodeTiled", &fn, cudaEnableDefault, &qr);
        enc = reinterpret_cast<EncodeFn>(fn);
        cudaGetSymbolAddress(reinterpret_cast<void**>(&scr), g_scr);
        cudaFuncSetAttribute(decode_kernel, cudaFuncAttributeMaxDynamicSharedMemorySize, SM_TOTAL);
    }
    Maps maps;
    make_map(enc, &maps.k, d_in[1], 2, 64, (uint64_t)NH * SK * 3, 1, 128, 0, 64, 48, 1, CU_TENSOR_MAP_SWIZZLE_128B);
    make_map(enc, &maps.v, d_in[2], 2, 64, (uint64_t)NH * SK * 3, 1, 128, 0, 64, 48, 1, CU_TENSOR_MAP_SWIZZLE_128B);
    {
        cuuint64_t dims[5] = {64, 16, NH * DH / 64, DM / 80, 5};
        cuuint64_t strides[4] = {NH * DH * 2, 128, 80 * NH * DH * 2, 16 * NH * DH * 2};
        cuuint32_t box[5] = {64, 16, 3, 2, 5};
        cuuint32_t es[5] = {1, 1, 1, 1, 1};
        enc(&maps.wq, CU_TENSOR_MAP_DATA_TYPE_BFLOAT16, 5, d_in[3], dims, strides, box, es, CU_TENSOR_MAP_INTERLEAVE_NONE, CU_TENSOR_MAP_SWIZZLE_128B,
            CU_TENSOR_MAP_L2_PROMOTION_NONE, CU_TENSOR_MAP_FLOAT_OOB_FILL_NONE);
    }
    make_map(enc, &maps.wo, d_in[4], 3, 32, NH * DH, DM / 32, DM * 2, 64, 32, 192, 1, CU_TENSOR_MAP_SWIZZLE_64B);
    constexpr int GW = 48;
    make_map(enc, &maps.w1, d_in[6], 3, FF, 160, 4, FF * 2, 160 * FF * 2, GW, 160, 4, CU_TENSOR_MAP_SWIZZLE_NONE);
    make_map(enc, &maps.w3, d_in[7], 3, FF, 160, 4, FF * 2, 160 * FF * 2, GW, 160, 4, CU_TENSOR_MAP_SWIZZLE_NONE);
    make_map(enc, &maps.w2, d_in[8], 3, DM, 256, 6, DM * 2, 256 * DM * 2, 16, 256, 6, CU_TENSOR_MAP_SWIZZLE_32B);
    make_map(enc, &maps.ks, d_in[1], 2, 64, (uint64_t)NH * SK * 3, 1, 128, 0, 16, 48, 1, CU_TENSOR_MAP_SWIZZLE_NONE);
    make_map(enc, &maps.vs, d_in[2], 2, 64, (uint64_t)NH * SK * 3, 1, 128, 0, 16, 48, 1, CU_TENSOR_MAP_SWIZZLE_NONE);
    make_map(enc, &maps.kh, d_in[1], 2, 64, (uint64_t)NH * SK * 3, 1, 128, 0, 64, 24, 1, CU_TENSOR_MAP_SWIZZLE_128B);
    maps.kp = d_in[1];
    maps.vp = d_in[2];
    maps.scr = scr;
    maps.zero = 0;
    const uint32_t rt[8] = {0x2EE0, 0x35E0, 0x2EE0, 0x35E0, 0x3EE0, 0x35E0, 0x3EE0, 0x35E0};
    for (int i = 0; i < 8; i++) maps.rt[i] = rt[i];
    decode_kernel<<<NCTA, NT, SM_TOTAL, cudaStreamPerThread>>>(maps, (const __nv_bfloat16*)d_in[0], (__nv_bfloat16*)d_out);
}
```

```cpp
#include <cuda_runtime.h>
#include <cuda_bf16.h>
#include <cuda.h>
#include <stdint.h>
#include <math.h>

namespace {

constexpr int DM = 640;
constexpr int NH = 32;
constexpr int DH = 192;
constexpr int SK = 32768;
constexpr int WIN = 4096;
constexpr int FF = 1536;
constexpr int NCTA = 128;
constexpr int NT = 256;
constexpr int TILE = 6144;
constexpr int TS = 48;
constexpr int NG = 64;
constexpr int DN0 = 64;
constexpr int NDN = 40;

constexpr uint32_t SB = 1024;
constexpr uint32_t SM_RING = SB;
constexpr uint32_t SM_B = SM_RING + 8 * 2 * TILE;
constexpr uint32_t SM_Q = SM_B + 61440;
constexpr uint32_t SM_XS = SM_Q + 61440;
constexpr uint32_t SM_R = SM_XS + 1280;
constexpr uint32_t SM_ST = SM_R + 4096;
constexpr uint32_t SM_QS = SM_R + 6272;
constexpr uint32_t SM_OS = SM_QS + 384;
constexpr uint32_t SM_CS = SM_OS + 384;
constexpr uint32_t SM_BAR = SM_CS + 768;
constexpr uint32_t SM_XBAR = SM_BAR + 24 * 8;
constexpr uint32_t SM_MISC = SM_XBAR + 8 * 8;
constexpr uint32_t SM_ONE = SM_MISC + 32;
constexpr uint32_t SM_ZERO = SM_ONE + 160;
constexpr uint32_t SM_KX = SM_ZERO + 160;
constexpr uint32_t SM_TOTAL = SM_KX + 8 * 96 - SB;
constexpr int NEXC = 16;
static_assert(SM_TOTAL <= 232448, "shared memory");
constexpr uint32_t QBAR = SM_BAR + 16 * 8, FBAR = QBAR + 8, WBAR = QBAR + 16, QRDY = QBAR + 56;

constexpr unsigned long long POL_EF = 0x12F0000000000000ull;
constexpr unsigned long long POL_EN = 0x1000000000000000ull;

constexpr int L1R = 3;
constexpr int DNTH = 21;
constexpr int NPRE = 8;
constexpr int SPIN_CAP = 1 << 19;
constexpr uint32_t ONES = 0x3F803F80u;
#define AFTER(x) ((x) & maps.zero)
#define ALL6(a, n) (a[n][0] | a[n + 1][0] | a[n + 2][0] | a[n + 3][0] | a[n + 4][0] | a[n + 5][0])
#define ROW0(w) ((h * SK + (SK - WIN) + c * 1024 + (w) * 128) * 3)

struct Scratch {
    uint4 qx[NCTA * 48];
    uint4 qc[NCTA * 48];
    uint4 cx[NCTA * 56];
    uint4 acc[2][256];
    uint4 ay[256];
    uint4 pad0[256];
    uint4 ah[NG * 8];
    uint2 mx[NH * 32];
    uint32_t ticket[32];
};
__device__ __align__(4096) Scratch g_scr;
struct Maps { CUtensorMap k, v, wq, wo, w1, w3, w2, ks, vs, kh; const void *kp, *vp; Scratch* scr; uint32_t rt[8], zero; };

__device__ __forceinline__ uint32_t smem_u32(const void* p) { return (uint32_t)__cvta_generic_to_shared(p); }
__device__ __forceinline__ void mbar_init(uint32_t bar, uint32_t cnt) {
    asm volatile("mbarrier.init.shared::cta.b64 [%0], %1;" ::"r"(bar), "r"(cnt) : "memory");
}
__device__ __forceinline__ void mbar_expect_tx(uint32_t bar, uint32_t bytes) {
    asm volatile("mbarrier.arrive.expect_tx.shared::cta.b64 _, [%0], %1;" ::"r"(bar), "r"(bytes) : "memory");
}
__device__ __forceinline__ bool mbar_test(uint32_t bar, uint32_t parity) {
    uint32_t done;
    asm volatile("{\n.reg .pred p;\nmbarrier.try_wait.parity.shared::cta.b64 p, [%1], %2;\nselp.u32 %0, 1, 0, p;\n}"
                 : "=r"(done) : "r"(bar), "r"(parity) : "memory");
    return done;
}
__device__ __forceinline__ void mbar_wait(uint32_t bar, uint32_t parity) {
    asm volatile("{\n.reg .pred p;\n.reg .u32 n;\nmov.u32 n, 0;\n"
                 "W: mbarrier.try_wait.parity.shared::cta.b64 p, [%0], %1;\n@p bra D;\n"
                 "add.u32 n, n, 1;\nsetp.lt.u32 p, n, %2;\n@p bra W;\nD:\n}" ::"r"(bar), "r"(parity), "n"(SPIN_CAP) : "memory");
}
__device__ __forceinline__ void tma2d(uint32_t dst, const CUtensorMap* map, int c0, int c1, uint32_t bar, unsigned long long pol) {
    asm volatile("cp.async.bulk.tensor.2d.shared::cluster.global.mbarrier::complete_tx::bytes.L2::cache_hint [%0], [%1, {%3, %4}], [%2], %5;"
                 ::"r"(dst), "l"(map), "r"(bar), "r"(c0), "r"(c1), "l"(pol) : "memory");
}
__device__ __forceinline__ void tma3d(uint32_t dst, const CUtensorMap* map, int c0, int c1, int c2, uint32_t bar, unsigned long long pol) {
    asm volatile("cp.async.bulk.tensor.3d.shared::cluster.global.mbarrier::complete_tx::bytes.L2::cache_hint [%0], [%1, {%3, %4, %5}], [%2], %6;"
                 ::"r"(dst), "l"(map), "r"(bar), "r"(c0), "r"(c1), "r"(c2), "l"(pol) : "memory");
}
__device__ __forceinline__ void tma5d(uint32_t dst, const CUtensorMap* map, int c2, int c3, uint32_t bar, unsigned long long pol) {
    asm volatile("cp.async.bulk.tensor.5d.shared::cluster.global.mbarrier::complete_tx::bytes.L2::cache_hint [%0], [%1, {0, 0, %3, %4, 0}], [%2], %5;"
                 ::"r"(dst), "l"(map), "r"(bar), "r"(c2), "r"(c3), "l"(pol) : "memory");
}
__device__ __forceinline__ void tile_load(uint32_t dst, const CUtensorMap* map, int row, uint32_t bar) {
    asm volatile("{\n.reg .pred p;\nelect.sync _|p, 0xffffffff;\n"
                 "@p mbarrier.arrive.expect_tx.shared::cta.b64 _, [%2], 6144;\n"
                 "@p cp.async.bulk.tensor.2d.shared::cluster.global.mbarrier::complete_tx::bytes.L2::cache_hint [%0], [%1, {0, %3}], [%2], %4;\n}"
                 ::"r"(dst), "l"(map), "r"(bar), "r"(row), "l"(POL_EF) : "memory");
}
__device__ __forceinline__ void half_load(uint32_t dst, const CUtensorMap* map, int row, uint32_t bar, bool first) {
    if (first) asm volatile("{\n.reg .pred p;\nelect.sync _|p, 0xffffffff;\n@p mbarrier.arrive.expect_tx.shared::cta.b64 _, [%0], 6144;\n}" ::"r"(bar) : "memory");
    asm volatile("{\n.reg .pred p;\nelect.sync _|p, 0xffffffff;\n"
                 "@p cp.async.bulk.tensor.2d.shared::cluster.global.mbarrier::complete_tx::bytes.L2::cache_hint [%0], [%1, {0, %3}], [%2], %4;\n}"
                 ::"r"(dst), "l"(map), "r"(bar), "r"(row), "l"(POL_EF) : "memory");
}
__device__ __forceinline__ void tile_keep(const CUtensorMap* map, int row) {
    asm volatile("{\n.reg .pred p;\nelect.sync _|p, 0xffffffff;\n"
                 "@p cp.async.bulk.prefetch.tensor.2d.L2.global.L2::cache_hint [%0, {0, %1}], %2;\n}"
                 ::"l"(map), "r"(row), "l"(POL_EN) : "memory");
}
__device__ __forceinline__ void tile_load_l1(uint32_t dst, const void* base, int row, uint32_t bar, int lane) {
    const char* g = static_cast<const char*>(base) + (size_t)row * 128 + lane * 16;
    const uint32_t s0 = dst + (lane >> 3) * 128 + (((lane & 7) ^ (lane >> 3)) << 4), s1 = s0 ^ 64;
#pragma unroll
    for (int k = 0; k < 12; k++)
        asm volatile("cp.async.ca.shared.global.L2::cache_hint [%0], [%1], 16, %2;" ::"r"(((k & 1) ? s1 : s0) + k * 512), "l"(g + k * 512), "l"(POL_EF) : "memory");
    asm volatile("cp.async.mbarrier.arrive.shared::cta.b64 [%0];" ::"r"(bar) : "memory");
    __syncwarp();
    if (lane == 0) asm volatile("mbarrier.arrive.shared::cta.b64 _, [%0];" ::"r"(bar) : "memory");
}
__device__ __forceinline__ bool elect_one() {
    uint32_t p;
    asm volatile("{\n.reg .pred p;\nelect.sync _|p, 0xffffffff;\nselp.u32 %0, 1, 0, p;\n}" : "=r"(p));
    return p;
}
__device__ __forceinline__ void delay(uint32_t clocks) {
    uint32_t t0, t1;
    asm volatile("mov.u32 %0, %%clock;" : "=r"(t0));
    do asm volatile("mov.u32 %0, %%clock;" : "=r"(t1)); while (t1 - t0 < clocks);
}
__device__ __forceinline__ void lds128(uint32_t addr, uint32_t& a, uint32_t& b, uint32_t& c, uint32_t& d) {
    asm volatile("ld.shared.v4.u32 {%0,%1,%2,%3}, [%4];" : "=r"(a), "=r"(b), "=r"(c), "=r"(d) : "r"(addr) : "memory");
}
__device__ __forceinline__ void lds64(uint32_t addr, uint32_t& a, uint32_t& b) {
    asm volatile("ld.shared.v2.u32 {%0,%1}, [%2];" : "=r"(a), "=r"(b) : "r"(addr) : "memory");
}
__device__ __forceinline__ void ldsm4t(uint32_t addr, uint32_t (&a)[4]) {
    asm volatile("ldmatrix.sync.aligned.m8n8.x4.trans.shared.b16 {%0,%1,%2,%3}, [%4];" : "=r"(a[0]), "=r"(a[1]), "=r"(a[2]), "=r"(a[3]) : "r"(addr) : "memory");
}
__device__ __forceinline__ void mma16816(float (&c)[4], uint32_t a0, uint32_t a1, uint32_t a2, uint32_t a3, uint32_t b0, uint32_t b1) {
    asm("mma.sync.aligned.m16n8k16.row.col.f32.bf16.bf16.f32 {%0,%1,%2,%3}, {%4,%5,%6,%7}, {%8,%9}, {%0,%1,%2,%3};"
        : "+f"(c[0]), "+f"(c[1]), "+f"(c[2]), "+f"(c[3]) : "r"(a0), "r"(a1), "r"(a2), "r"(a3), "r"(b0), "r"(b1));
}
__device__ __forceinline__ void mma16816v(float (&c)[4], uint32_t a0, uint32_t a1, uint32_t a2, uint32_t a3, uint32_t b0, uint32_t b1) {
    asm volatile("mma.sync.aligned.m16n8k16.row.col.f32.bf16.bf16.f32 {%0,%1,%2,%3}, {%4,%5,%6,%7}, {%8,%9}, {%0,%1,%2,%3};"
        : "+f"(c[0]), "+f"(c[1]), "+f"(c[2]), "+f"(c[3]) : "r"(a0), "r"(a1), "r"(a2), "r"(a3), "r"(b0), "r"(b1));
}
__device__ __forceinline__ int xpos(int w) {
    const int seg = w / 40, r = w - 40 * seg;
    return 40 * seg + (r < 32 ? (r & 16) + 4 * (r & 3) + ((r >> 2) & 3) : 32 + 2 * (r & 3) + ((r >> 2) & 1));
}
__device__ __forceinline__ void st_pkt(uint4* p, uint32_t a, uint32_t b, uint32_t c, uint32_t d) {
    asm volatile("{\n.reg .b128 t;\n.reg .b64 lo, hi;\nmov.b64 lo, {%1,%2};\nmov.b64 hi, {%3,%4};\nmov.b128 t, {lo,hi};\nst.relaxed.gpu.global.b128 [%0], t;\n}"
                 ::"l"(p), "r"(a), "r"(b), "r"(c), "r"(d) : "memory");
}
__device__ __forceinline__ void st_pktf(uint4* p, float a, float b, float c, float d, uint32_t bit) {
    st_pkt(p, __float_as_uint(a), __float_as_uint(b), __float_as_uint(c), (__float_as_uint(d) & ~1u) | bit);
}
__device__ __forceinline__ void red_pkt(uint4* p, float a, float b, float c) {
    asm volatile("red.relaxed.gpu.global.add.v4.f32 [%0], {%1,%2,%3,%4};" ::"l"(p), "f"(a), "f"(b), "f"(c), "f"(1.0f) : "memory");
}
__device__ __forceinline__ uint4 ld_pkt(const uint4* p) {
    uint4 v;
    asm volatile("{\n.reg .b128 t;\n.reg .b64 lo, hi;\nld.relaxed.gpu.global.b128 t, [%4];\nmov.b128 {lo,hi}, t;\nmov.b64 {%0,%1}, lo;\nmov.b64 {%2,%3}, hi;\n}"
                 : "=r"(v.x), "=r"(v.y), "=r"(v.z), "=r"(v.w) : "l"(p) : "memory");
    return v;
}
__device__ __forceinline__ uint2 ld_pkt2(const uint2* p) {
    unsigned long long v;
    asm volatile("ld.relaxed.gpu.global.b64 %0, [%1];" : "=l"(v) : "l"(p) : "memory");
    return make_uint2((uint32_t)v, (uint32_t)(v >> 32));
}
__device__ __forceinline__ void st_pkt2(uint2* p, uint32_t a, uint32_t b) {
    asm volatile("st.relaxed.gpu.global.b64 [%0], %1;" ::"l"(p), "l"((unsigned long long)a | ((unsigned long long)b << 32)) : "memory");
}
__device__ __forceinline__ float ex2(float x) { float y; asm("ex2.approx.ftz.f32 %0, %1;" : "=f"(y) : "f"(x)); return y; }
__device__ __forceinline__ float rcp(float x) { float y; asm("rcp.approx.ftz.f32 %0, %1;" : "=f"(y) : "f"(x)); return y; }
__device__ __forceinline__ uint32_t pack2(float lo, float hi) {
    uint32_t r; asm("cvt.rn.bf16x2.f32 %0, %1, %2;" : "=r"(r) : "f"(hi), "f"(lo)); return r;
}
__device__ __forceinline__ float bf_lo(uint32_t w) { return __uint_as_float(w << 16); }
__device__ __forceinline__ float bf_hi(uint32_t w) { return __uint_as_float(w & 0xffff0000u); }
__device__ __forceinline__ float bfr(float x) { return bf_lo(pack2(x, 0.f)); }
__device__ __forceinline__ float f_(uint32_t u) { return __uint_as_float(u); }

__device__ __forceinline__ uint32_t add2(uint32_t a, uint32_t b) { uint32_t r; asm("add.rn.bf16x2 %0, %1, %2;" : "=r"(r) : "r"(a), "r"(b)); return r; }
__device__ __forceinline__ uint32_t mul2(uint32_t a, uint32_t b) { uint32_t r; asm("mul.rn.bf16x2 %0, %1, %2;" : "=r"(r) : "r"(a), "r"(b)); return r; }
__device__ __forceinline__ uint32_t f2key(float f) { const uint32_t u = __float_as_uint(f); return u ^ ((uint32_t)((int)u >> 31) | 0x80000000u); }
__device__ __forceinline__ float key2f(uint32_t k) { return __uint_as_float(k ^ ((uint32_t)((int)~k >> 31) | 0x80000000u)); }
__device__ __forceinline__ float4 lds128f(uint32_t a) {
    float4 v; asm volatile("ld.shared.v4.f32 {%0,%1,%2,%3}, [%4];" : "=f"(v.x), "=f"(v.y), "=f"(v.z), "=f"(v.w) : "r"(a) : "memory"); return v;
}
__device__ __forceinline__ float2 lds64f(uint32_t a) { float2 v; asm volatile("ld.shared.v2.f32 {%0,%1}, [%2];" : "=f"(v.x), "=f"(v.y) : "r"(a) : "memory"); return v; }
__device__ __forceinline__ uint32_t lds32(uint32_t a) { uint32_t v; asm volatile("ld.shared.u32 %0, [%1];" : "=r"(v) : "r"(a) : "memory"); return v; }
__device__ __forceinline__ uint32_t lds16(uint32_t a) { uint32_t v; asm volatile("ld.shared.u16 %0, [%1];" : "=r"(v) : "r"(a) : "memory"); return v; }
__device__ __forceinline__ void sts16(uint32_t a, uint32_t v) { asm volatile("st.shared.u16 [%0], %1;" ::"r"(a), "r"(v) : "memory"); }
__device__ __forceinline__ void sts32(uint32_t a, uint32_t v) { asm volatile("st.shared.u32 [%0], %1;" ::"r"(a), "r"(v) : "memory"); }
__device__ __forceinline__ void sts32(uint32_t a, float v) { asm volatile("st.shared.f32 [%0], %1;" ::"r"(a), "f"(v) : "memory"); }
__device__ __forceinline__ void sts128(uint32_t a, float x, float y, float z, float w) {
    asm volatile("st.shared.v4.f32 [%0], {%1,%2,%3,%4};" ::"r"(a), "f"(x), "f"(y), "f"(z), "f"(w) : "memory");
}
template <int N> struct IC { static constexpr int value = N; };
__device__ __forceinline__ int opq(int x) { asm volatile("" : "+r"(x)); return x; }
__device__ __forceinline__ uint32_t opq(uint32_t x) { asm volatile("" : "+r"(x)); return x; }
template <typename T> __device__ __forceinline__ T* opq(T* p) { asm volatile("" : "+l"(p)); return p; }

__device__ __forceinline__ void ln_finish(float s1, float s2, float& mean, float& inv) {
    const float md = s1 * (1.0f / DM);
    const float var = fmaxf(s2 * (1.0f / DM) - md * md, 0.f);
    mean = bfr(md);
    asm("rsqrt.approx.ftz.f32 %0, %1;" : "=f"(inv) : "f"(var + 1e-5f));
}
__device__ __forceinline__ void ln_stats(float& mean, float& inv) {
    const float4 a = lds128f(SM_ST), b = lds128f(SM_ST + 16), c = lds128f(SM_ST + 32), d = lds128f(SM_ST + 48);
    ln_finish(((a.y + a.w) + (b.y + b.w)) + ((c.y + c.w) + (d.y + d.w)), ((a.x + a.z) + (b.x + b.z)) + ((c.x + c.z) + (d.x + d.z)), mean, inv);
}
template <int SK, bool GRAM, typename AddrF>
__device__ __forceinline__ void gemv15(float (&cc)[3][4], float (&gr)[4], uint32_t (&pre)[9][4], AddrF ad, uint32_t px, uint32_t px2) {
    uint32_t x0[4], x1[4];
    lds128(px, x0[0], x0[1], x0[2], x0[3]);
    lds128(px + 64, x1[0], x1[1], x1[2], x1[3]);
    gr[0] = gr[1] = gr[2] = gr[3] = 0.f;
#pragma unroll
    for (int i = 0; i < 3; i++) {
        cc[i][0] = cc[i][1] = cc[i][2] = cc[i][3] = 0.f;
        mma16816v(cc[i], pre[i][0], pre[i][1], pre[i][2], pre[i][3], x0[0], x0[1]);
    }
#pragma unroll
    for (int i = 0; i < 3; i++) ldsm4t(ad(i) + 3 * SK, pre[i]);
    if (GRAM) mma16816v(gr, x0[0], 0u, x0[1], 0u, x0[0], x0[1]);
#pragma unroll
    for (int i = 0; i < 3; i++) mma16816v(cc[i], pre[3 + i][0], pre[3 + i][1], pre[3 + i][2], pre[3 + i][3], x0[2], x0[3]);
#pragma unroll
    for (int i = 0; i < 3; i++) ldsm4t(ad(i) + 4 * SK, pre[3 + i]);
    lds64(px2, x0[0], x0[1]);
    if (GRAM) mma16816v(gr, x0[2], 0u, x0[3], 0u, x0[2], x0[3]);
#pragma unroll
    for (int i = 0; i < 3; i++) mma16816v(cc[i], pre[6 + i][0], pre[6 + i][1], pre[6 + i][2], pre[6 + i][3], x1[0], x1[1]);
    if (GRAM) mma16816v(gr, x1[0], 0u, x1[1], 0u, x1[0], x1[1]);
#pragma unroll
    for (int i = 0; i < 3; i++) mma16816v(cc[i], pre[i][0], pre[i][1], pre[i][2], pre[i][3], x1[2], x1[3]);
    if (GRAM) mma16816v(gr, x1[2], 0u, x1[3], 0u, x1[2], x1[3]);
    if (GRAM) mma16816v(gr, x0[0], 0u, x0[1], 0u, x0[0], x0[1]);
#pragma unroll
    for (int i = 0; i < 3; i++) mma16816v(cc[i], pre[3 + i][0], pre[3 + i][1], pre[3 + i][2], pre[3 + i][3], x0[0], x0[1]);
}
__device__ __forceinline__ void gemv15r(float (&cc)[3][4], float (&gr)[4], const uint32_t (&pre)[9][4], const uint32_t (&ext)[45][4], uint32_t px, uint32_t px2) {
    uint32_t x0[4], x1[4], x2[2];
    lds128(px, x0[0], x0[1], x0[2], x0[3]);
    lds128(px + 64, x1[0], x1[1], x1[2], x1[3]);
    lds64(px2, x2[0], x2[1]);
    gr[0] = gr[1] = gr[2] = gr[3] = 0.f;
#pragma unroll
    for (int ks = 0; ks < 5; ks++) {
        const uint32_t b0 = ks < 2 ? x0[2 * (ks & 1)] : ks < 4 ? x1[2 * (ks & 1)] : x2[0], b1 = ks < 2 ? x0[2 * (ks & 1) + 1] : ks < 4 ? x1[2 * (ks & 1) + 1] : x2[1];
        mma16816v(gr, b0, 0u, b1, 0u, b0, b1);
#pragma unroll
        for (int i = 0; i < 3; i++) {
            if (ks == 0) cc[i][0] = cc[i][1] = cc[i][2] = cc[i][3] = 0.f;
            const uint32_t (&f)[4] = ks < 3 ? pre[ks < 3 ? 3 * ks + i : 0] : ext[ks < 3 ? 0 : 3 * (ks - 3) + i];
            mma16816v(cc[i], f[0], f[1], f[2], f[3], b0, b1);
        }
    }
}

__device__ __forceinline__ void load_ffn(const Maps& maps, int b, uint32_t dst, uint32_t bar) {
    const bool gu = b < NG;
    mbar_expect_tx(bar, gu ? 61440 : 49152);
    tma3d(dst, gu ? (b < NG / 2 ? &maps.w1 : &maps.w3) : &maps.w2, gu ? 48 * (b & (NG / 2 - 1)) : 16 * (b - DN0), 0, 0, bar, POL_EF);
}

__device__ __forceinline__ void load_wo(const Maps& maps, uint32_t dst, int h, int c, uint32_t bar, int nbox) {
#pragma unroll 1
    for (int i = 0; i < nbox; i++) {
        mbar_expect_tx(bar + 8 * i, 12288);
        tma3d(dst + i * 12288, &maps.wo, 0, h * DH, 5 * c + i, bar + 8 * i, POL_EF);
    }
}

__global__ void __launch_bounds__(NT, 1)
decode_kernel(const __grid_constant__ Maps maps, const __nv_bfloat16* __restrict__ x_in, __nv_bfloat16* __restrict__ out) {
    extern __shared__ __align__(1024) unsigned char smem[];
    const int tid = threadIdx.x;
    const int wu = __shfl_sync(0xffffffffu, tid >> 5, 0);
    const int b = blockIdx.x, h = b >> 2, c = b & 3;
    if (smem_u32(smem) != SB) return;

    {
        const int warp = tid >> 5, lane = tid & 31;
        const uint32_t rbar = SM_BAR + warp * 16;
        if (lane == 0) {
            if (warp == 0) {
                mbar_init(QBAR, 1);
                asm volatile("fence.mbarrier_init.release.cluster;" ::: "memory");
                mbar_expect_tx(QBAR, 61440);
                tma5d(SM_Q, &maps.wq, 3 * h, 2 * c, QBAR, POL_EF);
            }
            mbar_init(rbar, 1); mbar_init(rbar + 8, 1); mbar_init(SM_XBAR + warp * 8, 1);
            mbar_init(FBAR + 8 * max(warp - 1, 0), warp == 7 ? 2 : 1);
            asm volatile("fence.mbarrier_init.release.cluster;" ::: "memory");
            if (warp >= 1 && warp < 7) {
                const CUtensorMap* mp = warp == 1 ? &maps.k : warp == 2 ? &maps.v : warp == 3 ? &maps.wo : warp == 4 ? &maps.w1 : warp == 5 ? &maps.w3 : &maps.w2;
                asm volatile("prefetch.tensormap [%0];" ::"l"(mp) : "memory");
            }
        }
        if (tid == 96) sts32(SM_MISC + 8, 0u);
        if (lane < 2) sts32(SM_KX + warp * 96 + 4 * lane, 0u);
        if (tid >= 128 && tid < 148) {
            const float v = f_(tid < 138 ? ONES : 0u);
            sts128(SM_ONE + 16 * (tid - 128), v, v, v, v);
        }
        if (b == 0 && tid == 255) asm volatile("st.relaxed.gpu.global.u32 [%0], %1;" ::"l"(maps.scr->ticket), "r"(0) : "memory");
        if (tid < 4) st_pkt(reinterpret_cast<uint4*>(&maps.scr->mx[h * 32 + c * 8]) + tid, 0, 0, 0, 0);
        if (tid >= 64 && tid < 66 && b < 108) st_pkt(&maps.scr->acc[1][(2 * b + tid - 64)], 0, 0, 0, 0);
        __syncthreads();
        if (lane == 0) {
            const int row = ROW0(warp);
            mbar_expect_tx(rbar, TILE);
            tma2d(SM_RING + warp * 2 * TILE, &maps.k, 0, row, rbar, POL_EF);
            mbar_expect_tx(rbar + 8, TILE);
            tma2d(SM_RING + (warp * 2 + 1) * TILE, &maps.k, 0, row + TS, rbar + 8, POL_EF);
        }
    }

    uint32_t kr[45][4];
#define KR(n) kr[(n) >> 2][(n) & 3]
    const float SC = 0.07216878364870322f * 1.4426950408889634f;
    int role = 0;
    uint32_t wk[3][4];

#pragma unroll 1
    for (int layer = 0; layer < 2; layer++) {
        const uint32_t tag = layer + 1, tbit = layer ^ 1;
        uint2 xv = make_uint2(0u, 0u);
        uint32_t qo;
        {
            const int tl = opq(tid), warp = tl >> 5, lane = tl & 31, g = lane >> 2, t = lane & 3, mat = lane >> 3, r8 = lane & 7;
            const int kh = warp >> 2, mg = warp & 3;
            const uint32_t aq = SM_Q + kh * TILE + ((mat >> 1) * 8 + r8) * 128 + (((2 * mg + (mat & 1)) ^ r8) << 4);
            if (layer == 0 && tl < 160) xv = reinterpret_cast<const uint2*>(x_in)[tl];
            mbar_wait(QBAR, 0);
            uint32_t pre[9][4];
#pragma unroll
            for (int n = 0; n < 9; n++) ldsm4t(aq + (n % 3) * 2048 + (n / 3) * 2 * TILE, pre[n]);
            const bool dn = role >= DN0 && role < DN0 + NDN;
            if (layer == 1 && !dn) {
                sts32(SM_MISC + 12, ALL6(pre, 0) | ALL6(pre, 3));
                __syncthreads();
                delay(role >= DN0 + NDN ? 1000 : 0);
                if (wu == 7) {
#pragma unroll 1
                    for (int w = 0; w < 6; w++) tile_load(SM_Q + w * TILE, &maps.k, ROW0(w) + 5 * TS, SM_XBAR + w * 8);
                }
            }
            const uint32_t pm = opq(g == 1 ? SM_ONE : SM_XS + 160 * (2 * c + kh) + 16 * t);
            const uint32_t pm2 = opq(pm + 128 - (g == 1 ? 0 : 8 * t));
            const uint32_t dq = opq(SM_R + 768 * kh + 4 * (16 * mg + g));
            qo = opq(16u * (b * 48 + (tl & 63) + (tl >= 64 ? NCTA * 48 : 0)));
            if (tl < 160) {
                const uint32_t xa0 = opq(SM_XS + 4 * xpos(2 * tl));
                const bool xl = tl % 20 < 16;
                if (layer == 1) {
                    const uint4* px = opq(&maps.scr->ay[tl]);
                    uint4 v;
                    int it = 0;
                    bool more;
                    do { v = ld_pkt(px); more = ++it < SPIN_CAP; } while (!__all_sync(0xffffffffu, (v.y & v.w) == 1) && more);
                    xv = make_uint2(v.x, v.z);
                }
                sts32(xa0, xv.x);
                if (xl) sts32(xa0 + 16, xv.y); else sts32(xa0 + 8, xv.y);
            }
            if (layer == 1 && dn) sts32(SM_MISC + 12, ALL6(pre, 0) | ALL6(pre, 3));
            __syncthreads();
            if (layer == 1 && dn && wu < 6) tile_load(SM_Q + wu * TILE, &maps.k, ROW0(wu) + 5 * TS, SM_XBAR + wu * 8);
            float cc[3][4], gr[4];
            gemv15<2 * TILE, false>(cc, gr, pre, [&](int i) { return aq + i * 2048; }, pm, pm2);
            if (t == 0) {
#pragma unroll
                for (int i = 0; i < 3; i++) { sts32(dq + 256 * i, cc[i][0]); sts32(dq + 256 * i + 32, cc[i][2]); }
                if (layer == 0) {
#pragma unroll
                    for (int i = 0; i < 3; i++) { sts32(dq + 256 * i + 1536, cc[i][1]); sts32(dq + 256 * i + 1568, cc[i][3]); }
                }
            }
        }
        {
            const int tl = opq(tid), j = tl & 63;
            const bool snd = j < 48 && (tl < 64 || (tl < 128 && layer == 0));
            const uint32_t fa = opq(SM_R + 16 * tl + (tl >= 64 ? 512 : 0));
            uint4* pq = reinterpret_cast<uint4*>(reinterpret_cast<char*>(maps.scr->qx) + qo);
            __syncthreads();
            if (snd) {
                const float4 u = lds128f(fa), v = lds128f(fa + 768);
                st_pktf(pq, u.x + v.x, u.y + v.y, u.z + v.z, u.w + v.w, tbit);
            }
            if (layer == 1 && wu >= 5) {
                delay(300);
                if (wu >= 6) tile_load(SM_Q + wu * TILE, &maps.k, ROW0(wu) + 5 * TS, SM_XBAR + wu * 8);
                else if (role < NG && elect_one()) {
                    mbar_expect_tx(WBAR + 32, 12288);
                    tma3d(SM_Q + 4 * 12288, &maps.wo, 0, h * DH, 5 * c + 4, WBAR + 32, POL_EF);
                }
            }
            if (layer == 1 && tl >= 192 && tl < 194 && b < 108) st_pkt(&maps.scr->acc[0][(2 * b + tl - 192)], 0, 0, 0, 0);
        }

        float sc0 = -INFINITY, sc1 = -INFINITY, sc2 = 0.f, sc3 = 0.f, mw;
        uint32_t pk0, pk1;
        float acc[3][4];
        {
            const uint32_t ring = SM_RING + wu * 2 * TILE, rb = SM_BAR + wu * 16;
            const uint32_t xtile = SM_Q + wu * TILE, xb = SM_XBAR + wu * 8;
            const int row0 = ROW0(wu);
            const uint32_t bt = SM_B + wu * TILE;
            auto issue1 = [&](int n, uint32_t dep, bool vph) {
                const CUtensorMap* mp = n < 8 ? &maps.k : &maps.v;
                const int row = row0 + ((n + (n >= 8 ? 2 : 0)) & 7) * TS;
                if (vph && wu < L1R && n == 12 - (wu & 1)) {
                    tile_load_l1(ring + (n & 1) * TILE, maps.vp, row, rb + (n & 1) * 8, opq(tid) & 31);
                    return;
                }
                const int k = vph || n >= 6 ? n & 1 : n >= 3 ? n - 3 : n;
                tile_load(k == 2 ? bt : ring + k * TILE, mp, row + dep, k == 2 ? xb : rb + k * 8);
                if ((maps.rt[wu] >> n) & 1) tile_keep(n < 8 ? &maps.ks : &maps.vs, row);
            };
            auto refill1 = [&](int s, uint32_t dep, bool vph = false) { issue1(s + 2, dep, vph); };
#define K_OFF(i) ((uint32_t)((3 * ((g >> 1) + 4 * (g & 1)) + ((i) >> 1)) * 128 + ((t ^ ((3 * ((g >> 1) + 4 * (g & 1)) + ((i) >> 1)) & 7) ^ (((i) & 1) << 2)) << 4)))
#define V_OFF(i) ((uint32_t)((6 * t + (i)) * 128 + ((g ^ ((6 * t + (i)) & 7)) << 4)))
#define LANE_IDS const int tl = opq(tid), lane = tl & 31, g = lane >> 2, t = lane & 3; (void)tl; (void)lane; (void)g; (void)t;
            const uint32_t kx = SM_KX + wu * 96;
#pragma unroll 1
            for (int s = layer ? 5 : 0; s < 5 + layer; s++) {
                if (s < 5) {
                    LANE_IDS
                    const int k = s >= 3 ? s - 3 : s;
                    mbar_wait(k == 2 ? xb : rb + k * 8, s >= 3);
                    refill1(s, 0);
                    const uint32_t tile = k == 2 ? bt : ring + k * TILE;
                    uint32_t mx = 0u, mn = 0xffffffffu, mn2 = 0xffffffffu;
#pragma unroll
                    for (int q = 0; q < 12; q++) {
                        uint32_t a0, a1, a2, a3;
                        lds128(tile + K_OFF(q % 6) + (q / 6) * 3072, a0, a1, a2, a3);
                        a0 &= 0x7fff7fffu; a1 &= 0x7fff7fffu; a2 &= 0x7fff7fffu; a3 &= 0x7fff7fffu;
                        mx = __vimax3_u16x2(__vimax3_u16x2(mx, a0, a1), a2, a3);
                        mn = __viaddmin_u16x2(a0, 0xffffffffu, __viaddmin_u16x2(a1, 0xffffffffu, mn));
                        mn2 = __viaddmin_u16x2(a2, 0xffffffffu, __viaddmin_u16x2(a3, 0xffffffffu, mn2));
                    }
                    mn = __vminu2(mn, mn2);
                    const uint32_t emax = __reduce_max_sync(0xffffffffu, max(mx & 0xffffu, mx >> 16)) >> 7;
                    const uint32_t base = (max(emax, 16u) - 15u) << 7, lim = base + 0x7fu;
                    bool raw = emax < 80u || emax > 190u;
                    uint32_t fl = __ballot_sync(0xffffffffu, min(mn & 0xffffu, mn >> 16) < lim);
                    if (!raw && fl) {
                        const uint32_t n0 = lds32(kx);
                        __syncwarp();
#pragma unroll 1
                        for (; fl; fl &= fl - 1) {
                            const int g = (__ffs(fl) - 1) >> 2, t = (__ffs(fl) - 1) & 3, q = min(lane, 23) >> 1, i = q >= 6 ? q - 6 : q;
                            const uint32_t a = tile + K_OFF(i) + (q >= 6 ? 3072 : 0) + 8 * (lane & 1);
                            uint32_t w0, w1;
                            lds64(a, w0, w1);
#pragma unroll 1
                            for (int e = 0; e < 4; e++) {
                                const uint32_t x = __funnelshift_r(w0, w1, 16 * e) & 0xffffu;
                                if (e == 1) w0 = w1;
                                if ((x & 0x7fffu) - 1u < lim && lane < 24) {
                                    uint32_t n;
                                    asm volatile("atom.shared.add.u32 %0, [%1], 1;" : "=r"(n) : "r"(kx) : "memory");
                                    if (n < NEXC) sts32(kx + 32 + 4 * n, x | (2 * ((2 * t + (e >> 1)) * 12 + 2 * i + (lane & 1)) + (e & 1)) << 16 | (16 * (s & 4) + (q >= 6 ? 32 : 0) + 4 * g + (s & 3)) << 24);
                                    sts16(a + 2 * e, 0u);
                                }
                            }
                        }
                        __syncwarp();
                        raw = lds32(kx) > NEXC;
                        __syncwarp();
                        if (raw && lane == 0) sts32(kx, n0);
                    }
                    if (lane == 0) {
                        sts32(kx + 8 + 4 * s, (base + (31u << 7)) << 16);
                        if (raw) sts32(kx + 4, lds32(kx + 4) | 1u << s);
                    }
                    const uint32_t b2 = (0x10000u - base) * 0x10001u;
                    auto pack = [&](auto S) {
                        constexpr int n0 = 36 * decltype(S)::value;
#pragma unroll
                        for (int q = 0; q < 12; q++) {
                            uint32_t a0, a1, a2, a3;
                            lds128(tile + K_OFF(q % 6) + (q / 6) * 3072, a0, a1, a2, a3);
                            a0 = __viaddmax_s16x2(a0 & 0x7fff7fffu, b2, 0u) | (a0 & 0x80008000u); a1 = __viaddmax_s16x2(a1 & 0x7fff7fffu, b2, 0u) | (a1 & 0x80008000u);
                            a2 = __viaddmax_s16x2(a2 & 0x7fff7fffu, b2, 0u) | (a2 & 0x80008000u); a3 = __viaddmax_s16x2(a3 & 0x7fff7fffu, b2, 0u) | (a3 & 0x80008000u);
                            KR(n0 + 3 * q) = __byte_perm(a0, a1, 0x6420);
                            KR(n0 + 3 * q + 1) = __byte_perm(a2, a3, 0x6420);
                            const uint32_t ho = __byte_perm(a2, a3, 0x7531);
                            KR(n0 + 3 * q + 2) = __byte_perm(a0, a1, 0x7531) | __funnelshift_r(ho, ho, 4);
                        }
                    };
                    switch (s) {
                        case 0: pack(IC<0>()); break;
                        case 1: pack(IC<1>()); break;
                        case 2: pack(IC<2>()); break;
                        case 3: pack(IC<3>()); break;
                        default: pack(IC<4>()); break;
                    }
                    __syncwarp();
                }
                if (wu < 2 && (s == 3 || layer)) {
                    const int tc = min(opq(tid), 47);
                    const uint4* pq = opq(&maps.scr->qx[h * 4 * 48 + tc]);
                    uint4 v[4];
                    int it = 0;
                    bool more = true;
#pragma unroll
                    for (int k = 0; k < 4; k++) v[k] = ld_pkt(pq + 48 * k);
                    if (layer == 0) {
                        uint4 u[4];
                        do {
#pragma unroll
                            for (int k = 0; k < 4; k++) u[k] = ld_pkt(pq + NCTA * 48 + 48 * k);
                            more = ++it < SPIN_CAP;
                        } while (!__all_sync(0xffffffffu, u[0].w & u[1].w & u[2].w & u[3].w & 1) && more);
                        sts128(SM_CS + 16 * tc, (f_(u[0].x) + f_(u[1].x)) + (f_(u[2].x) + f_(u[3].x)), (f_(u[0].y) + f_(u[1].y)) + (f_(u[2].y) + f_(u[3].y)),
                               (f_(u[0].z) + f_(u[1].z)) + (f_(u[2].z) + f_(u[3].z)), (f_(u[0].w) + f_(u[1].w)) + (f_(u[2].w) + f_(u[3].w)));
                    }
                    float mean, inv;
                    {
                        const int lane = opq(tid) & 31;
                        uint32_t xw[10];
                        lds128(SM_XS + 16 * lane, xw[0], xw[1], xw[2], xw[3]);
                        lds128(SM_XS + 512 + 16 * lane, xw[4], xw[5], xw[6], xw[7]);
                        lds64(SM_XS + 1024 + 8 * lane, xw[8], xw[9]);
                        float s1 = 0.f, s2 = 0.f, s3 = 0.f, s4 = 0.f;
#pragma unroll
                        for (int i = 0; i < 10; i++) { const float e0 = bf_lo(xw[i]), e1 = bf_hi(xw[i]); s1 += e0; s3 += e1; s2 = fmaf(e0, e0, s2); s4 = fmaf(e1, e1, s4); }
                        s1 += s3; s2 += s4;
                        const bool lo = lane < 16;
                        float sv = (lo ? s1 : s2) + __shfl_xor_sync(0xffffffffu, lo ? s2 : s1, 16);
#pragma unroll
                        for (int o = 8; o > 0; o >>= 1) sv += __shfl_xor_sync(0xffffffffu, sv, o);
                        const float so = __shfl_xor_sync(0xffffffffu, sv, 16);
                        ln_finish(lo ? sv : so, lo ? so : sv, mean, inv);
                    }
                    const float4 cs = lds128f(SM_CS + 16 * tc);
                    mean *= -inv;
                    const float m0 = mean * cs.x, m1 = mean * cs.y, m2 = mean * cs.z, m3 = mean * cs.w;
                    const int w = 2 * tc;
                    const uint32_t qd = opq(SM_QS + 4 * (((w >> 2) & 3) * 24 + 2 * (w >> 4) + ((w >> 1) & 1)));
                    while (__any_sync(0xffffffffu, ((v[0].w ^ tbit) | (v[1].w ^ tbit) | (v[2].w ^ tbit) | (v[3].w ^ tbit)) & 1) && more) {
#pragma unroll
                        for (int k = 0; k < 4; k++) v[k] = ld_pkt(pq + 48 * k);
                        more = ++it < SPIN_CAP;
                    }
                    const float q0 = fmaf(inv, (f_(v[0].x) + f_(v[1].x)) + (f_(v[2].x) + f_(v[3].x)), m0), q1 = fmaf(inv, (f_(v[0].y) + f_(v[1].y)) + (f_(v[2].y) + f_(v[3].y)), m1);
                    const float q2 = fmaf(inv, (f_(v[0].z) + f_(v[1].z)) + (f_(v[2].z) + f_(v[3].z)), m2), q3 = fmaf(inv, (f_(v[0].w) + f_(v[1].w)) + (f_(v[2].w) + f_(v[3].w)), m3);
                    sts32(qd, pack2(q0, q1));
                    sts32(qd + 48, pack2(q2, q3));
                    __syncwarp();
                    if (elect_one()) asm volatile("mbarrier.arrive.shared::cta.b64 _, [%0];" ::"r"(QRDY) : "memory");
                }
            }
            uint32_t qa, ka[3];
            {
                LANE_IDS
                qa = opq(SM_QS + (2 * t + (g & 1)) * 48);
#pragma unroll
                for (int i = 0; i < 3; i++) ka[i] = opq(xtile + K_OFF(2 * i));
            }
            uint32_t f[6][4];
            if (layer == 1) {
                if (wu >= 2 && wu < 5) delay(150);
                mbar_wait(xb, 0);
            }
#pragma unroll
            for (int i = 0; i < 6; i++) lds128(ka[i >> 1] ^ ((i & 1) << 6), f[i][0], f[i][1], f[i][2], f[i][3]);
            if (layer == 1) {
                __syncwarp();
                half_load(xtile, &maps.kh, row0 + 6 * TS + AFTER(ALL6(f, 0)), xb, true);
            }
            mbar_wait(QRDY, layer);
            {
                uint32_t qf[12];
#pragma unroll
                for (int i = 0; i < 3; i++) lds128(qa + 16 * i, qf[4 * i], qf[4 * i + 1], qf[4 * i + 2], qf[4 * i + 3]);
                const int t = opq(tid) & 3;
                auto kr_scores = [&](auto TAU, float& sa, float& sb) {
                    constexpr int tau = decltype(TAU)::value;
                    float cc[2][4] = {{0.f, 0.f, 0.f, 0.f}, {0.f, 0.f, 0.f, 0.f}};
#pragma unroll
                    for (int n = 0; n < 12; n++) {
                        const int q = (n & 1) * 6 + (n >> 1), i = n >> 1;
                        const uint32_t l0 = KR(36 * tau + 3 * q), l1 = KR(36 * tau + 3 * q + 1), hh = KR(36 * tau + 3 * q + 2);
                        const uint32_t h0 = hh & 0x87878787u, h1 = __funnelshift_l(hh, hh, 4) & 0x87878787u;
                        mma16816v(cc[n & 1], __byte_perm(l0, h0, 0x5140), __byte_perm(l0, h0, 0x7362), __byte_perm(l1, h1, 0x5140), __byte_perm(l1, h1, 0x7362), qf[2 * i], qf[2 * i + 1]);
                    }
                    if (t == (tau & 3)) { sa = cc[0][0] + cc[0][3]; sb = cc[1][0] + cc[1][3]; }
                };
                auto stage_v = [&](auto S) {
                    constexpr int s = decltype(S)::value;
                    const int lane = opq(tid) & 31, g = lane >> 2, t = lane & 3;
#pragma unroll
                    for (int i = 0; i < 6; i++) {
                        const uint32_t a = ring + s * TILE + V_OFF(i);
                        lds128(a, kr[12 * s + i][0], kr[12 * s + i][1], kr[12 * s + i][2], kr[12 * s + i][3]);
                        lds128(a + 3072, kr[12 * s + 6 + i][0], kr[12 * s + 6 + i][1], kr[12 * s + 6 + i][2], kr[12 * s + 6 + i][3]);
                    }
                    __syncwarp();
                    tile_load(ring + s * TILE, s ? &maps.v : &maps.k, row0 + (s ? 2 : 7) * TS + AFTER(ALL6(kr, 12 * s) | ALL6(kr, 12 * s + 6)), rb + s * 8);
                };
                if (layer == 1) {
                    float cA[4] = {0.f, 0.f, 0.f, 0.f}, cB[4] = {0.f, 0.f, 0.f, 0.f};
#pragma unroll
                    for (int i = 0; i < 6; i++) {
                        mma16816v(cA, f[i][0], f[i][1], f[i][2], f[i][3], qf[2 * i], qf[2 * i + 1]);
                        lds128((opq(ka[i >> 1]) ^ ((i & 1) << 6)) + 3072, f[i][0], f[i][1], f[i][2], f[i][3]);
                    }
                    __syncwarp();
                    half_load(xtile + 3072, &maps.kh, row0 + 6 * TS + 24 + AFTER(ALL6(f, 0)), xb, false);
#pragma unroll
                    for (int i = 0; i < 6; i++) mma16816v(cB, f[i][0], f[i][1], f[i][2], f[i][3], qf[2 * i], qf[2 * i + 1]);
                    sc2 = cA[0] + cA[3]; sc3 = cB[0] + cB[3];
                }
#pragma unroll
                for (int i = 0; i < 12; i++) qf[i] = mul2(qf[i], 0x6f806f80u);
                kr_scores(IC<0>(), sc0, sc1);
                kr_scores(IC<1>(), sc0, sc1);
                if (layer == 1) stage_v(IC<0>());
                kr_scores(IC<2>(), sc0, sc1);
                if (layer == 1) stage_v(IC<1>());
                kr_scores(IC<3>(), sc0, sc1);
                kr_scores(IC<4>(), sc2, sc3);
                {
                    LANE_IDS
                    const float sa = f_(lds32(kx + 8 + 4 * t)), sb = t == 0 ? f_(lds32(kx + 24)) : 1.0f;
                    const int nx = (int)lds32(kx);
                    uint32_t rm = lds32(kx + 4), qm = 0u;
#pragma unroll
                    for (int i = 0; i < 6; i++) qm = __vimax3_u16x2(qm, qf[2 * i] & 0x7fff7fffu, qf[2 * i + 1] & 0x7fff7fffu);
#pragma unroll
                    for (int i = 0; i < 3; i++) lds128(SM_QS + (2 * t + (g & 1)) * 48 + 16 * i, qf[4 * i], qf[4 * i + 1], qf[4 * i + 2], qf[4 * i + 3]);
                    if (__any_sync(0xffffffffu, max(qm & 0xffffu, qm >> 16) >= 0x7f80u)) rm = 31;
                    sc0 *= sa; sc1 *= sa; sc2 *= sb; sc3 *= sb;
                    if (nx) {
                        const uint32_t w = lds32(kx + 32 + 4 * (lane & 15));
                        const float d = bf_lo(lds16(SM_QS + ((w >> 15) & 0x1fe))) * bf_lo(w);
#pragma unroll 1
                        for (int n = 0; n < nx; n++) {
                            const uint32_t k = (__shfl_sync(0xffffffffu, w, n) >> 24) ^ lane;
                            const float dn = __shfl_sync(0xffffffffu, d, n);
                            if (k == 0) sc0 += dn;
                            if (k == 32) sc1 += dn;
                            if (k == 64) sc2 += dn;
                            if (k == 96) sc3 += dn;
                        }
                    }
#pragma unroll 1
                    for (; rm; rm &= rm - 1) {
                        const int tau = __ffs(rm) - 1;
#pragma unroll 1
                        for (int hf = 0; hf < 2; hf++) {
                            const char* gp = static_cast<const char*>(maps.kp) + (size_t)(row0 + tau * TS) * 128 + (8 * hf + (g >> 1) + 4 * (g & 1)) * 384 + 16 * t;
                            float cA[4] = {0.f, 0.f, 0.f, 0.f};
#pragma unroll
                            for (int i = 0; i < 6; i++) {
                                const uint4 a = __ldcg(reinterpret_cast<const uint4*>(gp + 64 * i));
                                mma16816(cA, a.x, a.y, a.z, a.w, qf[2 * i], qf[2 * i + 1]);
                            }
                            if ((tau & 3) == t) {
                                const int k = hf + (tau >> 2) * 2;
                                const float d = cA[0] + cA[3];
                                if (k == 0) sc0 = d; else if (k == 1) sc1 = d; else if (k == 2) sc2 = d; else sc3 = d;
                            }
                        }
                    }
                }
                if (layer == 0) {
                    LANE_IDS
#pragma unroll 1
                    for (int s = 5; s < 8; s++) {
                        mbar_wait(s == 5 ? xb : rb + (s & 1) * 8, s == 5);
                        const uint32_t tile = s == 5 ? bt : ring + (s & 1) * TILE;
                        float cA[4] = {0.f, 0.f, 0.f, 0.f}, cB[4] = {0.f, 0.f, 0.f, 0.f};
#pragma unroll
                        for (int i = 0; i < 6; i++) {
                            uint32_t a0, a1, a2, a3;
                            lds128(tile + K_OFF(i), a0, a1, a2, a3);
                            mma16816(cA, a0, a1, a2, a3, qf[2 * i], qf[2 * i + 1]);
                            lds128(tile + K_OFF(i) + 3072, a0, a1, a2, a3);
                            mma16816(cB, a0, a1, a2, a3, qf[2 * i], qf[2 * i + 1]);
                        }
                        if (t == (s & 3)) { sc2 = cA[0] + cA[3]; sc3 = cB[0] + cB[3]; }
                        __syncwarp();
                        refill1(s, AFTER(__float_as_uint(cA[0]) | __float_as_uint(cB[0])));
                    }
                } else {
                    LANE_IDS
#pragma unroll 1
                    for (int i = 2; i < 4; i++) {
                        const uint32_t tile = i == 3 ? ring : xtile, tb = i == 3 ? rb : xb;
                        mbar_wait(tb, 1);
#pragma unroll
                        for (int k = 0; k < 6; k++) {
                            const uint32_t a = tile + K_OFF(k);
                            lds128(a, kr[24 + k][0], kr[24 + k][1], kr[24 + k][2], kr[24 + k][3]);
                            lds128(a + 3072, kr[24 + 6 + k][0], kr[24 + 6 + k][1], kr[24 + 6 + k][2], kr[24 + 6 + k][3]);
                        }
                        float cA[4] = {0.f, 0.f, 0.f, 0.f}, cB[4] = {0.f, 0.f, 0.f, 0.f}, cC[4] = {0.f, 0.f, 0.f, 0.f}, cD[4] = {0.f, 0.f, 0.f, 0.f};
#pragma unroll
                        for (int k = 0; k < 3; k++) {
                            mma16816(cA, kr[24 + k][0], kr[24 + k][1], kr[24 + k][2], kr[24 + k][3], qf[2 * k], qf[2 * k + 1]);
                            mma16816(cB, kr[24 + 6 + k][0], kr[24 + 6 + k][1], kr[24 + 6 + k][2], kr[24 + 6 + k][3], qf[2 * k], qf[2 * k + 1]);
                            mma16816(cC, kr[24 + 3 + k][0], kr[24 + 3 + k][1], kr[24 + 3 + k][2], kr[24 + 3 + k][3], qf[6 + 2 * k], qf[7 + 2 * k]);
                            mma16816(cD, kr[24 + 9 + k][0], kr[24 + 9 + k][1], kr[24 + 9 + k][2], kr[24 + 9 + k][3], qf[6 + 2 * k], qf[7 + 2 * k]);
                        }
                        __syncwarp();
                        tile_load(tile, &maps.v, row0 + (i + 1) * TS + AFTER(__float_as_uint(cA[0]) | __float_as_uint(cB[0]) | __float_as_uint(cC[0]) | __float_as_uint(cD[0])), tb);
                        if (t == i) { sc2 = (cA[0] + cC[0]) + (cA[3] + cC[3]); sc3 = (cB[0] + cD[0]) + (cB[3] + cD[3]); }
                    }
                }
            }
            {
                const uint32_t mk = __reduce_max_sync(0xffffffffu, f2key(fmaxf(fmaxf(sc0, sc1), fmaxf(sc2, sc3))));
                if ((opq(tid) & 31) == 0) st_pkt2(&maps.scr->mx[h * 32 + c * 8 + wu], mk, tag);
                mw = key2f(mk);
            }
            pk0 = pack2(ex2((sc0 - mw) * SC), ex2((sc1 - mw) * SC));
            pk1 = pack2(ex2((sc2 - mw) * SC), ex2((sc3 - mw) * SC));
            sc2 = (bf_lo(pk0) + bf_hi(pk0)) + (bf_lo(pk1) + bf_hi(pk1));
#pragma unroll
            for (int o = 16; o > 0; o >>= 1) sc2 += __shfl_xor_sync(0xffffffffu, sc2, o);
#pragma unroll
            for (int s = 0; s < 3; s++) { acc[s][0] = acc[s][1] = acc[s][2] = acc[s][3] = 0.f; }
            auto head_ld = [&](int lane) { const uint2 mv = ld_pkt2(&maps.scr->mx[h * 32 + lane]); sc0 = f_(mv.x); sc1 = f_(mv.y); };
            auto head_factor = [&](int lane) {
                int it = 0;
                while (!__all_sync(0xffffffffu, __float_as_uint(sc1) == tag) && ++it < SPIN_CAP) head_ld(lane);
                sc3 = ex2((mw - key2f(__reduce_max_sync(0xffffffffu, __float_as_uint(sc0)))) * SC);
            };
#define P_CONSTS \
                const uint32_t sel0 = g == 0 ? 0x4410u : (g == 1 ? 0x1044u : 0x4444u); \
                const uint32_t sel1 = g == 2 ? 0x4410u : (g == 3 ? 0x1044u : 0x4444u); \
                const int src00 = 4 * (t < 2 ? 4 * t : 4 * (t - 2) + 1);
#define P_FRAGS(tau) \
                const uint32_t pk = ((tau) & 4) ? pk1 : pk0; \
                const uint32_t w0 = __shfl_sync(0xffffffffu, pk, src00 + ((tau) & 3)); \
                const uint32_t w1 = __shfl_sync(0xffffffffu, pk, src00 + ((tau) & 3) + 8); \
                uint32_t pb[4][2]; \
                _Pragma("unroll") for (int j = 0; j < 4; j++) { \
                    const uint32_t src = ((j & 1) ? w1 : w0) >> ((j >> 1) * 16); \
                    pb[j][0] = __byte_perm(src, 0, sel0); pb[j][1] = __byte_perm(src, 0, sel1); \
                }
            if (layer == 0) {
#pragma unroll 1
                for (int s = 8; s < 16; s++) {
                    LANE_IDS
                    P_CONSTS
                    if (s == 14) {
                        uint4* p = nullptr;
                        if (tl < 48) p = &maps.scr->qx[b * 48 + tl];
                        else if (tl < 98) p = &maps.scr->cx[b * 56 + tl - 48];
                        else if (tl < 145) {}
                        else if (tl >= 160) { if (tl < 208) p = &maps.scr->qc[b * 48 + tl - 160]; }
                        else if (b < NG) { if (tl < 153) p = &maps.scr->ah[b * 8 + tl - 145]; }
                        else if (b < DN0 + NDN && tl < 149) p = &maps.scr->ay[(b - DN0) * 4 + tl - 145];
                        if (p) st_pkt(p, 0, 0, 0, tl < 48);
                    }
                    if (s == 13) head_ld(lane);
                    P_FRAGS((s + 2) & 7)
                    mbar_wait(rb + (s & 1) * 8, ((s >> 1) + 1) & 1);
                    const uint32_t tile = ring + (s & 1) * TILE;
#pragma unroll
                    for (int j = 0; j < 4; j++) {
#pragma unroll
                        for (int u = 0; u < 3; u++) {
                            uint32_t a0, a1, a2, a3;
                            lds128(tile + (j >> 1) * 3072 + V_OFF(3 * (j & 1) + u), a0, a1, a2, a3);
                            mma16816(acc[u], a0, a1, a2, a3, pb[j][0], pb[j][1]);
                        }
                    }
                    __syncwarp();
                    if (s < 14) refill1(s, AFTER(__float_as_uint(acc[0][0]) | __float_as_uint(acc[1][0]) | __float_as_uint(acc[2][0])), true);
                    if (s == 13) head_factor(lane);
                    if (s == 15 && elect_one()) {
                        uint32_t n;
                        asm volatile("atom.shared.add.u32 %0, [%1], 1;" : "=r"(n) : "r"(SM_MISC + 8) : "memory");
                        if (n == 7) load_wo(maps, SM_B, h, c, WBAR, 5);
                    }
                }
            } else {
                LANE_IDS
                P_CONSTS
#pragma unroll
                for (int s = 0; s < 2; s++) {
                    P_FRAGS(s)
#pragma unroll
                    for (int j = 0; j < 4; j++) {
#pragma unroll
                        for (int u = 0; u < 3; u++) {
                            const int k = 6 * (j >> 1) + 3 * (j & 1) + u;
                            mma16816(acc[u], kr[12 * s + k][0], kr[12 * s + k][1], kr[12 * s + k][2], kr[12 * s + k][3], pb[j][0], pb[j][1]);
                        }
                    }
                }
#pragma unroll 1
                for (int i = 4; i < 10; i++) {
                    const int sl = i == 5 ? 0 : (i == 6 || i == 8 ? 1 : 2);
                    const uint32_t tile = sl ? ring + (sl - 1) * TILE : xtile, tb = sl ? rb + (sl - 1) * 8 : xb;
                    if (i == 8) head_ld(lane);
                    if (i == 9) head_factor(lane);
                    P_FRAGS(i - 2)
                    mbar_wait(tb, (0x310 >> i) & 1);
#pragma unroll
                    for (int k = 0; k < 6; k++) {
                        const uint32_t a = tile + V_OFF(k);
                        lds128(a, kr[24 + k][0], kr[24 + k][1], kr[24 + k][2], kr[24 + k][3]);
                        lds128(a + 3072, kr[24 + 6 + k][0], kr[24 + 6 + k][1], kr[24 + 6 + k][2], kr[24 + 6 + k][3]);
                    }
#pragma unroll
                    for (int j = 0; j < 4; j++) {
#pragma unroll
                        for (int u = 0; u < 3; u++) {
                            const int k = 6 * (j >> 1) + 3 * (j & 1) + u;
                            mma16816(acc[u], kr[24 + k][0], kr[24 + k][1], kr[24 + k][2], kr[24 + k][3], pb[j][0], pb[j][1]);
                        }
                    }
                    __syncwarp();
                    if (wu < L1R && i == 6 - 2 * (wu & 1)) tile_load_l1(tile, maps.vp, row0 + (6 - (wu & 1)) * TS, tb, lane);
                    else if (i == 4 || i == 6 || i == 7) tile_load(tile, &maps.v, row0 + (i == 4 ? 5 : i) * TS + AFTER(__float_as_uint(acc[0][0]) | __float_as_uint(acc[1][0]) | __float_as_uint(acc[2][0])), tb);
                    if (i == 7 && role < DN0 + NDN && elect_one()) {
                        uint32_t n;
                        asm volatile("atom.shared.add.u32 %0, [%1], 1;" : "=r"(n) : "r"(SM_MISC + 8) : "memory");
                        if (n == 15) load_wo(maps, SM_Q, h, c, WBAR, 3);
                    }
                }
            }
#undef P_FRAGS
#undef P_CONSTS
#undef LANE_IDS
#undef K_OFF
#undef V_OFF
        }

        uint32_t ticket = 0;
        {
            const int tl = opq(tid), warp = tl >> 5, lane = tl & 31, g = lane >> 2, t = lane & 3, mat = lane >> 3, r8 = lane & 7;
            {
                const uint32_t d = SM_R + 4 * (warp * 196 + 8 * g + 4 * t);
                if (t < 2) {
#pragma unroll
                    for (int u = 0; u < 3; u++) sts128(d + 256 * u, acc[u][0] * sc3, acc[u][1] * sc3, acc[u][2] * sc3, acc[u][3] * sc3);
                }
                if (lane == 0) sts128(d + 768, sc2 * sc3, 0.f, 0.f, 0.f);
            }
            const int tc = min(tl, 48);
            uint4* pc = opq(&maps.scr->cx[h * 4 * 56 + tc]);
            uint4* po = pc + c * 56;
            const uint32_t fa = opq(SM_R + 16 * tc);
            __syncthreads();
            const int kg = warp >> 1, mg = warp & 1;
            const bool wo2 = layer && role < DN0 + NDN;
            const bool wo4 = layer && role < NG;
            uint32_t aw, oa, ob0, dw;
            uint32_t* tk;
            auto addrs = [&]() {
                aw = opq((wo2 ? SM_Q : SM_B) + (48 * kg + (mat >> 1) * 8 + r8) * 64 + (((2 * mg + (mat & 1)) ^ ((r8 >> 1) & 3)) << 4));
                oa = opq(SM_OS + 96 * kg + 8 * t);
                ob0 = opq(oa + 8 * t);
                dw = opq(SM_R + 4 * (4 * (16 * mg + g) + kg));
                tk = maps.scr->ticket;
            };
            uint32_t a[2][3][4];
            auto preload = [&]() {
#pragma unroll
                for (int i = 0; i < 2; i++) {
                    mbar_wait(WBAR + 8 * i, wo2);
#pragma unroll
                    for (int ks = 0; ks < 3; ks++) ldsm4t(aw + i * 12288 + ks * 1024, a[i][ks]);
                }
            };
            if (wu < 2) {
                if (tl < 49) {
                    float4 v[8];
#pragma unroll
                    for (int w = 0; w < 8; w++) v[w] = lds128f(fa + w * 784);
                    st_pktf(po, ((v[0].x + v[1].x) + (v[2].x + v[3].x)) + ((v[4].x + v[5].x) + (v[6].x + v[7].x)),
                            ((v[0].y + v[1].y) + (v[2].y + v[3].y)) + ((v[4].y + v[5].y) + (v[6].y + v[7].y)),
                            ((v[0].z + v[1].z) + (v[2].z + v[3].z)) + ((v[4].z + v[5].z) + (v[6].z + v[7].z)),
                            ((v[0].w + v[1].w) + (v[2].w + v[3].w)) + ((v[4].w + v[5].w) + (v[6].w + v[7].w)), tbit);
                }
                __syncwarp();
                uint4 v[4];
#pragma unroll
                for (int k = 0; k < 4; k++) v[k] = ld_pkt(pc + k * 56);
                asm volatile("bar.arrive 1, 256;" ::: "memory");
                addrs();
                const int w = 2 * tc, k3 = w / 24, r = w - 24 * k3;
                const uint32_t d0 = opq(tl < 48 ? SM_OS + 4 * (24 * k3 + (r < 16 ? 4 * (r & 3) + (r >> 2) : 16 + 2 * (r & 3) + ((r >> 2) & 1))) : SM_MISC);
                const uint32_t d1 = opq(tl < 48 ? d0 + (r < 16 ? 16 : 8) : SM_MISC + 12);
                int it = 0;
                bool more = true;
                while (__any_sync(0xffffffffu, ((v[0].w ^ tbit) | (v[1].w ^ tbit) | (v[2].w ^ tbit) | (v[3].w ^ tbit)) & 1) && more) {
#pragma unroll
                    for (int k = 0; k < 4; k++) v[k] = ld_pkt(pc + k * 56);
                    more = ++it < SPIN_CAP;
                }
                const float o0 = (f_(v[0].x) + f_(v[1].x)) + (f_(v[2].x) + f_(v[3].x));
                const uint32_t w0 = pack2(o0, (f_(v[0].y) + f_(v[1].y)) + (f_(v[2].y) + f_(v[3].y)));
                sts32(d1, pack2((f_(v[0].z) + f_(v[1].z)) + (f_(v[2].z) + f_(v[3].z)), (f_(v[0].w) + f_(v[1].w)) + (f_(v[2].w) + f_(v[3].w))));
                sts32(d0, tl < 48 ? w0 : __float_as_uint(o0));
                asm volatile("bar.arrive 2, 256;" ::: "memory");
                preload();
                asm volatile("bar.sync 3, 64;" ::: "memory");
            } else {
                addrs();
                asm volatile("bar.sync 1, 256;" ::: "memory");
                preload();
                asm volatile("bar.sync 2, 256;" ::: "memory");
            }
            uint32_t ob[6];
            lds128(ob0, ob[0], ob[1], ob[2], ob[3]);
            lds64(oa + 64, ob[4], ob[5]);
            if (tl == 224 && layer == 0)
                asm volatile("atom.relaxed.gpu.global.inc.u32 %0, [%1], 0x7fffffff;" : "=r"(ticket) : "l"(tk) : "memory");
            auto put = [&](int i, const float (&cc)[4]) { if (t == 0) { sts32(dw + 512 * i, cc[0]); sts32(dw + 512 * i + 128, cc[2]); } };
            {
                float c0[4] = {0.f, 0.f, 0.f, 0.f}, c1[4] = {0.f, 0.f, 0.f, 0.f}, c2[4] = {0.f, 0.f, 0.f, 0.f}, c3[4] = {0.f, 0.f, 0.f, 0.f};
                mbar_wait(WBAR + 16, wo2);
#pragma unroll
                for (int ks = 0; ks < 3; ks++) {
                    mma16816v(c0, a[0][ks][0], a[0][ks][1], a[0][ks][2], a[0][ks][3], ob[2 * ks], ob[2 * ks + 1]);
                    mma16816v(c1, a[1][ks][0], a[1][ks][1], a[1][ks][2], a[1][ks][3], ob[2 * ks], ob[2 * ks + 1]);
                    if (ks == 0 && layer == 0) {
                        mbar_wait(WBAR + 24, 0);
#pragma unroll
                        for (int k = 0; k < 3; k++) ldsm4t(aw + 3 * 12288 + k * 1024, wk[k]);
                    }
                    if (ks == 1) mbar_wait(WBAR + 32, wo4);
                    ldsm4t(aw + 2 * 12288 + ks * 1024, a[0][ks]);
                }
                const uint32_t aw4 = aw + (wo2 && !wo4 ? SM_B - SM_Q : 0) + 4 * 12288;
                ldsm4t(aw4 + 1024, a[1][0]);
#pragma unroll
                for (int ks = 0; ks < 3; ks++) {
                    mma16816v(c2, a[0][ks][0], a[0][ks][1], a[0][ks][2], a[0][ks][3], ob[2 * ks], ob[2 * ks + 1]);
                    mma16816v(c3, wk[ks][0], wk[ks][1], wk[ks][2], wk[ks][3], ob[2 * ks], ob[2 * ks + 1]);
                    if (ks == 0) { ldsm4t(aw4, a[0][0]); put(0, c0); put(1, c1); }
                    if (ks == 1) ldsm4t(aw4 + 2048, a[0][1]);
                }
                float c4[4] = {0.f, 0.f, 0.f, 0.f}, c5[4] = {0.f, 0.f, 0.f, 0.f};
                mma16816v(c4, a[0][0][0], a[0][0][1], a[0][0][2], a[0][0][3], ob[0], ob[1]);
                mma16816v(c5, a[1][0][0], a[1][0][1], a[1][0][2], a[1][0][3], ob[2], ob[3]);
                mma16816v(c4, a[0][1][0], a[0][1][1], a[0][1][2], a[0][1][3], ob[4], ob[5]);
                put(2, c2); put(3, c3);
                c4[0] += c5[0]; c4[2] += c5[2];
                put(4, c4);
            }
        }
        {
            const int tl = opq(tid);
            uint4* pr = opq(&maps.scr->acc[layer][54 * c + min(tl, 53)]);
            const uint32_t fa = opq(SM_R + 48 * tl);
            const float il = rcp(f_(lds32(SM_MISC)));
            __syncthreads();
            if (tl < 54) {
                const float4 v0 = lds128f(fa), v1 = lds128f(fa + 16), v2 = lds128f(fa + 32);
                const float y0 = il * ((v0.x + v0.y) + (v0.z + v0.w)), y1 = il * ((v1.x + v1.y) + (v1.z + v1.w)), y2 = il * ((v2.x + v2.y) + (v2.z + v2.w));
                red_pkt(pr, y0, tl == 53 ? 0.f : y1, tl == 53 ? 0.f : y2);
            }
            if (tl == 224 && layer == 0) {
                sts32(SM_MISC + 4, ticket);
                if (ticket < NG) load_ffn(maps, ticket, SM_B, FBAR);
            }
        }
        __syncthreads();
        if (layer == 0) role = __shfl_sync(0xffffffffu, (int)lds32(SM_MISC + 4), 0);
        const uint32_t DONE32 = 0x42000000u;
        if (role < NG) {
            const int tl = opq(tid), warp = tl >> 5, lane = tl & 31, g = lane >> 2, t = lane & 3, mat = lane >> 3, r8 = lane & 7;
            const uint32_t ag = SM_B + (80 * warp + (mat >> 1) * 8 + r8) * 96 + (((mat & 1) ^ (r8 >> 2)) << 4);
            constexpr int GI = 32, GK = 16 * 96;
            const bool on = (g & 1) == (t >> 1), isx = (on && g < 2) || g == 4;
            const uint32_t pm = opq(isx ? SM_XS + 160 * warp + 16 * t : (on || g == 5 ? SM_ONE : SM_ZERO)), pm2 = opq(pm + 128 - (isx ? 8 * t : 0));
            const uint32_t dg = opq(SM_R + 4 * (2 * (warp * 48 + g) + t));
            const uint32_t ho = opq(16u * (role * 8 + 4 * warp + ((lane * 11) >> 5)));
            const uint32_t fa = opq(SM_R + 8 * (24 * warp + 2 * min(lane, 11)));
            uint32_t pre[9][4];
            {
                bool hx = wu == 7;
                int it = 0;
                const uint4* px = opq(&maps.scr->acc[layer][min(tl, 215)]);
                const int cq = tl / 54, r = tl - 54 * cq, k0 = min(160 * cq + 3 * r, DM - 1);
                const uint32_t w0 = SM_XS + 4 * xpos(k0 >> 1), w1 = SM_XS + 4 * xpos(min((k0 >> 1) + 1, DM / 2 - 1));
                const bool two = tl < 216 && r != 53;
                const uint32_t e0 = opq(tl < 216 ? w0 + 2 * (k0 & 1) : SM_MISC + 12);
                const uint32_t e1 = opq(two ? ((k0 & 1) ? w1 : w0 + 2) : SM_MISC + 12), e2 = opq(two ? w1 + 2 * (k0 & 1) : SM_MISC + 12);
                const uint32_t x01 = opq(lds16(e0) | (lds16(e1) << 16)), x2 = lds16(e2);
                auto take_x = [&](const uint4 v) {
                    if (__all_sync(0xffffffffu, v.w == DONE32)) {
                        hx = true;
                        const uint32_t y01 = add2(x01, pack2(f_(v.x), f_(v.y))), y2 = add2(x2, pack2(f_(v.z), 0.f));
                        sts16(e0, y01); sts16(e1, y01 >> 16); sts16(e2, y2);
                    }
                };
                while (!mbar_test(FBAR, 0) && ++it < SPIN_CAP) { if (!hx) take_x(ld_pkt(px)); }
                uint4 v = make_uint4(0u, 0u, 0u, 0u);
                if (!hx) v = ld_pkt(px);
#pragma unroll
                for (int n = 0; n < 9; n++) ldsm4t(ag + (n % 3) * GI + (n / 3) * GK, pre[n]);
                if (layer) {
#pragma unroll
                    for (int n = 9; n < 15; n++) ldsm4t(ag + (n % 3) * GI + (n / 3) * GK, kr[n - 9]);
                }
                if (!hx) {
                    bool more = true;
                    while (!__all_sync(0xffffffffu, v.w == DONE32) && more) { v = ld_pkt(px); more = ++it < SPIN_CAP; }
                    const uint32_t y01 = add2(x01, pack2(f_(v.x), f_(v.y))), y2 = add2(x2, pack2(f_(v.z), 0.f));
                    sts16(e0, y01); sts16(e1, y01 >> 16); sts16(e2, y2);
                }
            }
            __syncthreads();
            {
                float cc[3][4], gr[4];
                if (layer) gemv15r(cc, gr, pre, kr, pm, pm2);
                else gemv15<GK, true>(cc, gr, pre, [&](int i) { return ag + i * GI; }, pm, pm2);
                if (t < 2) {
#pragma unroll
                    for (int i = 0; i < 3; i++) { sts32(dg + 128 * i, cc[i][0] + cc[i][3]); sts32(dg + 128 * i + 64, cc[i][1] + cc[i][2]); }
                }
                if ((lane | 4) == 22) sts32(SM_ST + 8 * warp + (g & 1) * 4, gr[0]);
            }
            uint4* ph = reinterpret_cast<uint4*>(reinterpret_cast<char*>(maps.scr->ah) + ho);
            const bool snd = (0x249 >> lane) & 1;
            __syncthreads();
            if (wu < 2) {
                float mean, inv;
                float4 v[8];
#pragma unroll
                for (int w = 0; w < 8; w++) v[w] = lds128f(fa + w * 384);
                ln_stats(mean, inv);
                const float ga = inv * ((((v[0].x + v[1].x) + (v[2].x + v[3].x)) + ((v[4].x + v[5].x) + (v[6].x + v[7].x))) -
                                        mean * (((v[0].y + v[1].y) + (v[2].y + v[3].y)) + ((v[4].y + v[5].y) + (v[6].y + v[7].y))));
                const float gb = inv * ((((v[0].z + v[1].z) + (v[2].z + v[3].z)) + ((v[4].z + v[5].z) + (v[6].z + v[7].z))) -
                                        mean * (((v[0].w + v[1].w) + (v[2].w + v[3].w)) + ((v[4].w + v[5].w) + (v[6].w + v[7].w))));
                uint32_t wd = pack2(ga, gb);
                if (role < NG / 2) {
                    const float g0 = bf_lo(wd), g1 = bf_hi(wd);
                    wd = pack2(g0 * rcp(1.0f + ex2(-1.4426950408889634f * g0)), g1 * rcp(1.0f + ex2(-1.4426950408889634f * g1)));
                }
                const uint32_t wa = __shfl_down_sync(0xffffffffu, wd, 1), wb = __shfl_down_sync(0xffffffffu, wd, 2);
                if (snd) st_pkt(ph, wd, wa, wb, tag);
            }
            __syncthreads();
        } else if (role < DN0 + NDN) {
            const int j = role - DN0;
            const int tl = opq(tid), warp = tl >> 5, lane = tl & 31, g = lane >> 2, t = lane & 3, mat = lane >> 3, r8 = lane & 7;
            float xr0 = 0.f, xr1 = 0.f;
            if (wu == 0) {
                const int col = 16 * j + (lane & 15), cc = col / 160, r = col - 160 * cc, e = r % 3;
                const uint4* px = &maps.scr->acc[layer][(54 * cc + r / 3)];
                const float x0 = bf_lo(lds16(SM_XS + 4 * xpos(col >> 1) + 2 * (col & 1)));
                uint4 v;
                int it = 0;
                bool ld = layer == 0;
                do {
                    v = ld_pkt(px);
                    if (ld && f_(__shfl_sync(0xffffffffu, v.w, 0)) >= (float)DNTH) { ld = false; if (lane == 0) load_ffn(maps, role, SM_B, FBAR); }
                } while (!__all_sync(0xffffffffu, v.w == DONE32) && ++it < SPIN_CAP);
                if (ld && lane == 0) load_ffn(maps, role, SM_B, FBAR);
                const float xres = bfr(x0 + bfr(f_(e == 0 ? v.x : (e == 1 ? v.y : v.z))));
                xr0 = __shfl_sync(0xffffffffu, xres, 2 * (lane & 7));
                xr1 = __shfl_sync(0xffffffffu, xres, 2 * (lane & 7) + 1);
            }
            const uint32_t ad = SM_B + (192 * warp + (mat >> 1) * 8 + r8) * 32 + (((mat & 1) ^ (r8 >> 2)) << 4);
            const uint32_t hs = SM_R + 384 * warp, hb = opq(hs + 16 * t), dd = opq(SM_R + 3072 + 4 * (warp * 16 + g));
            uint32_t pre[NPRE][4];
            uint32_t pos[3];
#pragma unroll
            for (int i = 0; i < 3; i++) { const int w = 3 * lane + i; pos[i] = opq(hs + 4 * ((w & ~15) + 4 * (w & 3) + ((w >> 2) & 1) + ((w >> 2) & 2))); }
            const uint4* ph = opq(&maps.scr->ah[tl]);
            const uint32_t fa = opq(SM_R + 3072 + 8 * (lane & 7));
            uint2* py = opq(reinterpret_cast<uint2*>(maps.scr->ay) + 8 * j + (lane & 7));
            uint32_t* po = opq(reinterpret_cast<uint32_t*>(out) + 8 * j + (lane & 7));
            mbar_wait(FBAR, 0);
#pragma unroll
            for (int n = 0; n < NPRE; n++) ldsm4t(ad + n * 512, pre[n]);
            {
                uint4 v, u;
                int it = 0;
                bool more;
                do { v = ld_pkt(ph); u = ld_pkt(ph + 256); more = ++it < SPIN_CAP; }
                while (!__all_sync(0xffffffffu, v.w == tag && u.w == tag) && more);
                sts32(pos[0], mul2(v.x, u.x)); sts32(pos[1], mul2(v.y, u.y)); sts32(pos[2], mul2(v.z, u.z));
            }
            __syncwarp();
            {
                float cc[4][4];
                uint32_t hv[3][4];
#pragma unroll
                for (int jj = 0; jj < 3; jj++) lds128(hb + 64 * jj, hv[jj][0], hv[jj][1], hv[jj][2], hv[jj][3]);
#pragma unroll
                for (int n = 0; n < 12; n++) {
                    const int s = n < NPRE ? n : n - NPRE;
                    if (n < 4) cc[n][0] = cc[n][1] = cc[n][2] = cc[n][3] = 0.f;
                    mma16816v(cc[n & 3], pre[s][0], pre[s][1], pre[s][2], pre[s][3], hv[(n >> 1) % 3][2 * (n & 1)], hv[(n >> 1) % 3][2 * (n & 1) + 1]);
                    if (n + NPRE < 12) ldsm4t(ad + (n + NPRE) * 512, pre[n]);
                    if ((n & 1) && n < 6) lds128(hb + 64 * ((n >> 1) + 3), hv[n >> 1][0], hv[n >> 1][1], hv[n >> 1][2], hv[n >> 1][3]);
                }
                if (t == 0) { sts32(dd, (cc[0][0] + cc[1][0]) + (cc[2][0] + cc[3][0])); sts32(dd + 32, (cc[0][2] + cc[1][2]) + (cc[2][2] + cc[3][2])); }
            }
            __syncthreads();
            if (tl < 8) {
                float2 v[8];
#pragma unroll
                for (int w = 0; w < 8; w++) v[w] = lds64f(fa + 64 * w);
                const uint32_t y = pack2(((v[0].x + v[1].x) + (v[2].x + v[3].x)) + ((v[4].x + v[5].x) + (v[6].x + v[7].x)),
                                         ((v[0].y + v[1].y) + (v[2].y + v[3].y)) + ((v[4].y + v[5].y) + (v[6].y + v[7].y)));
                const uint32_t wd = pack2(xr0 + bf_lo(y), xr1 + bf_hi(y));
                if (layer) asm volatile("st.global.u32 [%0], %1;" ::"l"(po), "r"(wd) : "memory");
                st_pkt2(py, wd, tag);
            }
            __syncthreads();
        }
    }
}

typedef CUresult (*EncodeFn)(CUtensorMap*, CUtensorMapDataType, cuuint32_t, void*, const cuuint64_t*, const cuuint64_t*, const cuuint32_t*,
                             const cuuint32_t*, CUtensorMapInterleave, CUtensorMapSwizzle, CUtensorMapL2promotion, CUtensorMapFloatOOBfill);

void make_map(EncodeFn enc, CUtensorMap* m, const void* base, int rank, uint64_t d0, uint64_t d1, uint64_t d2, uint64_t s1, uint64_t s2,
              uint32_t b0, uint32_t b1, uint32_t b2, CUtensorMapSwizzle sw, CUtensorMapL2promotion pr = CU_TENSOR_MAP_L2_PROMOTION_NONE) {
    cuuint64_t dims[3] = {d0, d1, d2};
    cuuint64_t strides[2] = {s1, s2};
    cuuint32_t box[3] = {b0, b1, b2};
    cuuint32_t es[3] = {1, 1, 1};
    enc(m, CU_TENSOR_MAP_DATA_TYPE_BFLOAT16, rank, const_cast<void*>(base), dims, strides, box, es, CU_TENSOR_MAP_INTERLEAVE_NONE, sw,
        pr, CU_TENSOR_MAP_FLOAT_OOB_FILL_NONE);
}

}

extern "C" void kernel_launch(void* const* d_in, const int* in_sizes, int n_in, void* d_out, int out_size) {
    (void)in_sizes; (void)n_in; (void)out_size;
    static EncodeFn enc = nullptr;
    static Scratch* scr = nullptr;
    if (!enc) {
        void* fn = nullptr;
        cudaDriverEntryPointQueryResult qr;
        cudaGetDriverEntryPoint("cuTensorMapEncodeTiled", &fn, cudaEnableDefault, &qr);
        enc = reinterpret_cast<EncodeFn>(fn);
        cudaGetSymbolAddress(reinterpret_cast<void**>(&scr), g_scr);
        cudaFuncSetAttribute(decode_kernel, cudaFuncAttributeMaxDynamicSharedMemorySize, SM_TOTAL);
    }
    Maps maps;
    make_map(enc, &maps.k, d_in[1], 2, 64, (uint64_t)NH * SK * 3, 1, 128, 0, 64, 48, 1, CU_TENSOR_MAP_SWIZZLE_128B);
    make_map(enc, &maps.v, d_in[2], 2, 64, (uint64_t)NH * SK * 3, 1, 128, 0, 64, 48, 1, CU_TENSOR_MAP_SWIZZLE_128B);
    {
        cuuint64_t dims[5] = {64, 16, NH * DH / 64, DM / 80, 5};
        cuuint64_t strides[4] = {NH * DH * 2, 128, 80 * NH * DH * 2, 16 * NH * DH * 2};
        cuuint32_t box[5] = {64, 16, 3, 2, 5};
        cuuint32_t es[5] = {1, 1, 1, 1, 1};
        enc(&maps.wq, CU_TENSOR_MAP_DATA_TYPE_BFLOAT16, 5, d_in[3], dims, strides, box, es, CU_TENSOR_MAP_INTERLEAVE_NONE, CU_TENSOR_MAP_SWIZZLE_128B,
            CU_TENSOR_MAP_L2_PROMOTION_NONE, CU_TENSOR_MAP_FLOAT_OOB_FILL_NONE);
    }
    make_map(enc, &maps.wo, d_in[4], 3, 32, NH * DH, DM / 32, DM * 2, 64, 32, 192, 1, CU_TENSOR_MAP_SWIZZLE_64B);
    constexpr int GW = 48;
    make_map(enc, &maps.w1, d_in[6], 3, FF, 160, 4, FF * 2, 160 * FF * 2, GW, 160, 4, CU_TENSOR_MAP_SWIZZLE_NONE);
    make_map(enc, &maps.w3, d_in[7], 3, FF, 160, 4, FF * 2, 160 * FF * 2, GW, 160, 4, CU_TENSOR_MAP_SWIZZLE_NONE);
    make_map(enc, &maps.w2, d_in[8], 3, DM, 256, 6, DM * 2, 256 * DM * 2, 16, 256, 6, CU_TENSOR_MAP_SWIZZLE_32B);
    make_map(enc, &maps.ks, d_in[1], 2, 64, (uint64_t)NH * SK * 3, 1, 128, 0, 16, 48, 1, CU_TENSOR_MAP_SWIZZLE_NONE);
    make_map(enc, &maps.vs, d_in[2], 2, 64, (uint64_t)NH * SK * 3, 1, 128, 0, 16, 48, 1, CU_TENSOR_MAP_SWIZZLE_NONE);
    make_map(enc, &maps.kh, d_in[1], 2, 64, (uint64_t)NH * SK * 3, 1, 128, 0, 64, 24, 1, CU_TENSOR_MAP_SWIZZLE_128B);
    maps.kp = d_in[1];
    maps.vp = d_in[2];
    maps.scr = scr;
    maps.zero = 0;
    const uint32_t rt[8] = {0x2EE0, 0x35E0, 0x2EE0, 0x35E0, 0x3EE0, 0x35E0, 0x3EE0, 0x35E0};
    for (int i = 0; i < 8; i++) maps.rt[i] = rt[i];
    decode_kernel<<<NCTA, NT, SM_TOTAL, cudaStreamPerThread>>>(maps, (const __nv_bfloat16*)d_in[0], (__nv_bfloat16*)d_out);
}
```

```cpp
#include <cuda_runtime.h>
#include <cuda_bf16.h>
#include <cuda.h>
#include <stdint.h>
#include <math.h>

namespace {

constexpr int DM = 640;
constexpr int NH = 32;
constexpr int DH = 192;
constexpr int SK = 32768;
constexpr int WIN = 4096;
constexpr int FF = 1536;
constexpr int NCTA = 128;
constexpr int NT = 256;
constexpr int TILE = 6144;
constexpr int TS = 48;
constexpr int NG = 64;
constexpr int DN0 = 64;
constexpr int NDN = 40;

constexpr uint32_t SB = 1024;
constexpr uint32_t SM_RING = SB;
constexpr uint32_t SM_B = SM_RING + 8 * 2 * TILE;
constexpr uint32_t SM_Q = SM_B + 61440;
constexpr uint32_t SM_XS = SM_Q + 61440;
constexpr uint32_t SM_R = SM_XS + 1280;
constexpr uint32_t SM_ST = SM_R + 4096;
constexpr uint32_t SM_QS = SM_R + 6272;
constexpr uint32_t SM_OS = SM_QS + 384;
constexpr uint32_t SM_CS = SM_OS + 384;
constexpr uint32_t SM_BAR = SM_CS + 768;
constexpr uint32_t SM_XBAR = SM_BAR + 24 * 8;
constexpr uint32_t SM_MISC = SM_XBAR + 8 * 8;
constexpr uint32_t SM_ONE = SM_MISC + 32;
constexpr uint32_t SM_ZERO = SM_ONE + 160;
constexpr uint32_t SM_KX = SM_ZERO + 160;
constexpr uint32_t SM_TOTAL = SM_KX + 8 * 96 - SB;
constexpr int NEXC = 16;
static_assert(SM_TOTAL <= 232448, "shared memory");
constexpr uint32_t QBAR = SM_BAR + 16 * 8, FBAR = QBAR + 8, WBAR = QBAR + 16, QRDY = QBAR + 56;

constexpr unsigned long long POL_EF = 0x12F0000000000000ull;
constexpr unsigned long long POL_EN = 0x1000000000000000ull;

constexpr int L1R = 3;
constexpr int DNTH = 21;
constexpr int NPRE = 8;
constexpr int SPIN_CAP = 1 << 19;
constexpr uint32_t ONES = 0x3F803F80u;
#define AFTER(x) ((x) & maps.zero)
#define ALL6(a, n) (a[n][0] | a[n + 1][0] | a[n + 2][0] | a[n + 3][0] | a[n + 4][0] | a[n + 5][0])
#define ROW0(w) ((h * SK + (SK - WIN) + c * 1024 + (w) * 128) * 3)

struct Scratch {
    uint4 qx[NCTA * 48];
    uint4 qc[NCTA * 48];
    uint4 cx[NCTA * 56];
    uint4 acc[2][256];
    uint4 ay[256];
    uint4 pad0[256];
    uint4 ah[NG * 8];
    uint2 mx[NH * 32];
    uint32_t ticket[32];
};
__device__ __align__(4096) Scratch g_scr;
struct Maps { CUtensorMap k, v, wq, wo, w1, w3, w2, ks, vs, kh; const void *kp, *vp; Scratch* scr; uint32_t rt[8], zero; };

__device__ __forceinline__ uint32_t smem_u32(const void* p) { return (uint32_t)__cvta_generic_to_shared(p); }
__device__ __forceinline__ void mbar_init(uint32_t bar, uint32_t cnt) {
    asm volatile("mbarrier.init.shared::cta.b64 [%0], %1;" ::"r"(bar), "r"(cnt) : "memory");
}
__device__ __forceinline__ void mbar_expect_tx(uint32_t bar, uint32_t bytes) {
    asm volatile("mbarrier.arrive.expect_tx.shared::cta.b64 _, [%0], %1;" ::"r"(bar), "r"(bytes) : "memory");
}
__device__ __forceinline__ bool mbar_test(uint32_t bar, uint32_t parity) {
    uint32_t done;
    asm volatile("{\n.reg .pred p;\nmbarrier.try_wait.parity.shared::cta.b64 p, [%1], %2;\nselp.u32 %0, 1, 0, p;\n}"
                 : "=r"(done) : "r"(bar), "r"(parity) : "memory");
    return done;
}
__device__ __forceinline__ void mbar_wait(uint32_t bar, uint32_t parity) {
    asm volatile("{\n.reg .pred p;\n.reg .u32 n;\nmov.u32 n, 0;\n"
                 "W: mbarrier.try_wait.parity.shared::cta.b64 p, [%0], %1;\n@p bra D;\n"
                 "add.u32 n, n, 1;\nsetp.lt.u32 p, n, %2;\n@p bra W;\nD:\n}" ::"r"(bar), "r"(parity), "n"(SPIN_CAP) : "memory");
}
__device__ __forceinline__ void tma2d(uint32_t dst, const CUtensorMap* map, int c0, int c1, uint32_t bar, unsigned long long pol) {
    asm volatile("cp.async.bulk.tensor.2d.shared::cluster.global.mbarrier::complete_tx::bytes.L2::cache_hint [%0], [%1, {%3, %4}], [%2], %5;"
                 ::"r"(dst), "l"(map), "r"(bar), "r"(c0), "r"(c1), "l"(pol) : "memory");
}
__device__ __forceinline__ void tma3d(uint32_t dst, const CUtensorMap* map, int c0, int c1, int c2, uint32_t bar, unsigned long long pol) {
    asm volatile("cp.async.bulk.tensor.3d.shared::cluster.global.mbarrier::complete_tx::bytes.L2::cache_hint [%0], [%1, {%3, %4, %5}], [%2], %6;"
                 ::"r"(dst), "l"(map), "r"(bar), "r"(c0), "r"(c1), "r"(c2), "l"(pol) : "memory");
}
__device__ __forceinline__ void tma5d(uint32_t dst, const CUtensorMap* map, int c2, int c3, uint32_t bar, unsigned long long pol) {
    asm volatile("cp.async.bulk.tensor.5d.shared::cluster.global.mbarrier::complete_tx::bytes.L2::cache_hint [%0], [%1, {0, 0, %3, %4, 0}], [%2], %5;"
                 ::"r"(dst), "l"(map), "r"(bar), "r"(c2), "r"(c3), "l"(pol) : "memory");
}
__device__ __forceinline__ void tile_load(uint32_t dst, const CUtensorMap* map, int row, uint32_t bar) {
    asm volatile("{\n.reg .pred p;\nelect.sync _|p, 0xffffffff;\n"
                 "@p mbarrier.arrive.expect_tx.shared::cta.b64 _, [%2], 6144;\n"
                 "@p cp.async.bulk.tensor.2d.shared::cluster.global.mbarrier::complete_tx::bytes.L2::cache_hint [%0], [%1, {0, %3}], [%2], %4;\n}"
                 ::"r"(dst), "l"(map), "r"(bar), "r"(row), "l"(POL_EF) : "memory");
}
__device__ __forceinline__ void half_load(uint32_t dst, const CUtensorMap* map, int row, uint32_t bar, bool first) {
    if (first) asm volatile("{\n.reg .pred p;\nelect.sync _|p, 0xffffffff;\n@p mbarrier.arrive.expect_tx.shared::cta.b64 _, [%0], 6144;\n}" ::"r"(bar) : "memory");
    asm volatile("{\n.reg .pred p;\nelect.sync _|p, 0xffffffff;\n"
                 "@p cp.async.bulk.tensor.2d.shared::cluster.global.mbarrier::complete_tx::bytes.L2::cache_hint [%0], [%1, {0, %3}], [%2], %4;\n}"
                 ::"r"(dst), "l"(map), "r"(bar), "r"(row), "l"(POL_EF) : "memory");
}
__device__ __forceinline__ void tile_keep(const CUtensorMap* map, int row) {
    asm volatile("{\n.reg .pred p;\nelect.sync _|p, 0xffffffff;\n"
                 "@p cp.async.bulk.prefetch.tensor.2d.L2.global.L2::cache_hint [%0, {0, %1}], %2;\n}"
                 ::"l"(map), "r"(row), "l"(POL_EN) : "memory");
}
__device__ __forceinline__ void tile_load_l1(uint32_t dst, const void* base, int row, uint32_t bar, int lane) {
    const char* g = static_cast<const char*>(base) + (size_t)row * 128 + lane * 16;
    const uint32_t s0 = dst + (lane >> 3) * 128 + (((lane & 7) ^ (lane >> 3)) << 4), s1 = s0 ^ 64;
#pragma unroll
    for (int k = 0; k < 12; k++)
        asm volatile("cp.async.ca.shared.global.L2::cache_hint [%0], [%1], 16, %2;" ::"r"(((k & 1) ? s1 : s0) + k * 512), "l"(g + k * 512), "l"(POL_EF) : "memory");
    asm volatile("cp.async.mbarrier.arrive.shared::cta.b64 [%0];" ::"r"(bar) : "memory");
    __syncwarp();
    if (lane == 0) asm volatile("mbarrier.arrive.shared::cta.b64 _, [%0];" ::"r"(bar) : "memory");
}
__device__ __forceinline__ bool elect_one() {
    uint32_t p;
    asm volatile("{\n.reg .pred p;\nelect.sync _|p, 0xffffffff;\nselp.u32 %0, 1, 0, p;\n}" : "=r"(p));
    return p;
}
__device__ __forceinline__ void delay(uint32_t clocks) {
    uint32_t t0, t1;
    asm volatile("mov.u32 %0, %%clock;" : "=r"(t0));
    do asm volatile("mov.u32 %0, %%clock;" : "=r"(t1)); while (t1 - t0 < clocks);
}
__device__ __forceinline__ void lds128(uint32_t addr, uint32_t& a, uint32_t& b, uint32_t& c, uint32_t& d) {
    asm volatile("ld.shared.v4.u32 {%0,%1,%2,%3}, [%4];" : "=r"(a), "=r"(b), "=r"(c), "=r"(d) : "r"(addr) : "memory");
}
__device__ __forceinline__ void lds64(uint32_t addr, uint32_t& a, uint32_t& b) {
    asm volatile("ld.shared.v2.u32 {%0,%1}, [%2];" : "=r"(a), "=r"(b) : "r"(addr) : "memory");
}
__device__ __forceinline__ void ldsm4t(uint32_t addr, uint32_t (&a)[4]) {
    asm volatile("ldmatrix.sync.aligned.m8n8.x4.trans.shared.b16 {%0,%1,%2,%3}, [%4];" : "=r"(a[0]), "=r"(a[1]), "=r"(a[2]), "=r"(a[3]) : "r"(addr) : "memory");
}
__device__ __forceinline__ void mma16816(float (&c)[4], uint32_t a0, uint32_t a1, uint32_t a2, uint32_t a3, uint32_t b0, uint32_t b1) {
    asm("mma.sync.aligned.m16n8k16.row.col.f32.bf16.bf16.f32 {%0,%1,%2,%3}, {%4,%5,%6,%7}, {%8,%9}, {%0,%1,%2,%3};"
        : "+f"(c[0]), "+f"(c[1]), "+f"(c[2]), "+f"(c[3]) : "r"(a0), "r"(a1), "r"(a2), "r"(a3), "r"(b0), "r"(b1));
}
__device__ __forceinline__ void mma16816v(float (&c)[4], uint32_t a0, uint32_t a1, uint32_t a2, uint32_t a3, uint32_t b0, uint32_t b1) {
    asm volatile("mma.sync.aligned.m16n8k16.row.col.f32.bf16.bf16.f32 {%0,%1,%2,%3}, {%4,%5,%6,%7}, {%8,%9}, {%0,%1,%2,%3};"
        : "+f"(c[0]), "+f"(c[1]), "+f"(c[2]), "+f"(c[3]) : "r"(a0), "r"(a1), "r"(a2), "r"(a3), "r"(b0), "r"(b1));
}
__device__ __forceinline__ uint32_t awake(int it, uint32_t zero) {
    float d[4];
    asm volatile("mma.sync.aligned.m16n8k8.row.col.f32.bf16.bf16.f32 {%0,%1,%2,%3}, {%4,%4}, {%4}, {%5,%5,%5,%5};" : "=f"(d[0]), "=f"(d[1]), "=f"(d[2]), "=f"(d[3]) : "r"(it), "f"(0.f));
    return __float_as_uint(d[0]) & zero;
}
__device__ __forceinline__ int xpos(int w) {
    const int seg = w / 40, r = w - 40 * seg;
    return 40 * seg + (r < 32 ? (r & 16) + 4 * (r & 3) + ((r >> 2) & 3) : 32 + 2 * (r & 3) + ((r >> 2) & 1));
}
__device__ __forceinline__ void st_pkt(uint4* p, uint32_t a, uint32_t b, uint32_t c, uint32_t d) {
    asm volatile("{\n.reg .b128 t;\n.reg .b64 lo, hi;\nmov.b64 lo, {%1,%2};\nmov.b64 hi, {%3,%4};\nmov.b128 t, {lo,hi};\nst.relaxed.gpu.global.b128 [%0], t;\n}"
                 ::"l"(p), "r"(a), "r"(b), "r"(c), "r"(d) : "memory");
}
__device__ __forceinline__ void st_pktf(uint4* p, float a, float b, float c, float d, uint32_t bit) {
    st_pkt(p, __float_as_uint(a), __float_as_uint(b), __float_as_uint(c), (__float_as_uint(d) & ~1u) | bit);
}
__device__ __forceinline__ void red_pkt(uint4* p, float a, float b, float c) {
    asm volatile("red.relaxed.gpu.global.add.v4.f32 [%0], {%1,%2,%3,%4};" ::"l"(p), "f"(a), "f"(b), "f"(c), "f"(1.0f) : "memory");
}
__device__ __forceinline__ uint4 ld_pkt(const uint4* p) {
    uint4 v;
    asm volatile("{\n.reg .b128 t;\n.reg .b64 lo, hi;\nld.relaxed.gpu.global.b128 t, [%4];\nmov.b128 {lo,hi}, t;\nmov.b64 {%0,%1}, lo;\nmov.b64 {%2,%3}, hi;\n}"
                 : "=r"(v.x), "=r"(v.y), "=r"(v.z), "=r"(v.w) : "l"(p) : "memory");
    return v;
}
__device__ __forceinline__ uint2 ld_pkt2(const uint2* p) {
    unsigned long long v;
    asm volatile("ld.relaxed.gpu.global.b64 %0, [%1];" : "=l"(v) : "l"(p) : "memory");
    return make_uint2((uint32_t)v, (uint32_t)(v >> 32));
}
__device__ __forceinline__ void st_pkt2(uint2* p, uint32_t a, uint32_t b) {
    asm volatile("st.relaxed.gpu.global.b64 [%0], %1;" ::"l"(p), "l"((unsigned long long)a | ((unsigned long long)b << 32)) : "memory");
}
__device__ __forceinline__ float ex2(float x) { float y; asm("ex2.approx.ftz.f32 %0, %1;" : "=f"(y) : "f"(x)); return y; }
__device__ __forceinline__ float rcp(float x) { float y; asm("rcp.approx.ftz.f32 %0, %1;" : "=f"(y) : "f"(x)); return y; }
__device__ __forceinline__ uint32_t pack2(float lo, float hi) {
    uint32_t r; asm("cvt.rn.bf16x2.f32 %0, %1, %2;" : "=r"(r) : "f"(hi), "f"(lo)); return r;
}
__device__ __forceinline__ float bf_lo(uint32_t w) { return __uint_as_float(w << 16); }
__device__ __forceinline__ float bf_hi(uint32_t w) { return __uint_as_float(w & 0xffff0000u); }
__device__ __forceinline__ float bfr(float x) { return bf_lo(pack2(x, 0.f)); }
__device__ __forceinline__ float f_(uint32_t u) { return __uint_as_float(u); }

__device__ __forceinline__ uint32_t add2(uint32_t a, uint32_t b) { uint32_t r; asm("add.rn.bf16x2 %0, %1, %2;" : "=r"(r) : "r"(a), "r"(b)); return r; }
__device__ __forceinline__ uint32_t mul2(uint32_t a, uint32_t b) { uint32_t r; asm("mul.rn.bf16x2 %0, %1, %2;" : "=r"(r) : "r"(a), "r"(b)); return r; }
__device__ __forceinline__ uint32_t f2key(float f) { const uint32_t u = __float_as_uint(f); return u ^ ((uint32_t)((int)u >> 31) | 0x80000000u); }
__device__ __forceinline__ float key2f(uint32_t k) { return __uint_as_float(k ^ ((uint32_t)((int)~k >> 31) | 0x80000000u)); }
__device__ __forceinline__ float4 lds128f(uint32_t a) {
    float4 v; asm volatile("ld.shared.v4.f32 {%0,%1,%2,%3}, [%4];" : "=f"(v.x), "=f"(v.y), "=f"(v.z), "=f"(v.w) : "r"(a) : "memory"); return v;
}
__device__ __forceinline__ float2 lds64f(uint32_t a) { float2 v; asm volatile("ld.shared.v2.f32 {%0,%1}, [%2];" : "=f"(v.x), "=f"(v.y) : "r"(a) : "memory"); return v; }
__device__ __forceinline__ uint32_t lds32(uint32_t a) { uint32_t v; asm volatile("ld.shared.u32 %0, [%1];" : "=r"(v) : "r"(a) : "memory"); return v; }
__device__ __forceinline__ uint32_t lds16(uint32_t a) { uint32_t v; asm volatile("ld.shared.u16 %0, [%1];" : "=r"(v) : "r"(a) : "memory"); return v; }
__device__ __forceinline__ void sts16(uint32_t a, uint32_t v) { asm volatile("st.shared.u16 [%0], %1;" ::"r"(a), "r"(v) : "memory"); }
__device__ __forceinline__ void sts32(uint32_t a, uint32_t v) { asm volatile("st.shared.u32 [%0], %1;" ::"r"(a), "r"(v) : "memory"); }
__device__ __forceinline__ void sts32(uint32_t a, float v) { asm volatile("st.shared.f32 [%0], %1;" ::"r"(a), "f"(v) : "memory"); }
__device__ __forceinline__ void sts128(uint32_t a, float x, float y, float z, float w) {
    asm volatile("st.shared.v4.f32 [%0], {%1,%2,%3,%4};" ::"r"(a), "f"(x), "f"(y), "f"(z), "f"(w) : "memory");
}
template <int N> struct IC { static constexpr int value = N; };
__device__ __forceinline__ int opq(int x) { asm volatile("" : "+r"(x)); return x; }
__device__ __forceinline__ uint32_t opq(uint32_t x) { asm volatile("" : "+r"(x)); return x; }
template <typename T> __device__ __forceinline__ T* opq(T* p) { asm volatile("" : "+l"(p)); return p; }

__device__ __forceinline__ void ln_finish(float s1, float s2, float& mean, float& inv) {
    const float md = s1 * (1.0f / DM);
    const float var = fmaxf(s2 * (1.0f / DM) - md * md, 0.f);
    mean = bfr(md);
    asm("rsqrt.approx.ftz.f32 %0, %1;" : "=f"(inv) : "f"(var + 1e-5f));
}
__device__ __forceinline__ void ln_stats(float& mean, float& inv) {
    const float4 a = lds128f(SM_ST), b = lds128f(SM_ST + 16), c = lds128f(SM_ST + 32), d = lds128f(SM_ST + 48);
    ln_finish(((a.y + a.w) + (b.y + b.w)) + ((c.y + c.w) + (d.y + d.w)), ((a.x + a.z) + (b.x + b.z)) + ((c.x + c.z) + (d.x + d.z)), mean, inv);
}
template <int SK, bool GRAM, typename AddrF>
__device__ __forceinline__ void gemv15(float (&cc)[3][4], float (&gr)[4], uint32_t (&pre)[9][4], AddrF ad, uint32_t px, uint32_t px2) {
    uint32_t x0[4], x1[4];
    lds128(px, x0[0], x0[1], x0[2], x0[3]);
    lds128(px + 64, x1[0], x1[1], x1[2], x1[3]);
    gr[0] = gr[1] = gr[2] = gr[3] = 0.f;
#pragma unroll
    for (int i = 0; i < 3; i++) {
        cc[i][0] = cc[i][1] = cc[i][2] = cc[i][3] = 0.f;
        mma16816v(cc[i], pre[i][0], pre[i][1], pre[i][2], pre[i][3], x0[0], x0[1]);
    }
#pragma unroll
    for (int i = 0; i < 3; i++) ldsm4t(ad(i) + 3 * SK, pre[i]);
    if (GRAM) mma16816v(gr, x0[0], 0u, x0[1], 0u, x0[0], x0[1]);
#pragma unroll
    for (int i = 0; i < 3; i++) mma16816v(cc[i], pre[3 + i][0], pre[3 + i][1], pre[3 + i][2], pre[3 + i][3], x0[2], x0[3]);
#pragma unroll
    for (int i = 0; i < 3; i++) ldsm4t(ad(i) + 4 * SK, pre[3 + i]);
    lds64(px2, x0[0], x0[1]);
    if (GRAM) mma16816v(gr, x0[2], 0u, x0[3], 0u, x0[2], x0[3]);
#pragma unroll
    for (int i = 0; i < 3; i++) mma16816v(cc[i], pre[6 + i][0], pre[6 + i][1], pre[6 + i][2], pre[6 + i][3], x1[0], x1[1]);
    if (GRAM) mma16816v(gr, x1[0], 0u, x1[1], 0u, x1[0], x1[1]);
#pragma unroll
    for (int i = 0; i < 3; i++) mma16816v(cc[i], pre[i][0], pre[i][1], pre[i][2], pre[i][3], x1[2], x1[3]);
    if (GRAM) mma16816v(gr, x1[2], 0u, x1[3], 0u, x1[2], x1[3]);
    if (GRAM) mma16816v(gr, x0[0], 0u, x0[1], 0u, x0[0], x0[1]);
#pragma unroll
    for (int i = 0; i < 3; i++) mma16816v(cc[i], pre[3 + i][0], pre[3 + i][1], pre[3 + i][2], pre[3 + i][3], x0[0], x0[1]);
}
__device__ __forceinline__ void gemv15r(float (&cc)[3][4], float (&gr)[4], const uint32_t (&pre)[9][4], const uint32_t (&ext)[45][4], uint32_t px, uint32_t px2) {
    uint32_t x0[4], x1[4], x2[2];
    lds128(px, x0[0], x0[1], x0[2], x0[3]);
    lds128(px + 64, x1[0], x1[1], x1[2], x1[3]);
    lds64(px2, x2[0], x2[1]);
    gr[0] = gr[1] = gr[2] = gr[3] = 0.f;
#pragma unroll
    for (int ks = 0; ks < 5; ks++) {
        const uint32_t b0 = ks < 2 ? x0[2 * (ks & 1)] : ks < 4 ? x1[2 * (ks & 1)] : x2[0], b1 = ks < 2 ? x0[2 * (ks & 1) + 1] : ks < 4 ? x1[2 * (ks & 1) + 1] : x2[1];
        mma16816v(gr, b0, 0u, b1, 0u, b0, b1);
#pragma unroll
        for (int i = 0; i < 3; i++) {
            if (ks == 0) cc[i][0] = cc[i][1] = cc[i][2] = cc[i][3] = 0.f;
            const uint32_t (&f)[4] = ks < 3 ? pre[ks < 3 ? 3 * ks + i : 0] : ext[ks < 3 ? 0 : 3 * (ks - 3) + i];
            mma16816v(cc[i], f[0], f[1], f[2], f[3], b0, b1);
        }
    }
}

__device__ __forceinline__ void load_ffn(const Maps& maps, int b, uint32_t dst, uint32_t bar) {
    const bool gu = b < NG;
    mbar_expect_tx(bar, gu ? 61440 : 49152);
    tma3d(dst, gu ? (b < NG / 2 ? &maps.w1 : &maps.w3) : &maps.w2, gu ? 48 * (b & (NG / 2 - 1)) : 16 * (b - DN0), 0, 0, bar, POL_EF);
}

__device__ __forceinline__ void load_wo(const Maps& maps, uint32_t dst, int h, int c, uint32_t bar, int nbox) {
#pragma unroll 1
    for (int i = 0; i < nbox; i++) {
        mbar_expect_tx(bar + 8 * i, 12288);
        tma3d(dst + i * 12288, &maps.wo, 0, h * DH, 5 * c + i, bar + 8 * i, POL_EF);
    }
}

__global__ void __launch_bounds__(NT, 1)
decode_kernel(const __grid_constant__ Maps maps, const __nv_bfloat16* __restrict__ x_in, __nv_bfloat16* __restrict__ out) {
    extern __shared__ __align__(1024) unsigned char smem[];
    const int tid = threadIdx.x;
    const int wu = __shfl_sync(0xffffffffu, tid >> 5, 0);
    const int b = blockIdx.x, h = b >> 2, c = b & 3;
    if (smem_u32(smem) != SB) return;

    {
        const int warp = tid >> 5, lane = tid & 31;
        const uint32_t rbar = SM_BAR + warp * 16;
        if (lane == 0) {
            if (warp == 0) {
                mbar_init(QBAR, 1);
                asm volatile("fence.mbarrier_init.release.cluster;" ::: "memory");
                mbar_expect_tx(QBAR, 61440);
                tma5d(SM_Q, &maps.wq, 3 * h, 2 * c, QBAR, POL_EF);
            }
            mbar_init(rbar, 1); mbar_init(rbar + 8, 1); mbar_init(SM_XBAR + warp * 8, 1);
            mbar_init(FBAR + 8 * max(warp - 1, 0), warp == 7 ? 2 : 1);
            asm volatile("fence.mbarrier_init.release.cluster;" ::: "memory");
            if (warp >= 1 && warp < 7) {
                const CUtensorMap* mp = warp == 1 ? &maps.k : warp == 2 ? &maps.v : warp == 3 ? &maps.wo : warp == 4 ? &maps.w1 : warp == 5 ? &maps.w3 : &maps.w2;
                asm volatile("prefetch.tensormap [%0];" ::"l"(mp) : "memory");
            }
        }
        if (tid == 96) sts32(SM_MISC + 8, 0u);
        if (lane < 2) sts32(SM_KX + warp * 96 + 4 * lane, 0u);
        if (tid >= 128 && tid < 148) {
            const float v = f_(tid < 138 ? ONES : 0u);
            sts128(SM_ONE + 16 * (tid - 128), v, v, v, v);
        }
        if (b == 0 && tid == 255) asm volatile("st.relaxed.gpu.global.u32 [%0], %1;" ::"l"(maps.scr->ticket), "r"(0) : "memory");
        if (tid < 4) st_pkt(reinterpret_cast<uint4*>(&maps.scr->mx[h * 32 + c * 8]) + tid, 0, 0, 0, 0);
        if (tid >= 64 && tid < 66 && b < 108) st_pkt(&maps.scr->acc[1][(2 * b + tid - 64)], 0, 0, 0, 0);
        __syncthreads();
        if (lane == 0) {
            const int row = ROW0(warp);
            mbar_expect_tx(rbar, TILE);
            tma2d(SM_RING + warp * 2 * TILE, &maps.k, 0, row, rbar, POL_EF);
            mbar_expect_tx(rbar + 8, TILE);
            tma2d(SM_RING + (warp * 2 + 1) * TILE, &maps.k, 0, row + TS, rbar + 8, POL_EF);
        }
    }

    uint32_t kr[45][4];
#define KR(n) kr[(n) >> 2][(n) & 3]
    const float SC = 0.07216878364870322f * 1.4426950408889634f;
    int role = 0;
    uint32_t wk[3][4];

#pragma unroll 1
    for (int layer = 0; layer < 2; layer++) {
        const uint32_t tag = layer + 1, tbit = layer ^ 1;
        uint2 xv = make_uint2(0u, 0u);
        uint32_t qo;
        {
            const int tl = opq(tid), warp = tl >> 5, lane = tl & 31, g = lane >> 2, t = lane & 3, mat = lane >> 3, r8 = lane & 7;
            const int kh = warp >> 2, mg = warp & 3;
            const uint32_t aq = SM_Q + kh * TILE + ((mat >> 1) * 8 + r8) * 128 + (((2 * mg + (mat & 1)) ^ r8) << 4);
            if (layer == 0 && tl < 160) xv = reinterpret_cast<const uint2*>(x_in)[tl];
            mbar_wait(QBAR, 0);
            uint32_t pre[9][4];
#pragma unroll
            for (int n = 0; n < 9; n++) ldsm4t(aq + (n % 3) * 2048 + (n / 3) * 2 * TILE, pre[n]);
            const bool dn = role >= DN0 && role < DN0 + NDN;
            if (layer == 1 && !dn) {
                sts32(SM_MISC + 12, ALL6(pre, 0) | ALL6(pre, 3));
                __syncthreads();
                delay(role >= DN0 + NDN ? 1000 : 0);
                if (wu == 7) {
#pragma unroll 1
                    for (int w = 0; w < 6; w++) tile_load(SM_Q + w * TILE, &maps.k, ROW0(w) + 5 * TS, SM_XBAR + w * 8);
                }
            }
            const uint32_t pm = opq(g == 1 ? SM_ONE : SM_XS + 160 * (2 * c + kh) + 16 * t);
            const uint32_t pm2 = opq(pm + 128 - (g == 1 ? 0 : 8 * t));
            const uint32_t dq = opq(SM_R + 768 * kh + 4 * (16 * mg + g));
            qo = opq(16u * (b * 48 + (tl & 63) + (tl >= 64 ? NCTA * 48 : 0)));
            if (tl < 160) {
                const uint32_t xa0 = opq(SM_XS + 4 * xpos(2 * tl));
                const bool xl = tl % 20 < 16;
                if (layer == 1) {
                    const uint4* px = opq(&maps.scr->ay[tl]);
                    uint4 v;
                    int it = 0;
                    bool more;
                    do { v = ld_pkt(px); it += awake(it, maps.zero); more = ++it < SPIN_CAP; } while (!__all_sync(0xffffffffu, (v.y & v.w) == 1) && more);
                    xv = make_uint2(v.x, v.z);
                }
                sts32(xa0, xv.x);
                if (xl) sts32(xa0 + 16, xv.y); else sts32(xa0 + 8, xv.y);
            }
            if (layer == 1 && dn) sts32(SM_MISC + 12, ALL6(pre, 0) | ALL6(pre, 3));
            __syncthreads();
            if (layer == 1 && dn && wu < 6) tile_load(SM_Q + wu * TILE, &maps.k, ROW0(wu) + 5 * TS, SM_XBAR + wu * 8);
            float cc[3][4], gr[4];
            gemv15<2 * TILE, false>(cc, gr, pre, [&](int i) { return aq + i * 2048; }, pm, pm2);
            if (t == 0) {
#pragma unroll
                for (int i = 0; i < 3; i++) { sts32(dq + 256 * i, cc[i][0]); sts32(dq + 256 * i + 32, cc[i][2]); }
                if (layer == 0) {
#pragma unroll
                    for (int i = 0; i < 3; i++) { sts32(dq + 256 * i + 1536, cc[i][1]); sts32(dq + 256 * i + 1568, cc[i][3]); }
                }
            }
        }
        {
            const int tl = opq(tid), j = tl & 63;
            const bool snd = j < 48 && (tl < 64 || (tl < 128 && layer == 0));
            const uint32_t fa = opq(SM_R + 16 * tl + (tl >= 64 ? 512 : 0));
            uint4* pq = reinterpret_cast<uint4*>(reinterpret_cast<char*>(maps.scr->qx) + qo);
            __syncthreads();
            if (snd) {
                const float4 u = lds128f(fa), v = lds128f(fa + 768);
                st_pktf(pq, u.x + v.x, u.y + v.y, u.z + v.z, u.w + v.w, tbit);
            }
            if (layer == 1 && wu >= 5) {
                delay(300);
                if (wu >= 6) tile_load(SM_Q + wu * TILE, &maps.k, ROW0(wu) + 5 * TS, SM_XBAR + wu * 8);
                else if (role < NG && elect_one()) {
                    mbar_expect_tx(WBAR + 32, 12288);
                    tma3d(SM_Q + 4 * 12288, &maps.wo, 0, h * DH, 5 * c + 4, WBAR + 32, POL_EF);
                }
            }
            if (layer == 1 && tl >= 192 && tl < 194 && b < 108) st_pkt(&maps.scr->acc[0][(2 * b + tl - 192)], 0, 0, 0, 0);
        }

        float sc0 = -INFINITY, sc1 = -INFINITY, sc2 = 0.f, sc3 = 0.f, mw;
        uint32_t pk0, pk1;
        float acc[3][4];
        {
            const uint32_t ring = SM_RING + wu * 2 * TILE, rb = SM_BAR + wu * 16;
            const uint32_t xtile = SM_Q + wu * TILE, xb = SM_XBAR + wu * 8;
            const int row0 = ROW0(wu);
            const uint32_t bt = SM_B + wu * TILE;
            auto issue1 = [&](int n, uint32_t dep, bool vph) {
                const CUtensorMap* mp = n < 8 ? &maps.k : &maps.v;
                const int row = row0 + ((n + (n >= 8 ? 2 : 0)) & 7) * TS;
                if (vph && wu < L1R && n == 12 - (wu & 1)) {
                    tile_load_l1(ring + (n & 1) * TILE, maps.vp, row, rb + (n & 1) * 8, opq(tid) & 31);
                    return;
                }
                const int k = vph || n >= 6 ? n & 1 : n >= 3 ? n - 3 : n;
                tile_load(k == 2 ? bt : ring + k * TILE, mp, row + dep, k == 2 ? xb : rb + k * 8);
                if ((maps.rt[wu] >> n) & 1) tile_keep(n < 8 ? &maps.ks : &maps.vs, row);
            };
            auto refill1 = [&](int s, uint32_t dep, bool vph = false) { issue1(s + 2, dep, vph); };
#define K_OFF(i) ((uint32_t)((3 * ((g >> 1) + 4 * (g & 1)) + ((i) >> 1)) * 128 + ((t ^ ((3 * ((g >> 1) + 4 * (g & 1)) + ((i) >> 1)) & 7) ^ (((i) & 1) << 2)) << 4)))
#define V_OFF(i) ((uint32_t)((6 * t + (i)) * 128 + ((g ^ ((6 * t + (i)) & 7)) << 4)))
#define LANE_IDS const int tl = opq(tid), lane = tl & 31, g = lane >> 2, t = lane & 3; (void)tl; (void)lane; (void)g; (void)t;
            const uint32_t kx = SM_KX + wu * 96;
#pragma unroll 1
            for (int s = layer ? 5 : 0; s < 5 + layer; s++) {
                if (s < 5) {
                    LANE_IDS
                    const int k = s >= 3 ? s - 3 : s;
                    mbar_wait(k == 2 ? xb : rb + k * 8, s >= 3);
                    refill1(s, 0);
                    const uint32_t tile = k == 2 ? bt : ring + k * TILE;
                    uint32_t mx = 0u, mn = 0xffffffffu, mn2 = 0xffffffffu;
#pragma unroll
                    for (int q = 0; q < 12; q++) {
                        uint32_t a0, a1, a2, a3;
                        lds128(tile + K_OFF(q % 6) + (q / 6) * 3072, a0, a1, a2, a3);
                        a0 &= 0x7fff7fffu; a1 &= 0x7fff7fffu; a2 &= 0x7fff7fffu; a3 &= 0x7fff7fffu;
                        mx = __vimax3_u16x2(__vimax3_u16x2(mx, a0, a1), a2, a3);
                        mn = __viaddmin_u16x2(a0, 0xffffffffu, __viaddmin_u16x2(a1, 0xffffffffu, mn));
                        mn2 = __viaddmin_u16x2(a2, 0xffffffffu, __viaddmin_u16x2(a3, 0xffffffffu, mn2));
                    }
                    mn = __vminu2(mn, mn2);
                    const uint32_t emax = __reduce_max_sync(0xffffffffu, max(mx & 0xffffu, mx >> 16)) >> 7;
                    const uint32_t base = (max(emax, 16u) - 15u) << 7, lim = base + 0x7fu;
                    bool raw = emax < 80u || emax > 190u;
                    uint32_t fl = __ballot_sync(0xffffffffu, min(mn & 0xffffu, mn >> 16) < lim);
                    if (!raw && fl) {
                        const uint32_t n0 = lds32(kx);
                        __syncwarp();
#pragma unroll 1
                        for (; fl; fl &= fl - 1) {
                            const int g = (__ffs(fl) - 1) >> 2, t = (__ffs(fl) - 1) & 3, q = min(lane, 23) >> 1, i = q >= 6 ? q - 6 : q;
                            const uint32_t a = tile + K_OFF(i) + (q >= 6 ? 3072 : 0) + 8 * (lane & 1);
                            uint32_t w0, w1;
                            lds64(a, w0, w1);
#pragma unroll 1
                            for (int e = 0; e < 4; e++) {
                                const uint32_t x = __funnelshift_r(w0, w1, 16 * e) & 0xffffu;
                                if (e == 1) w0 = w1;
                                if ((x & 0x7fffu) - 1u < lim && lane < 24) {
                                    uint32_t n;
                                    asm volatile("atom.shared.add.u32 %0, [%1], 1;" : "=r"(n) : "r"(kx) : "memory");
                                    if (n < NEXC) sts32(kx + 32 + 4 * n, x | (2 * ((2 * t + (e >> 1)) * 12 + 2 * i + (lane & 1)) + (e & 1)) << 16 | (16 * (s & 4) + (q >= 6 ? 32 : 0) + 4 * g + (s & 3)) << 24);
                                    sts16(a + 2 * e, 0u);
                                }
                            }
                        }
                        __syncwarp();
                        raw = lds32(kx) > NEXC;
                        __syncwarp();
                        if (raw && lane == 0) sts32(kx, n0);
                    }
                    if (lane == 0) {
                        sts32(kx + 8 + 4 * s, (base + (31u << 7)) << 16);
                        if (raw) sts32(kx + 4, lds32(kx + 4) | 1u << s);
                    }
                    const uint32_t b2 = (0x10000u - base) * 0x10001u;
                    auto pack = [&](auto S) {
                        constexpr int n0 = 36 * decltype(S)::value;
#pragma unroll
                        for (int q = 0; q < 12; q++) {
                            uint32_t a0, a1, a2, a3;
                            lds128(tile + K_OFF(q % 6) + (q / 6) * 3072, a0, a1, a2, a3);
                            a0 = __viaddmax_s16x2(a0 & 0x7fff7fffu, b2, 0u) | (a0 & 0x80008000u); a1 = __viaddmax_s16x2(a1 & 0x7fff7fffu, b2, 0u) | (a1 & 0x80008000u);
                            a2 = __viaddmax_s16x2(a2 & 0x7fff7fffu, b2, 0u) | (a2 & 0x80008000u); a3 = __viaddmax_s16x2(a3 & 0x7fff7fffu, b2, 0u) | (a3 & 0x80008000u);
                            KR(n0 + 3 * q) = __byte_perm(a0, a1, 0x6420);
                            KR(n0 + 3 * q + 1) = __byte_perm(a2, a3, 0x6420);
                            const uint32_t ho = __byte_perm(a2, a3, 0x7531);
                            KR(n0 + 3 * q + 2) = __byte_perm(a0, a1, 0x7531) | __funnelshift_r(ho, ho, 4);
                        }
                    };
                    switch (s) {
                        case 0: pack(IC<0>()); break;
                        case 1: pack(IC<1>()); break;
                        case 2: pack(IC<2>()); break;
                        case 3: pack(IC<3>()); break;
                        default: pack(IC<4>()); break;
                    }
                    __syncwarp();
                }
                if (wu < 2 && (s == 3 || layer)) {
                    const int tc = min(opq(tid), 47);
                    const uint4* pq = opq(&maps.scr->qx[h * 4 * 48 + tc]);
                    uint4 v[4];
                    int it = 0;
                    bool more = true;
#pragma unroll
                    for (int k = 0; k < 4; k++) v[k] = ld_pkt(pq + 48 * k);
                    if (layer == 0) {
                        uint4 u[4];
                        do {
#pragma unroll
                            for (int k = 0; k < 4; k++) u[k] = ld_pkt(pq + NCTA * 48 + 48 * k);
                            more = ++it < SPIN_CAP;
                        } while (!__all_sync(0xffffffffu, u[0].w & u[1].w & u[2].w & u[3].w & 1) && more);
                        sts128(SM_CS + 16 * tc, (f_(u[0].x) + f_(u[1].x)) + (f_(u[2].x) + f_(u[3].x)), (f_(u[0].y) + f_(u[1].y)) + (f_(u[2].y) + f_(u[3].y)),
                               (f_(u[0].z) + f_(u[1].z)) + (f_(u[2].z) + f_(u[3].z)), (f_(u[0].w) + f_(u[1].w)) + (f_(u[2].w) + f_(u[3].w)));
                    }
                    float mean, inv;
                    {
                        const int lane = opq(tid) & 31;
                        uint32_t xw[10];
                        lds128(SM_XS + 16 * lane, xw[0], xw[1], xw[2], xw[3]);
                        lds128(SM_XS + 512 + 16 * lane, xw[4], xw[5], xw[6], xw[7]);
                        lds64(SM_XS + 1024 + 8 * lane, xw[8], xw[9]);
                        float s1 = 0.f, s2 = 0.f, s3 = 0.f, s4 = 0.f;
#pragma unroll
                        for (int i = 0; i < 10; i++) { const float e0 = bf_lo(xw[i]), e1 = bf_hi(xw[i]); s1 += e0; s3 += e1; s2 = fmaf(e0, e0, s2); s4 = fmaf(e1, e1, s4); }
                        s1 += s3; s2 += s4;
                        const bool lo = lane < 16;
                        float sv = (lo ? s1 : s2) + __shfl_xor_sync(0xffffffffu, lo ? s2 : s1, 16);
#pragma unroll
                        for (int o = 8; o > 0; o >>= 1) sv += __shfl_xor_sync(0xffffffffu, sv, o);
                        const float so = __shfl_xor_sync(0xffffffffu, sv, 16);
                        ln_finish(lo ? sv : so, lo ? so : sv, mean, inv);
                    }
                    const float4 cs = lds128f(SM_CS + 16 * tc);
                    mean *= -inv;
                    const float m0 = mean * cs.x, m1 = mean * cs.y, m2 = mean * cs.z, m3 = mean * cs.w;
                    const int w = 2 * tc;
                    const uint32_t qd = opq(SM_QS + 4 * (((w >> 2) & 3) * 24 + 2 * (w >> 4) + ((w >> 1) & 1)));
                    while (__any_sync(0xffffffffu, ((v[0].w ^ tbit) | (v[1].w ^ tbit) | (v[2].w ^ tbit) | (v[3].w ^ tbit)) & 1) && more) {
#pragma unroll
                        for (int k = 0; k < 4; k++) v[k] = ld_pkt(pq + 48 * k);
                        more = ++it < SPIN_CAP;
                    }
                    const float q0 = fmaf(inv, (f_(v[0].x) + f_(v[1].x)) + (f_(v[2].x) + f_(v[3].x)), m0), q1 = fmaf(inv, (f_(v[0].y) + f_(v[1].y)) + (f_(v[2].y) + f_(v[3].y)), m1);
                    const float q2 = fmaf(inv, (f_(v[0].z) + f_(v[1].z)) + (f_(v[2].z) + f_(v[3].z)), m2), q3 = fmaf(inv, (f_(v[0].w) + f_(v[1].w)) + (f_(v[2].w) + f_(v[3].w)), m3);
                    sts32(qd, pack2(q0, q1));
                    sts32(qd + 48, pack2(q2, q3));
                    __syncwarp();
                    if (elect_one()) asm volatile("mbarrier.arrive.shared::cta.b64 _, [%0];" ::"r"(QRDY) : "memory");
                }
            }
            uint32_t qa, ka[3];
            {
                LANE_IDS
                qa = opq(SM_QS + (2 * t + (g & 1)) * 48);
#pragma unroll
                for (int i = 0; i < 3; i++) ka[i] = opq(xtile + K_OFF(2 * i));
            }
            uint32_t f[6][4];
            if (layer == 1) {
                if (wu >= 2 && wu < 5) delay(150);
                mbar_wait(xb, 0);
            }
#pragma unroll
            for (int i = 0; i < 6; i++) lds128(ka[i >> 1] ^ ((i & 1) << 6), f[i][0], f[i][1], f[i][2], f[i][3]);
            if (layer == 1) {
                __syncwarp();
                half_load(xtile, &maps.kh, row0 + 6 * TS + AFTER(ALL6(f, 0)), xb, true);
            }
            mbar_wait(QRDY, layer);
            {
                uint32_t qf[12];
#pragma unroll
                for (int i = 0; i < 3; i++) lds128(qa + 16 * i, qf[4 * i], qf[4 * i + 1], qf[4 * i + 2], qf[4 * i + 3]);
                const int t = opq(tid) & 3;
                auto kr_scores = [&](auto TAU, float& sa, float& sb) {
                    constexpr int tau = decltype(TAU)::value;
                    float cc[2][4] = {{0.f, 0.f, 0.f, 0.f}, {0.f, 0.f, 0.f, 0.f}};
#pragma unroll
                    for (int n = 0; n < 12; n++) {
                        const int q = (n & 1) * 6 + (n >> 1), i = n >> 1;
                        const uint32_t l0 = KR(36 * tau + 3 * q), l1 = KR(36 * tau + 3 * q + 1), hh = KR(36 * tau + 3 * q + 2);
                        const uint32_t h0 = hh & 0x87878787u, h1 = __funnelshift_l(hh, hh, 4) & 0x87878787u;
                        mma16816v(cc[n & 1], __byte_perm(l0, h0, 0x5140), __byte_perm(l0, h0, 0x7362), __byte_perm(l1, h1, 0x5140), __byte_perm(l1, h1, 0x7362), qf[2 * i], qf[2 * i + 1]);
                    }
                    if (t == (tau & 3)) { sa = cc[0][0] + cc[0][3]; sb = cc[1][0] + cc[1][3]; }
                };
                auto stage_v = [&](auto S) {
                    constexpr int s = decltype(S)::value;
                    const int lane = opq(tid) & 31, g = lane >> 2, t = lane & 3;
#pragma unroll
                    for (int i = 0; i < 6; i++) {
                        const uint32_t a = ring + s * TILE + V_OFF(i);
                        lds128(a, kr[12 * s + i][0], kr[12 * s + i][1], kr[12 * s + i][2], kr[12 * s + i][3]);
                        lds128(a + 3072, kr[12 * s + 6 + i][0], kr[12 * s + 6 + i][1], kr[12 * s + 6 + i][2], kr[12 * s + 6 + i][3]);
                    }
                    __syncwarp();
                    tile_load(ring + s * TILE, s ? &maps.v : &maps.k, row0 + (s ? 2 : 7) * TS + AFTER(ALL6(kr, 12 * s) | ALL6(kr, 12 * s + 6)), rb + s * 8);
                };
                if (layer == 1) {
                    float cA[4] = {0.f, 0.f, 0.f, 0.f}, cB[4] = {0.f, 0.f, 0.f, 0.f};
#pragma unroll
                    for (int i = 0; i < 6; i++) {
                        mma16816v(cA, f[i][0], f[i][1], f[i][2], f[i][3], qf[2 * i], qf[2 * i + 1]);
                        lds128((opq(ka[i >> 1]) ^ ((i & 1) << 6)) + 3072, f[i][0], f[i][1], f[i][2], f[i][3]);
                    }
                    __syncwarp();
                    half_load(xtile + 3072, &maps.kh, row0 + 6 * TS + 24 + AFTER(ALL6(f, 0)), xb, false);
#pragma unroll
                    for (int i = 0; i < 6; i++) mma16816v(cB, f[i][0], f[i][1], f[i][2], f[i][3], qf[2 * i], qf[2 * i + 1]);
                    sc2 = cA[0] + cA[3]; sc3 = cB[0] + cB[3];
                }
#pragma unroll
                for (int i = 0; i < 12; i++) qf[i] = mul2(qf[i], 0x6f806f80u);
                kr_scores(IC<0>(), sc0, sc1);
                kr_scores(IC<1>(), sc0, sc1);
                if (layer == 1) stage_v(IC<0>());
                kr_scores(IC<2>(), sc0, sc1);
                if (layer == 1) stage_v(IC<1>());
                kr_scores(IC<3>(), sc0, sc1);
                kr_scores(IC<4>(), sc2, sc3);
                {
                    LANE_IDS
                    const float sa = f_(lds32(kx + 8 + 4 * t)), sb = t == 0 ? f_(lds32(kx + 24)) : 1.0f;
                    const int nx = (int)lds32(kx);
                    uint32_t rm = lds32(kx + 4), qm = 0u;
#pragma unroll
                    for (int i = 0; i < 6; i++) qm = __vimax3_u16x2(qm, qf[2 * i] & 0x7fff7fffu, qf[2 * i + 1] & 0x7fff7fffu);
#pragma unroll
                    for (int i = 0; i < 3; i++) lds128(SM_QS + (2 * t + (g & 1)) * 48 + 16 * i, qf[4 * i], qf[4 * i + 1], qf[4 * i + 2], qf[4 * i + 3]);
                    if (__any_sync(0xffffffffu, max(qm & 0xffffu, qm >> 16) >= 0x7f80u)) rm = 31;
                    sc0 *= sa; sc1 *= sa; sc2 *= sb; sc3 *= sb;
                    if (nx) {
                        const uint32_t w = lds32(kx + 32 + 4 * (lane & 15));
                        const float d = bf_lo(lds16(SM_QS + ((w >> 15) & 0x1fe))) * bf_lo(w);
#pragma unroll 1
                        for (int n = 0; n < nx; n++) {
                            const uint32_t k = (__shfl_sync(0xffffffffu, w, n) >> 24) ^ lane;
                            const float dn = __shfl_sync(0xffffffffu, d, n);
                            if (k == 0) sc0 += dn;
                            if (k == 32) sc1 += dn;
                            if (k == 64) sc2 += dn;
                            if (k == 96) sc3 += dn;
                        }
                    }
#pragma unroll 1
                    for (; rm; rm &= rm - 1) {
                        const int tau = __ffs(rm) - 1;
#pragma unroll 1
                        for (int hf = 0; hf < 2; hf++) {
                            const char* gp = static_cast<const char*>(maps.kp) + (size_t)(row0 + tau * TS) * 128 + (8 * hf + (g >> 1) + 4 * (g & 1)) * 384 + 16 * t;
                            float cA[4] = {0.f, 0.f, 0.f, 0.f};
#pragma unroll
                            for (int i = 0; i < 6; i++) {
                                const uint4 a = __ldcg(reinterpret_cast<const uint4*>(gp + 64 * i));
                                mma16816(cA, a.x, a.y, a.z, a.w, qf[2 * i], qf[2 * i + 1]);
                            }
                            if ((tau & 3) == t) {
                                const int k = hf + (tau >> 2) * 2;
                                const float d = cA[0] + cA[3];
                                if (k == 0) sc0 = d; else if (k == 1) sc1 = d; else if (k == 2) sc2 = d; else sc3 = d;
                            }
                        }
                    }
                }
                if (layer == 0) {
                    LANE_IDS
#pragma unroll 1
                    for (int s = 5; s < 8; s++) {
                        mbar_wait(s == 5 ? xb : rb + (s & 1) * 8, s == 5);
                        const uint32_t tile = s == 5 ? bt : ring + (s & 1) * TILE;
                        float cA[4] = {0.f, 0.f, 0.f, 0.f}, cB[4] = {0.f, 0.f, 0.f, 0.f};
#pragma unroll
                        for (int i = 0; i < 6; i++) {
                            uint32_t a0, a1, a2, a3;
                            lds128(tile + K_OFF(i), a0, a1, a2, a3);
                            mma16816(cA, a0, a1, a2, a3, qf[2 * i], qf[2 * i + 1]);
                            lds128(tile + K_OFF(i) + 3072, a0, a1, a2, a3);
                            mma16816(cB, a0, a1, a2, a3, qf[2 * i], qf[2 * i + 1]);
                        }
                        if (t == (s & 3)) { sc2 = cA[0] + cA[3]; sc3 = cB[0] + cB[3]; }
                        __syncwarp();
                        refill1(s, AFTER(__float_as_uint(cA[0]) | __float_as_uint(cB[0])));
                    }
                } else {
                    LANE_IDS
#pragma unroll 1
                    for (int i = 2; i < 4; i++) {
                        const uint32_t tile = i == 3 ? ring : xtile, tb = i == 3 ? rb : xb;
                        mbar_wait(tb, 1);
#pragma unroll
                        for (int k = 0; k < 6; k++) {
                            const uint32_t a = tile + K_OFF(k);
                            lds128(a, kr[24 + k][0], kr[24 + k][1], kr[24 + k][2], kr[24 + k][3]);
                            lds128(a + 3072, kr[24 + 6 + k][0], kr[24 + 6 + k][1], kr[24 + 6 + k][2], kr[24 + 6 + k][3]);
                        }
                        float cA[4] = {0.f, 0.f, 0.f, 0.f}, cB[4] = {0.f, 0.f, 0.f, 0.f}, cC[4] = {0.f, 0.f, 0.f, 0.f}, cD[4] = {0.f, 0.f, 0.f, 0.f};
#pragma unroll
                        for (int k = 0; k < 3; k++) {
                            mma16816(cA, kr[24 + k][0], kr[24 + k][1], kr[24 + k][2], kr[24 + k][3], qf[2 * k], qf[2 * k + 1]);
                            mma16816(cB, kr[24 + 6 + k][0], kr[24 + 6 + k][1], kr[24 + 6 + k][2], kr[24 + 6 + k][3], qf[2 * k], qf[2 * k + 1]);
                            mma16816(cC, kr[24 + 3 + k][0], kr[24 + 3 + k][1], kr[24 + 3 + k][2], kr[24 + 3 + k][3], qf[6 + 2 * k], qf[7 + 2 * k]);
                            mma16816(cD, kr[24 + 9 + k][0], kr[24 + 9 + k][1], kr[24 + 9 + k][2], kr[24 + 9 + k][3], qf[6 + 2 * k], qf[7 + 2 * k]);
                        }
                        __syncwarp();
                        tile_load(tile, &maps.v, row0 + (i + 1) * TS + AFTER(__float_as_uint(cA[0]) | __float_as_uint(cB[0]) | __float_as_uint(cC[0]) | __float_as_uint(cD[0])), tb);
                        if (t == i) { sc2 = (cA[0] + cC[0]) + (cA[3] + cC[3]); sc3 = (cB[0] + cD[0]) + (cB[3] + cD[3]); }
                    }
                }
            }
            {
                const uint32_t mk = __reduce_max_sync(0xffffffffu, f2key(fmaxf(fmaxf(sc0, sc1), fmaxf(sc2, sc3))));
                if ((opq(tid) & 31) == 0) st_pkt2(&maps.scr->mx[h * 32 + c * 8 + wu], mk, tag);
                mw = key2f(mk);
            }
            pk0 = pack2(ex2((sc0 - mw) * SC), ex2((sc1 - mw) * SC));
            pk1 = pack2(ex2((sc2 - mw) * SC), ex2((sc3 - mw) * SC));
            sc2 = (bf_lo(pk0) + bf_hi(pk0)) + (bf_lo(pk1) + bf_hi(pk1));
#pragma unroll
            for (int o = 16; o > 0; o >>= 1) sc2 += __shfl_xor_sync(0xffffffffu, sc2, o);
#pragma unroll
            for (int s = 0; s < 3; s++) { acc[s][0] = acc[s][1] = acc[s][2] = acc[s][3] = 0.f; }
            auto head_ld = [&](int lane) { const uint2 mv = ld_pkt2(&maps.scr->mx[h * 32 + lane]); sc0 = f_(mv.x); sc1 = f_(mv.y); };
            auto head_factor = [&](int lane) {
                int it = 0;
                while (!__all_sync(0xffffffffu, __float_as_uint(sc1) == tag) && ++it < SPIN_CAP) head_ld(lane);
                sc3 = ex2((mw - key2f(__reduce_max_sync(0xffffffffu, __float_as_uint(sc0)))) * SC);
            };
#define P_CONSTS \
                const uint32_t sel0 = g == 0 ? 0x4410u : (g == 1 ? 0x1044u : 0x4444u); \
                const uint32_t sel1 = g == 2 ? 0x4410u : (g == 3 ? 0x1044u : 0x4444u); \
                const int src00 = 4 * (t < 2 ? 4 * t : 4 * (t - 2) + 1);
#define P_FRAGS(tau) \
                const uint32_t pk = ((tau) & 4) ? pk1 : pk0; \
                const uint32_t w0 = __shfl_sync(0xffffffffu, pk, src00 + ((tau) & 3)); \
                const uint32_t w1 = __shfl_sync(0xffffffffu, pk, src00 + ((tau) & 3) + 8); \
                uint32_t pb[4][2]; \
                _Pragma("unroll") for (int j = 0; j < 4; j++) { \
                    const uint32_t src = ((j & 1) ? w1 : w0) >> ((j >> 1) * 16); \
                    pb[j][0] = __byte_perm(src, 0, sel0); pb[j][1] = __byte_perm(src, 0, sel1); \
                }
            if (layer == 0) {
#pragma unroll 1
                for (int s = 8; s < 16; s++) {
                    LANE_IDS
                    P_CONSTS
                    if (s == 14) {
                        uint4* p = nullptr;
                        if (tl < 48) p = &maps.scr->qx[b * 48 + tl];
                        else if (tl < 98) p = &maps.scr->cx[b * 56 + tl - 48];
                        else if (tl < 145) {}
                        else if (tl >= 160) { if (tl < 208) p = &maps.scr->qc[b * 48 + tl - 160]; }
                        else if (b < NG) { if (tl < 153) p = &maps.scr->ah[b * 8 + tl - 145]; }
                        else if (b < DN0 + NDN && tl < 149) p = &maps.scr->ay[(b - DN0) * 4 + tl - 145];
                        if (p) st_pkt(p, 0, 0, 0, tl < 48);
                    }
                    if (s == 13) head_ld(lane);
                    P_FRAGS((s + 2) & 7)
                    mbar_wait(rb + (s & 1) * 8, ((s >> 1) + 1) & 1);
                    const uint32_t tile = ring + (s & 1) * TILE;
#pragma unroll
                    for (int j = 0; j < 4; j++) {
#pragma unroll
                        for (int u = 0; u < 3; u++) {
                            uint32_t a0, a1, a2, a3;
                            lds128(tile + (j >> 1) * 3072 + V_OFF(3 * (j & 1) + u), a0, a1, a2, a3);
                            mma16816(acc[u], a0, a1, a2, a3, pb[j][0], pb[j][1]);
                        }
                    }
                    __syncwarp();
                    if (s == 12 || s == 13) __syncthreads();
                    if (s < 14) refill1(s, AFTER(__float_as_uint(acc[0][0]) | __float_as_uint(acc[1][0]) | __float_as_uint(acc[2][0])), true);
                    if (s == 13) head_factor(lane);
                    if (s == 15 && elect_one()) {
                        uint32_t n;
                        asm volatile("atom.shared.add.u32 %0, [%1], 1;" : "=r"(n) : "r"(SM_MISC + 8) : "memory");
                        if (n == 7) load_wo(maps, SM_B, h, c, WBAR, 5);
                    }
                }
            } else {
                LANE_IDS
                P_CONSTS
#pragma unroll
                for (int s = 0; s < 2; s++) {
                    P_FRAGS(s)
#pragma unroll
                    for (int j = 0; j < 4; j++) {
#pragma unroll
                        for (int u = 0; u < 3; u++) {
                            const int k = 6 * (j >> 1) + 3 * (j & 1) + u;
                            mma16816(acc[u], kr[12 * s + k][0], kr[12 * s + k][1], kr[12 * s + k][2], kr[12 * s + k][3], pb[j][0], pb[j][1]);
                        }
                    }
                }
#pragma unroll 1
                for (int i = 4; i < 10; i++) {
                    const int sl = i == 5 ? 0 : (i == 6 || i == 8 ? 1 : 2);
                    const uint32_t tile = sl ? ring + (sl - 1) * TILE : xtile, tb = sl ? rb + (sl - 1) * 8 : xb;
                    if (i == 8) head_ld(lane);
                    if (i == 9) head_factor(lane);
                    P_FRAGS(i - 2)
                    mbar_wait(tb, (0x310 >> i) & 1);
#pragma unroll
                    for (int k = 0; k < 6; k++) {
                        const uint32_t a = tile + V_OFF(k);
                        lds128(a, kr[24 + k][0], kr[24 + k][1], kr[24 + k][2], kr[24 + k][3]);
                        lds128(a + 3072, kr[24 + 6 + k][0], kr[24 + 6 + k][1], kr[24 + 6 + k][2], kr[24 + 6 + k][3]);
                    }
#pragma unroll
                    for (int j = 0; j < 4; j++) {
#pragma unroll
                        for (int u = 0; u < 3; u++) {
                            const int k = 6 * (j >> 1) + 3 * (j & 1) + u;
                            mma16816(acc[u], kr[24 + k][0], kr[24 + k][1], kr[24 + k][2], kr[24 + k][3], pb[j][0], pb[j][1]);
                        }
                    }
                    __syncwarp();
                    if (wu < L1R && i == 6 - 2 * (wu & 1)) tile_load_l1(tile, maps.vp, row0 + (6 - (wu & 1)) * TS, tb, lane);
                    else if (i == 4 || i == 6 || i == 7) tile_load(tile, &maps.v, row0 + (i == 4 ? 5 : i) * TS + AFTER(__float_as_uint(acc[0][0]) | __float_as_uint(acc[1][0]) | __float_as_uint(acc[2][0])), tb);
                    if (i == 7 && role < DN0 + NDN && elect_one()) {
                        uint32_t n;
                        asm volatile("atom.shared.add.u32 %0, [%1], 1;" : "=r"(n) : "r"(SM_MISC + 8) : "memory");
                        if (n == 15) load_wo(maps, SM_Q, h, c, WBAR, 3);
                    }
                }
            }
#undef P_FRAGS
#undef P_CONSTS
#undef LANE_IDS
#undef K_OFF
#undef V_OFF
        }

        uint32_t ticket = 0;
        {
            const int tl = opq(tid), warp = tl >> 5, lane = tl & 31, g = lane >> 2, t = lane & 3, mat = lane >> 3, r8 = lane & 7;
            {
                const uint32_t d = SM_R + 4 * (warp * 196 + 8 * g + 4 * t);
                if (t < 2) {
#pragma unroll
                    for (int u = 0; u < 3; u++) sts128(d + 256 * u, acc[u][0] * sc3, acc[u][1] * sc3, acc[u][2] * sc3, acc[u][3] * sc3);
                }
                if (lane == 0) sts128(d + 768, sc2 * sc3, 0.f, 0.f, 0.f);
            }
            const int tc = min(tl, 48);
            uint4* pc = opq(&maps.scr->cx[h * 4 * 56 + tc]);
            uint4* po = pc + c * 56;
            const uint32_t fa = opq(SM_R + 16 * tc);
            __syncthreads();
            const int kg = warp >> 1, mg = warp & 1;
            const bool wo2 = layer && role < DN0 + NDN;
            const bool wo4 = layer && role < NG;
            uint32_t aw, oa, ob0, dw;
            uint32_t* tk;
            auto addrs = [&]() {
                aw = opq((wo2 ? SM_Q : SM_B) + (48 * kg + (mat >> 1) * 8 + r8) * 64 + (((2 * mg + (mat & 1)) ^ ((r8 >> 1) & 3)) << 4));
                oa = opq(SM_OS + 96 * kg + 8 * t);
                ob0 = opq(oa + 8 * t);
                dw = opq(SM_R + 4 * (4 * (16 * mg + g) + kg));
                tk = maps.scr->ticket;
            };
            uint32_t a[2][3][4];
            auto preload = [&]() {
#pragma unroll
                for (int i = 0; i < 2; i++) {
                    mbar_wait(WBAR + 8 * i, wo2);
#pragma unroll
                    for (int ks = 0; ks < 3; ks++) ldsm4t(aw + i * 12288 + ks * 1024, a[i][ks]);
                }
            };
            if (wu < 2) {
                if (tl < 49) {
                    float4 v[8];
#pragma unroll
                    for (int w = 0; w < 8; w++) v[w] = lds128f(fa + w * 784);
                    st_pktf(po, ((v[0].x + v[1].x) + (v[2].x + v[3].x)) + ((v[4].x + v[5].x) + (v[6].x + v[7].x)),
                            ((v[0].y + v[1].y) + (v[2].y + v[3].y)) + ((v[4].y + v[5].y) + (v[6].y + v[7].y)),
                            ((v[0].z + v[1].z) + (v[2].z + v[3].z)) + ((v[4].z + v[5].z) + (v[6].z + v[7].z)),
                            ((v[0].w + v[1].w) + (v[2].w + v[3].w)) + ((v[4].w + v[5].w) + (v[6].w + v[7].w)), tbit);
                }
                __syncwarp();
                uint4 v[4];
#pragma unroll
                for (int k = 0; k < 4; k++) v[k] = ld_pkt(pc + k * 56);
                asm volatile("bar.arrive 1, 256;" ::: "memory");
                addrs();
                const int w = 2 * tc, k3 = w / 24, r = w - 24 * k3;
                const uint32_t d0 = opq(tl < 48 ? SM_OS + 4 * (24 * k3 + (r < 16 ? 4 * (r & 3) + (r >> 2) : 16 + 2 * (r & 3) + ((r >> 2) & 1))) : SM_MISC);
                const uint32_t d1 = opq(tl < 48 ? d0 + (r < 16 ? 16 : 8) : SM_MISC + 12);
                int it = 0;
                bool more = true;
                while (__any_sync(0xffffffffu, ((v[0].w ^ tbit) | (v[1].w ^ tbit) | (v[2].w ^ tbit) | (v[3].w ^ tbit)) & 1) && more) {
#pragma unroll
                    for (int k = 0; k < 4; k++) v[k] = ld_pkt(pc + k * 56);
                    more = ++it < SPIN_CAP;
                }
                const float o0 = (f_(v[0].x) + f_(v[1].x)) + (f_(v[2].x) + f_(v[3].x));
                const uint32_t w0 = pack2(o0, (f_(v[0].y) + f_(v[1].y)) + (f_(v[2].y) + f_(v[3].y)));
                sts32(d1, pack2((f_(v[0].z) + f_(v[1].z)) + (f_(v[2].z) + f_(v[3].z)), (f_(v[0].w) + f_(v[1].w)) + (f_(v[2].w) + f_(v[3].w))));
                sts32(d0, tl < 48 ? w0 : __float_as_uint(o0));
                asm volatile("bar.arrive 2, 256;" ::: "memory");
                preload();
                asm volatile("bar.sync 3, 64;" ::: "memory");
            } else {
                addrs();
                asm volatile("bar.sync 1, 256;" ::: "memory");
                preload();
                asm volatile("bar.sync 2, 256;" ::: "memory");
            }
            uint32_t ob[6];
            lds128(ob0, ob[0], ob[1], ob[2], ob[3]);
            lds64(oa + 64, ob[4], ob[5]);
            if (tl == 224 && layer == 0)
                asm volatile("atom.relaxed.gpu.global.inc.u32 %0, [%1], 0x7fffffff;" : "=r"(ticket) : "l"(tk) : "memory");
            auto put = [&](int i, const float (&cc)[4]) { if (t == 0) { sts32(dw + 512 * i, cc[0]); sts32(dw + 512 * i + 128, cc[2]); } };
            {
                float c0[4] = {0.f, 0.f, 0.f, 0.f}, c1[4] = {0.f, 0.f, 0.f, 0.f}, c2[4] = {0.f, 0.f, 0.f, 0.f}, c3[4] = {0.f, 0.f, 0.f, 0.f};
                mbar_wait(WBAR + 16, wo2);
#pragma unroll
                for (int ks = 0; ks < 3; ks++) {
                    mma16816v(c0, a[0][ks][0], a[0][ks][1], a[0][ks][2], a[0][ks][3], ob[2 * ks], ob[2 * ks + 1]);
                    mma16816v(c1, a[1][ks][0], a[1][ks][1], a[1][ks][2], a[1][ks][3], ob[2 * ks], ob[2 * ks + 1]);
                    if (ks == 0 && layer == 0) {
                        mbar_wait(WBAR + 24, 0);
#pragma unroll
                        for (int k = 0; k < 3; k++) ldsm4t(aw + 3 * 12288 + k * 1024, wk[k]);
                    }
                    if (ks == 1) mbar_wait(WBAR + 32, wo4);
                    ldsm4t(aw + 2 * 12288 + ks * 1024, a[0][ks]);
                }
                const uint32_t aw4 = aw + (wo2 && !wo4 ? SM_B - SM_Q : 0) + 4 * 12288;
                ldsm4t(aw4 + 1024, a[1][0]);
#pragma unroll
                for (int ks = 0; ks < 3; ks++) {
                    mma16816v(c2, a[0][ks][0], a[0][ks][1], a[0][ks][2], a[0][ks][3], ob[2 * ks], ob[2 * ks + 1]);
                    mma16816v(c3, wk[ks][0], wk[ks][1], wk[ks][2], wk[ks][3], ob[2 * ks], ob[2 * ks + 1]);
                    if (ks == 0) { ldsm4t(aw4, a[0][0]); put(0, c0); put(1, c1); }
                    if (ks == 1) ldsm4t(aw4 + 2048, a[0][1]);
                }
                float c4[4] = {0.f, 0.f, 0.f, 0.f}, c5[4] = {0.f, 0.f, 0.f, 0.f};
                mma16816v(c4, a[0][0][0], a[0][0][1], a[0][0][2], a[0][0][3], ob[0], ob[1]);
                mma16816v(c5, a[1][0][0], a[1][0][1], a[1][0][2], a[1][0][3], ob[2], ob[3]);
                mma16816v(c4, a[0][1][0], a[0][1][1], a[0][1][2], a[0][1][3], ob[4], ob[5]);
                put(2, c2); put(3, c3);
                c4[0] += c5[0]; c4[2] += c5[2];
                put(4, c4);
            }
        }
        {
            const int tl = opq(tid);
            uint4* pr = opq(&maps.scr->acc[layer][54 * c + min(tl, 53)]);
            const uint32_t fa = opq(SM_R + 48 * tl);
            const float il = rcp(f_(lds32(SM_MISC)));
            __syncthreads();
            if (tl < 54) {
                const float4 v0 = lds128f(fa), v1 = lds128f(fa + 16), v2 = lds128f(fa + 32);
                const float y0 = il * ((v0.x + v0.y) + (v0.z + v0.w)), y1 = il * ((v1.x + v1.y) + (v1.z + v1.w)), y2 = il * ((v2.x + v2.y) + (v2.z + v2.w));
                red_pkt(pr, y0, tl == 53 ? 0.f : y1, tl == 53 ? 0.f : y2);
            }
            if (tl == 224 && layer == 0) {
                sts32(SM_MISC + 4, ticket);
                if (ticket < NG) load_ffn(maps, ticket, SM_B, FBAR);
            }
        }
        __syncthreads();
        if (layer == 0) role = __shfl_sync(0xffffffffu, (int)lds32(SM_MISC + 4), 0);
        const uint32_t DONE32 = 0x42000000u;
        if (role < NG) {
            const int tl = opq(tid), warp = tl >> 5, lane = tl & 31, g = lane >> 2, t = lane & 3, mat = lane >> 3, r8 = lane & 7;
            const uint32_t ag = SM_B + (80 * warp + (mat >> 1) * 8 + r8) * 96 + (((mat & 1) ^ (r8 >> 2)) << 4);
            constexpr int GI = 32, GK = 16 * 96;
            const bool on = (g & 1) == (t >> 1), isx = (on && g < 2) || g == 4;
            const uint32_t pm = opq(isx ? SM_XS + 160 * warp + 16 * t : (on || g == 5 ? SM_ONE : SM_ZERO)), pm2 = opq(pm + 128 - (isx ? 8 * t : 0));
            const uint32_t dg = opq(SM_R + 4 * (2 * (warp * 48 + g) + t));
            const uint32_t ho = opq(16u * (role * 8 + 4 * warp + ((lane * 11) >> 5)));
            const uint32_t fa = opq(SM_R + 8 * (24 * warp + 2 * min(lane, 11)));
            uint32_t pre[9][4];
            {
                bool hx = wu == 7;
                int it = 0;
                const uint4* px = opq(&maps.scr->acc[layer][min(tl, 215)]);
                const int cq = tl / 54, r = tl - 54 * cq, k0 = min(160 * cq + 3 * r, DM - 1);
                const uint32_t w0 = SM_XS + 4 * xpos(k0 >> 1), w1 = SM_XS + 4 * xpos(min((k0 >> 1) + 1, DM / 2 - 1));
                const bool two = tl < 216 && r != 53;
                const uint32_t e0 = opq(tl < 216 ? w0 + 2 * (k0 & 1) : SM_MISC + 12);
                const uint32_t e1 = opq(two ? ((k0 & 1) ? w1 : w0 + 2) : SM_MISC + 12), e2 = opq(two ? w1 + 2 * (k0 & 1) : SM_MISC + 12);
                const uint32_t x01 = opq(lds16(e0) | (lds16(e1) << 16)), x2 = lds16(e2);
                auto take_x = [&](const uint4 v) {
                    if (__all_sync(0xffffffffu, v.w == DONE32)) {
                        hx = true;
                        const uint32_t y01 = add2(x01, pack2(f_(v.x), f_(v.y))), y2 = add2(x2, pack2(f_(v.z), 0.f));
                        sts16(e0, y01); sts16(e1, y01 >> 16); sts16(e2, y2);
                    }
                };
                while (!mbar_test(FBAR, 0) && ++it < SPIN_CAP) { if (!hx) take_x(ld_pkt(px + awake(it, maps.zero))); else it += awake(it, maps.zero); }
                uint4 v = make_uint4(0u, 0u, 0u, 0u);
                if (!hx) v = ld_pkt(px);
#pragma unroll
                for (int n = 0; n < 9; n++) ldsm4t(ag + (n % 3) * GI + (n / 3) * GK, pre[n]);
                if (layer) {
#pragma unroll
                    for (int n = 9; n < 15; n++) ldsm4t(ag + (n % 3) * GI + (n / 3) * GK, kr[n - 9]);
                }
                if (!hx) {
                    bool more = true;
                    while (!__all_sync(0xffffffffu, v.w == DONE32) && more) { v = ld_pkt(px + awake(it, maps.zero)); more = ++it < SPIN_CAP; }
                    const uint32_t y01 = add2(x01, pack2(f_(v.x), f_(v.y))), y2 = add2(x2, pack2(f_(v.z), 0.f));
                    sts16(e0, y01); sts16(e1, y01 >> 16); sts16(e2, y2);
                }
            }
            __syncthreads();
            {
                float cc[3][4], gr[4];
                if (layer) gemv15r(cc, gr, pre, kr, pm, pm2);
                else gemv15<GK, true>(cc, gr, pre, [&](int i) { return ag + i * GI; }, pm, pm2);
                if (t < 2) {
#pragma unroll
                    for (int i = 0; i < 3; i++) { sts32(dg + 128 * i, cc[i][0] + cc[i][3]); sts32(dg + 128 * i + 64, cc[i][1] + cc[i][2]); }
                }
                if ((lane | 4) == 22) sts32(SM_ST + 8 * warp + (g & 1) * 4, gr[0]);
            }
            uint4* ph = reinterpret_cast<uint4*>(reinterpret_cast<char*>(maps.scr->ah) + ho);
            const bool snd = (0x249 >> lane) & 1;
            __syncthreads();
            if (wu < 2) {
                float mean, inv;
                float4 v[8];
#pragma unroll
                for (int w = 0; w < 8; w++) v[w] = lds128f(fa + w * 384);
                ln_stats(mean, inv);
                const float ga = inv * ((((v[0].x + v[1].x) + (v[2].x + v[3].x)) + ((v[4].x + v[5].x) + (v[6].x + v[7].x))) -
                                        mean * (((v[0].y + v[1].y) + (v[2].y + v[3].y)) + ((v[4].y + v[5].y) + (v[6].y + v[7].y))));
                const float gb = inv * ((((v[0].z + v[1].z) + (v[2].z + v[3].z)) + ((v[4].z + v[5].z) + (v[6].z + v[7].z))) -
                                        mean * (((v[0].w + v[1].w) + (v[2].w + v[3].w)) + ((v[4].w + v[5].w) + (v[6].w + v[7].w))));
                uint32_t wd = pack2(ga, gb);
                if (role < NG / 2) {
                    const float g0 = bf_lo(wd), g1 = bf_hi(wd);
                    wd = pack2(g0 * rcp(1.0f + ex2(-1.4426950408889634f * g0)), g1 * rcp(1.0f + ex2(-1.4426950408889634f * g1)));
                }
                const uint32_t wa = __shfl_down_sync(0xffffffffu, wd, 1), wb = __shfl_down_sync(0xffffffffu, wd, 2);
                if (snd) st_pkt(ph, wd, wa, wb, tag);
            }
            __syncthreads();
        } else if (role < DN0 + NDN) {
            const int j = role - DN0;
            const int tl = opq(tid), warp = tl >> 5, lane = tl & 31, g = lane >> 2, t = lane & 3, mat = lane >> 3, r8 = lane & 7;
            float xr0 = 0.f, xr1 = 0.f;
            if (wu == 0) {
                const int col = 16 * j + (lane & 15), cc = col / 160, r = col - 160 * cc, e = r % 3;
                const uint4* px = &maps.scr->acc[layer][(54 * cc + r / 3)];
                const float x0 = bf_lo(lds16(SM_XS + 4 * xpos(col >> 1) + 2 * (col & 1)));
                uint4 v;
                int it = 0;
                bool ld = layer == 0;
                do {
                    v = ld_pkt(px);
                    if (ld && f_(__shfl_sync(0xffffffffu, v.w, 0)) >= (float)DNTH) { ld = false; if (lane == 0) load_ffn(maps, role, SM_B, FBAR); }
                } while (!__all_sync(0xffffffffu, v.w == DONE32) && ++it < SPIN_CAP);
                if (ld && lane == 0) load_ffn(maps, role, SM_B, FBAR);
                const float xres = bfr(x0 + bfr(f_(e == 0 ? v.x : (e == 1 ? v.y : v.z))));
                xr0 = __shfl_sync(0xffffffffu, xres, 2 * (lane & 7));
                xr1 = __shfl_sync(0xffffffffu, xres, 2 * (lane & 7) + 1);
            }
            const uint32_t ad = SM_B + (192 * warp + (mat >> 1) * 8 + r8) * 32 + (((mat & 1) ^ (r8 >> 2)) << 4);
            const uint32_t hs = SM_R + 384 * warp, hb = opq(hs + 16 * t), dd = opq(SM_R + 3072 + 4 * (warp * 16 + g));
            uint32_t pre[NPRE][4];
            uint32_t pos[3];
#pragma unroll
            for (int i = 0; i < 3; i++) { const int w = 3 * lane + i; pos[i] = opq(hs + 4 * ((w & ~15) + 4 * (w & 3) + ((w >> 2) & 1) + ((w >> 2) & 2))); }
            const uint4* ph = opq(&maps.scr->ah[tl]);
            const uint32_t fa = opq(SM_R + 3072 + 8 * (lane & 7));
            uint2* py = opq(reinterpret_cast<uint2*>(maps.scr->ay) + 8 * j + (lane & 7));
            uint32_t* po = opq(reinterpret_cast<uint32_t*>(out) + 8 * j + (lane & 7));
            mbar_wait(FBAR, 0);
#pragma unroll
            for (int n = 0; n < NPRE; n++) ldsm4t(ad + n * 512, pre[n]);
            {
                uint4 v, u;
                int it = 0;
                bool more;
                do { const uint4* p2 = ph + awake(it, maps.zero); v = ld_pkt(p2); u = ld_pkt(p2 + 256); more = ++it < SPIN_CAP; }
                while (!__all_sync(0xffffffffu, v.w == tag && u.w == tag) && more);
                sts32(pos[0], mul2(v.x, u.x)); sts32(pos[1], mul2(v.y, u.y)); sts32(pos[2], mul2(v.z, u.z));
            }
            __syncwarp();
            {
                float cc[4][4];
                uint32_t hv[3][4];
#pragma unroll
                for (int jj = 0; jj < 3; jj++) lds128(hb + 64 * jj, hv[jj][0], hv[jj][1], hv[jj][2], hv[jj][3]);
#pragma unroll
                for (int n = 0; n < 12; n++) {
                    const int s = n < NPRE ? n : n - NPRE;
                    if (n < 4) cc[n][0] = cc[n][1] = cc[n][2] = cc[n][3] = 0.f;
                    mma16816v(cc[n & 3], pre[s][0], pre[s][1], pre[s][2], pre[s][3], hv[(n >> 1) % 3][2 * (n & 1)], hv[(n >> 1) % 3][2 * (n & 1) + 1]);
                    if (n + NPRE < 12) ldsm4t(ad + (n + NPRE) * 512, pre[n]);
                    if ((n & 1) && n < 6) lds128(hb + 64 * ((n >> 1) + 3), hv[n >> 1][0], hv[n >> 1][1], hv[n >> 1][2], hv[n >> 1][3]);
                }
                if (t == 0) { sts32(dd, (cc[0][0] + cc[1][0]) + (cc[2][0] + cc[3][0])); sts32(dd + 32, (cc[0][2] + cc[1][2]) + (cc[2][2] + cc[3][2])); }
            }
            __syncthreads();
            if (tl < 8) {
                float2 v[8];
#pragma unroll
                for (int w = 0; w < 8; w++) v[w] = lds64f(fa + 64 * w);
                const uint32_t y = pack2(((v[0].x + v[1].x) + (v[2].x + v[3].x)) + ((v[4].x + v[5].x) + (v[6].x + v[7].x)),
                                         ((v[0].y + v[1].y) + (v[2].y + v[3].y)) + ((v[4].y + v[5].y) + (v[6].y + v[7].y)));
                const uint32_t wd = pack2(xr0 + bf_lo(y), xr1 + bf_hi(y));
                if (layer) asm volatile("st.global.u32 [%0], %1;" ::"l"(po), "r"(wd) : "memory");
                st_pkt2(py, wd, tag);
            }
            __syncthreads();
        }
    }
}

typedef CUresult (*EncodeFn)(CUtensorMap*, CUtensorMapDataType, cuuint32_t, void*, const cuuint64_t*, const cuuint64_t*, const cuuint32_t*,
                             const cuuint32_t*, CUtensorMapInterleave, CUtensorMapSwizzle, CUtensorMapL2promotion, CUtensorMapFloatOOBfill);

void make_map(EncodeFn enc, CUtensorMap* m, const void* base, int rank, uint64_t d0, uint64_t d1, uint64_t d2, uint64_t s1, uint64_t s2,
              uint32_t b0, uint32_t b1, uint32_t b2, CUtensorMapSwizzle sw, CUtensorMapL2promotion pr = CU_TENSOR_MAP_L2_PROMOTION_NONE) {
    cuuint64_t dims[3] = {d0, d1, d2};
    cuuint64_t strides[2] = {s1, s2};
    cuuint32_t box[3] = {b0, b1, b2};
    cuuint32_t es[3] = {1, 1, 1};
    enc(m, CU_TENSOR_MAP_DATA_TYPE_BFLOAT16, rank, const_cast<void*>(base), dims, strides, box, es, CU_TENSOR_MAP_INTERLEAVE_NONE, sw,
        pr, CU_TENSOR_MAP_FLOAT_OOB_FILL_NONE);
}

}

extern "C" void kernel_launch(void* const* d_in, const int* in_sizes, int n_in, void* d_out, int out_size) {
    (void)in_sizes; (void)n_in; (void)out_size;
    static EncodeFn enc = nullptr;
    static Scratch* scr = nullptr;
    if (!enc) {
        void* fn = nullptr;
        cudaDriverEntryPointQueryResult qr;
        cudaGetDriverEntryPoint("cuTensorMapEncodeTiled", &fn, cudaEnableDefault, &qr);
        enc = reinterpret_cast<EncodeFn>(fn);
        cudaGetSymbolAddress(reinterpret_cast<void**>(&scr), g_scr);
        cudaFuncSetAttribute(decode_kernel, cudaFuncAttributeMaxDynamicSharedMemorySize, SM_TOTAL);
    }
    Maps maps;
    make_map(enc, &maps.k, d_in[1], 2, 64, (uint64_t)NH * SK * 3, 1, 128, 0, 64, 48, 1, CU_TENSOR_MAP_SWIZZLE_128B);
    make_map(enc, &maps.v, d_in[2], 2, 64, (uint64_t)NH * SK * 3, 1, 128, 0, 64, 48, 1, CU_TENSOR_MAP_SWIZZLE_128B);
    {
        cuuint64_t dims[5] = {64, 16, NH * DH / 64, DM / 80, 5};
        cuuint64_t strides[4] = {NH * DH * 2, 128, 80 * NH * DH * 2, 16 * NH * DH * 2};
        cuuint32_t box[5] = {64, 16, 3, 2, 5};
        cuuint32_t es[5] = {1, 1, 1, 1, 1};
        enc(&maps.wq, CU_TENSOR_MAP_DATA_TYPE_BFLOAT16, 5, d_in[3], dims, strides, box, es, CU_TENSOR_MAP_INTERLEAVE_NONE, CU_TENSOR_MAP_SWIZZLE_128B,
            CU_TENSOR_MAP_L2_PROMOTION_NONE, CU_TENSOR_MAP_FLOAT_OOB_FILL_NONE);
    }
    make_map(enc, &maps.wo, d_in[4], 3, 32, NH * DH, DM / 32, DM * 2, 64, 32, 192, 1, CU_TENSOR_MAP_SWIZZLE_64B);
    constexpr int GW = 48;
    make_map(enc, &maps.w1, d_in[6], 3, FF, 160, 4, FF * 2, 160 * FF * 2, GW, 160, 4, CU_TENSOR_MAP_SWIZZLE_NONE);
    make_map(enc, &maps.w3, d_in[7], 3, FF, 160, 4, FF * 2, 160 * FF * 2, GW, 160, 4, CU_TENSOR_MAP_SWIZZLE_NONE);
    make_map(enc, &maps.w2, d_in[8], 3, DM, 256, 6, DM * 2, 256 * DM * 2, 16, 256, 6, CU_TENSOR_MAP_SWIZZLE_32B);
    make_map(enc, &maps.ks, d_in[1], 2, 64, (uint64_t)NH * SK * 3, 1, 128, 0, 16, 48, 1, CU_TENSOR_MAP_SWIZZLE_NONE);
    make_map(enc, &maps.vs, d_in[2], 2, 64, (uint64_t)NH * SK * 3, 1, 128, 0, 16, 48, 1, CU_TENSOR_MAP_SWIZZLE_NONE);
    make_map(enc, &maps.kh, d_in[1], 2, 64, (uint64_t)NH * SK * 3, 1, 128, 0, 64, 24, 1, CU_TENSOR_MAP_SWIZZLE_128B);
    maps.kp = d_in[1];
    maps.vp = d_in[2];
    maps.scr = scr;
    maps.zero = 0;
    const uint32_t rt[8] = {0x2EE0, 0x35E0, 0x2EE0, 0x35E0, 0x36E0, 0x35E0, 0x36E0, 0x35E0};
    for (int i = 0; i < 8; i++) maps.rt[i] = rt[i];
    decode_kernel<<<NCTA, NT, SM_TOTAL, cudaStreamPerThread>>>(maps, (const __nv_bfloat16*)d_in[0], (__nv_bfloat16*)d_out);
}
```
